```python
import torch

def _softmax(x, axis=-1):
    return torch.softmax(x, dim=axis)
def _gelu(x):
    return torch.nn.functional.gelu(x, approximate="tanh")
def _silu(x):
    return torch.nn.functional.silu(x)
def _sigmoid(x):
    return torch.sigmoid(x)
def _layernorm(x, axis=-1, eps=1e-5):
    m = x.mean(dim=axis, keepdim=True)
    v = x.var(dim=axis, keepdim=True, unbiased=False)
    return (x - m) / torch.sqrt(v + eps)
def _scatter_add(tgt, idx, src, axis=0):
    return tgt.clone().index_add_(axis, idx, src)
def _segment_sum(src, seg, n):
    out = torch.zeros((n,) + src.shape[1:], dtype=src.dtype)
    return out.index_add_(0, seg, src)
def _pad(x, pw):
    flat = tuple(v for pair in reversed(pw) for v in pair)
    return torch.nn.functional.pad(x, flat)

kernel_name = 'concat_heads__ssm_conv_h3__compressed_kv_cla__prompt'

def setup_inputs():

    _w = (lambda a: (lambda t: t.to(torch.bfloat16) if t.is_floating_point() else t)(torch.as_tensor(a)))
    def _A_setup():
        B, S, D = 1, 2048, 448
        ks = 4
        return {
            "q": _w((lambda *s: torch.randn(*s, dtype=torch.bfloat16) * 0.05)(B, S, D)),
            "k": _w((lambda *s: torch.randn(*s, dtype=torch.bfloat16) * 0.1)(B, S, D)),
            "v": _w((lambda *s: torch.randn(*s, dtype=torch.bfloat16) * 0.1)(B, S, D)),
            "shift_k": _w((lambda *s: torch.randn(*s, dtype=torch.bfloat16) * 0.1)(D, ks) * 0.5),
            "ssm_k": _w((lambda *s: torch.randn(*s, dtype=torch.bfloat16) * 0.1)(D, S) * (1.0 / S ** 0.5)),
            "ssm_D": _w((lambda *s: torch.randn(*s, dtype=torch.bfloat16) * 0.1)(D)),
        }
    _A_in = _A_setup()

    def _B_setup():
        B, H, Sq, Sk, D, M = 1, 16, 2048, 2048, 256, 448
        Dc = 4 * D
        return {
            "x": _w((lambda *s: torch.randn(*s, dtype=torch.bfloat16) * 3.2)(B, Sq, M)),
            "c_kv": _w((lambda *s: torch.randn(*s, dtype=torch.bfloat16) * 0.05)(B, Sk, Dc)),
            "w_q": _w((lambda *s: torch.randn(*s, dtype=torch.bfloat16) * 3.2)(M, H, D) * (M ** -0.5)),
            "w_uk": _w((lambda *s: torch.randn(*s, dtype=torch.bfloat16) * 3.2)(Dc, H, D) * (Dc ** -0.5)),
            "w_uv": _w((lambda *s: torch.randn(*s, dtype=torch.bfloat16) * 0.05)(Dc, H, D) * (Dc ** -0.5)),
            "w_o": _w((lambda *s: torch.randn(*s, dtype=torch.bfloat16) * 0.05)(H, D, M) * ((H * D) ** -0.5)),
        }
    _B_in = _B_setup()

    return {
        "A_q": _A_in["q"],
        "A_k": _A_in["k"],
        "A_v": _A_in["v"],
        "A_shift_k": _A_in["shift_k"],
        "A_ssm_k": _A_in["ssm_k"],
        "A_ssm_D": _A_in["ssm_D"],
        "B_x": _B_in["x"],
        "B_c_kv": _B_in["c_kv"],
        "B_w_q": _B_in["w_q"],
        "B_w_uk": _B_in["w_uk"],
        "B_w_uv": _B_in["w_uv"],
        "B_w_o": _B_in["w_o"],
    }

def reference(A_q, A_k, A_v, A_shift_k, A_ssm_k, A_ssm_D, B_x, B_c_kv, B_w_q, B_w_uk, B_w_uv, B_w_o):
    def _A_ref(q, k, v, shift_k, ssm_k, ssm_D):
        B, S, D = q.shape
        ks = shift_k.shape[-1]
        k_pad = _pad(k, ((0, 0), (ks - 1, 0), (0, 0)))
        k_shift = torch.zeros_like(k)
        for t in range(ks):
            k_shift = k_shift + k_pad[:, t:t + S, :] * shift_k[:, ks - 1 - t][None, None, :]
        kv = k_shift * v
        L = 2 * S
        kv_pad = _pad(kv, ((0, 0), (0, S), (0, 0)))
        kf_pad = _pad(ssm_k, ((0, 0), (0, S)))
        kv_f = (lambda x, axes=(-2,-1): torch.fft.rfft2(x.float(), dim=axes))(kv_pad[:, None, :, :], axes=(1, 2))
        kf_f = (lambda x, axes=(-2,-1): torch.fft.rfft2(x.float(), dim=axes))(kf_pad[:, None, :], axes=(1, 2))
        kf_f = (lambda x, *d: x.permute(*d))(kf_f, 1, 2, 0)
        y_f = kv_f * kf_f[None, :, :, :]
        y = (lambda x, s, axes=(-2,-1): torch.fft.irfft2(x, s=s, dim=axes).to(torch.bfloat16))(y_f, (1, L), axes=(1, 2))[:, 0, :S, :]
        y = y + kv * ssm_D[None, None, :]
        return q * y

    def _B_ref(x, c_kv, w_q, w_uk, w_uv, w_o):
        B, Sq, M = x.shape[0], x.shape[1], x.shape[2]
        Sk = c_kv.shape[1]
        H, D = w_q.shape[1], w_q.shape[2]
        q = torch.einsum("bqm,mhd->bhqd", x, w_q)
        k = torch.einsum("bkc,chd->bhkd", c_kv, w_uk)
        v = torch.einsum("bkc,chd->bhkd", c_kv, w_uv)
        scores = torch.einsum("bhqd,bhkd->bhqk", q, k) * (D ** -0.5)
        off = Sk - Sq
        qi = torch.arange(Sq)[:, None]
        kj = torch.arange(Sk)[None, :]
        cmask = kj <= (qi + off)
        scores = torch.where(cmask[None, None], scores, -1e9)
        p = _softmax(scores, axis=-1)
        ctx = torch.einsum("bhqk,bhkd->bhqd", p, v)
        return torch.einsum("bhqd,hdm->bqm", ctx, w_o)

    a = _A_ref(A_q, A_k, A_v, A_shift_k, A_ssm_k, A_ssm_D)
    b = _B_ref(B_x, B_c_kv, B_w_q, B_w_uk, B_w_uv, B_w_o)
    return torch.concatenate([a, b], axis=-1)
```

```cpp
#include <cuda_runtime.h>
#include <cuda_bf16.h>
#include <cuda.h>
#include <stdint.h>

namespace {

typedef __nv_bfloat16 bf16;

constexpr int SEQ  = 2048;
constexpr int DA   = 448;
constexpr int NH   = 16;
constexpr int HD   = 256;
constexpr int DM   = 448;
constexpr int DC   = 1024;
constexpr int OUTW = DA + DM;
constexpr int NMAIN = 128;
constexpr int NCONV = 4;
constexpr int NCTA  = NMAIN + NCONV;
constexpr int NTHREADS = 384;
constexpr int D_SPARE = 320;

__device__ __align__(1024) bf16 g_kv[2ull * SEQ * NH * HD];
__device__ __align__(1024) bf16 g_ctx[(size_t)NMAIN * 128 * HD];
constexpr int XS_PLANE = 144 * 16;
__device__ __align__(128) uint8_t g_xs[NMAIN * 2 * XS_PLANE];
struct alignas(128) Flag { unsigned v; unsigned pad[31]; };
struct Flags {
  Flag kv_ready[NH];
  Flag ctx_ready[NMAIN * 2];
  Flag part_ready[16 * 2];
  Flag xs_ready[NH];
  Flag zs_ready[NH];
  alignas(128) unsigned long long done;
};
__device__ Flags g_flags;
#define TS(i)
#define TSG(i)
#define GT(i)
#define PT(i)
#define WHICH_TS 0
#define PCLK(var)
#define PACC(acc, t0)
#define PDECL
#define PDUMP()

#define TR_DECL
#define TR(tag)
#define TR_END()

struct alignas(64) Params {
  CUtensorMap ckv;
  CUtensorMap wuk;
  CUtensorMap wuv;
  CUtensorMap x;
  CUtensorMap wq;
  CUtensorMap kv;
  CUtensorMap part;
  CUtensorMap ctx;
  CUtensorMap wo;
  CUtensorMap ak, ak8, av, aq, ao;
  const bf16 *a_q, *a_k, *a_v, *a_shift, *a_ssmk, *a_D;
  bf16* out;
};

constexpr uint32_t P1_STAGE = 49152;
constexpr uint32_t P1_STG   = 196608;
constexpr uint32_t SLOT     = 32768;
constexpr int      NSLOT    = 5;
constexpr uint32_t QREG     = 163840;
constexpr uint32_t CV_X = 0, CV_PLANE = 2368, CV_HRAW = 4864, CV_HE = 9216, CV_HCOPY = 4160, CV_R = SLOT;
constexpr uint32_t BARS     = 229376;
constexpr uint32_t SMEM_BYTES = BARS + 512 + 1024;
enum : uint32_t {
  B_P1_FULL = 0, B_P1_EMPTY = 4, B_RG_FULL = 8, B_RG_EMPTY = 13, B_ST_FULL = 18, B_ST_EMPTY = 20,
  B_XS = 22, B_PFREE = 23, B_S2_FULL = 28, B_S2_EMPTY = 32, B_QFREE = 36, B_CTXF = 38, B_PART = 40, B_CONV = 42, B_COUNT = 43
};

__device__ __forceinline__ uint32_t smem_u32(const void* p) { return (uint32_t)__cvta_generic_to_shared(p); }
__device__ __forceinline__ void mbar_init(uint32_t bar, uint32_t cnt) {
  asm volatile("mbarrier.init.shared::cta.b64 [%0], %1;" :: "r"(bar), "r"(cnt) : "memory");
}
__device__ __forceinline__ void mbar_expect_tx(uint32_t bar, uint32_t bytes) {
  asm volatile("mbarrier.arrive.expect_tx.shared::cta.b64 _, [%0], %1;" :: "r"(bar), "r"(bytes) : "memory");
}
__device__ __forceinline__ void mbar_arrive(uint32_t bar) {
  asm volatile("mbarrier.arrive.shared::cta.b64 _, [%0];" :: "r"(bar) : "memory");
}
__device__ __forceinline__ void mbar_arrive_n(uint32_t bar, uint32_t n) {
  asm volatile("mbarrier.arrive.shared::cta.b64 _, [%0], %1;" :: "r"(bar), "r"(n) : "memory");
}
__device__ __forceinline__ void mbar_arrive_remote(uint32_t bar, uint32_t cta) {
  asm volatile("{\n.reg .b32 ra;\nmapa.shared::cluster.u32 ra, %0, %1;\n"
               "mbarrier.arrive.shared::cluster.b64 _, [ra];\n}" :: "r"(bar), "r"(cta) : "memory");
}
__device__ __forceinline__ bool mbar_try(uint32_t bar, uint32_t parity) {
  uint32_t ok;
  asm volatile("{\n.reg .pred p;\nmbarrier.try_wait.parity.shared::cta.b64 p, [%1], %2;\nselp.u32 %0, 1, 0, p;\n}"
               : "=r"(ok) : "r"(bar), "r"(parity) : "memory");
  return ok;
}
constexpr uint32_t SPIN_LIMIT = 1u << 24;
__device__ __forceinline__ void mbar_wait(uint32_t bar, uint32_t parity) {
  if (mbar_try(bar, parity)) return;
  uint32_t n = 0;
  while (!mbar_try(bar, parity)) { if (++n > SPIN_LIMIT) __trap(); }
}
__device__ __forceinline__ unsigned load_epoch() {
  unsigned long long e; asm volatile("ld.relaxed.gpu.global.u64 %0, [%1];" : "=l"(e) : "l"(&g_flags.done) : "memory"); return (unsigned)(e / NMAIN);
}
__device__ __forceinline__ void flag_wait(const unsigned* f, unsigned count, unsigned epoch) {
  const unsigned target = (epoch + 1) * count;
  uint32_t n = 0;
  while (true) {
    unsigned v;
    asm volatile("ld.acquire.gpu.global.u32 %0, [%1];" : "=r"(v) : "l"(f) : "memory");
    if ((int)(v - target) >= 0) break;
    if (++n > SPIN_LIMIT) __trap();
    __nanosleep(20);
  }
}
__device__ __forceinline__ void flag_wait_fast(const unsigned* f, unsigned count, unsigned epoch) {
  const unsigned target = (epoch + 1) * count;
  uint32_t n = 0;
  while (true) {
    unsigned v;
    asm volatile("ld.acquire.gpu.global.u32 %0, [%1];" : "=r"(v) : "l"(f) : "memory");
    if ((int)(v - target) >= 0) break;
    if (++n > SPIN_LIMIT) __trap();
  }
}
__device__ __forceinline__ void fence_async_all() { asm volatile("fence.proxy.async;" ::: "memory"); }
__device__ __forceinline__ void flag_signal(unsigned* f) {
  asm volatile("fence.acq_rel.gpu;" ::: "memory");
  asm volatile("red.relaxed.gpu.global.add.u32 [%0], 1;" :: "l"(f) : "memory");
}
__device__ __forceinline__ void flag_signal_after_bulk(unsigned* f) {
  asm volatile("red.relaxed.gpu.global.add.u32 [%0], 1;" :: "l"(f) : "memory");
}
__device__ __forceinline__ void fence_async_smem() { asm volatile("fence.proxy.async.shared::cta;" ::: "memory"); }
__device__ __forceinline__ void tma_ld2(uint32_t dst, const CUtensorMap* m, uint32_t bar, int c0, int c1) {
  asm volatile("cp.async.bulk.tensor.2d.shared::cluster.global.mbarrier::complete_tx::bytes [%0], [%1, {%3, %4}], [%2];"
               :: "r"(dst), "l"(m), "r"(bar), "r"(c0), "r"(c1) : "memory");
}
__device__ __forceinline__ void tma_ld3(uint32_t dst, const CUtensorMap* m, uint32_t bar, int c0, int c1, int c2) {
  asm volatile("cp.async.bulk.tensor.3d.shared::cluster.global.mbarrier::complete_tx::bytes [%0], [%1, {%3, %4, %5}], [%2];"
               :: "r"(dst), "l"(m), "r"(bar), "r"(c0), "r"(c1), "r"(c2) : "memory");
}
__device__ __forceinline__ void tma_ld3_mc(uint32_t dst, const CUtensorMap* m, uint32_t bar, int c0, int c1, int c2) {
  asm volatile("cp.async.bulk.tensor.3d.shared::cluster.global.mbarrier::complete_tx::bytes.multicast::cluster [%0], [%1, {%3, %4, %5}], [%2], %6;"
               :: "r"(dst), "l"(m), "r"(bar), "r"(c0), "r"(c1), "r"(c2), "h"((uint16_t)3) : "memory");
}
__device__ __forceinline__ void bulk_ld(uint32_t dst, const void* src, uint32_t bytes, uint32_t bar) {
  asm volatile("cp.async.bulk.shared::cluster.global.mbarrier::complete_tx::bytes [%0], [%1], %2, [%3];"
               :: "r"(dst), "l"(src), "r"(bytes), "r"(bar) : "memory");
}
__device__ __forceinline__ void tma_st3(const CUtensorMap* m, uint32_t src, int c0, int c1, int c2) {
  asm volatile("cp.async.bulk.tensor.3d.global.shared::cta.bulk_group [%0, {%2, %3, %4}], [%1];"
               :: "l"(m), "r"(src), "r"(c0), "r"(c1), "r"(c2) : "memory");
}
__device__ __forceinline__ void tma_ld2_mc(uint32_t dst, const CUtensorMap* m, uint32_t bar, int c0, int c1) {
  asm volatile("cp.async.bulk.tensor.2d.shared::cluster.global.mbarrier::complete_tx::bytes.multicast::cluster [%0], [%1, {%3, %4}], [%2], %5;"
               :: "r"(dst), "l"(m), "r"(bar), "r"(c0), "r"(c1), "h"((uint16_t)3) : "memory");
}
__device__ __forceinline__ void tma_st2(const CUtensorMap* m, uint32_t src, int c0, int c1) {
  asm volatile("cp.async.bulk.tensor.2d.global.shared::cta.bulk_group [%0, {%2, %3}], [%1];"
               :: "l"(m), "r"(src), "r"(c0), "r"(c1) : "memory");
}
__device__ __forceinline__ void tma_red2(const CUtensorMap* m, uint32_t src, int c0, int c1) {
  asm volatile("cp.reduce.async.bulk.tensor.2d.global.shared::cta.add.tile.bulk_group [%0, {%2, %3}], [%1];"
               :: "l"(m), "r"(src), "r"(c0), "r"(c1) : "memory");
}
__device__ __forceinline__ void bulk_commit() { asm volatile("cp.async.bulk.commit_group;" ::: "memory"); }
__device__ __forceinline__ void bulk_wait_read() { asm volatile("cp.async.bulk.wait_group.read 0;" ::: "memory"); }
__device__ __forceinline__ void bulk_wait_all() { asm volatile("cp.async.bulk.wait_group 0;" ::: "memory"); }
__device__ __forceinline__ void prefetch_map(const CUtensorMap* m) { asm volatile("prefetch.tensormap [%0];" :: "l"(m) : "memory"); }
__device__ __forceinline__ void wg_fence() { asm volatile("wgmma.fence.sync.aligned;" ::: "memory"); }
__device__ __forceinline__ void wg_commit() { asm volatile("wgmma.commit_group.sync.aligned;" ::: "memory"); }
template <int N> __device__ __forceinline__ void wg_wait() { asm volatile("wgmma.wait_group.sync.aligned %0;" :: "n"(N) : "memory"); }
template <int N> __device__ __forceinline__ void reg_fence(float (&d)[N]) {
#pragma unroll
  for (int i = 0; i < N; i++) asm volatile("" : "+f"(d[i]) :: "memory");
}
template <int N> __device__ __forceinline__ void reg_fence(uint32_t (&d)[N]) {
#pragma unroll
  for (int i = 0; i < N; i++) asm volatile("" : "+r"(d[i]) :: "memory");
}
__device__ __forceinline__ uint32_t fresh_tid() { uint32_t t; asm volatile("mov.u32 %0, %%tid.x;" : "=r"(t)); return t; }
__device__ __forceinline__ uint32_t lane_base16() {
  const uint32_t t = fresh_tid(), lane = t & 31, wq = (t >> 5) & 3;
  return (16 * wq + (lane & 7) + 8 * ((lane >> 3) & 1)) * 128 + (((lane >> 4) ^ (lane & 7)) << 4);
}
__device__ __forceinline__ void named_sync(int id, int n) { asm volatile("bar.sync %0, %1;" :: "r"(id), "r"(n) : "memory"); }
__device__ __forceinline__ void named_arrive(int id, int n) { asm volatile("bar.arrive %0, %1;" :: "r"(id), "r"(n) : "memory"); }
__device__ __forceinline__ uint32_t pack_bf16(float lo, float hi) {
  uint32_t r; asm("cvt.rn.bf16x2.f32 %0, %1, %2;" : "=r"(r) : "f"(hi), "f"(lo)); return r;
}
__device__ __forceinline__ float ex2(float x) { float y; asm("ex2.approx.ftz.f32 %0, %1;" : "=f"(y) : "f"(x)); return y; }
__device__ __forceinline__ void stsm4(uint32_t addr, uint32_t a, uint32_t b, uint32_t c, uint32_t d) {
  asm volatile("stmatrix.sync.aligned.m8n8.x4.shared.b16 [%0], {%1, %2, %3, %4};" :: "r"(addr), "r"(a), "r"(b), "r"(c), "r"(d) : "memory");
}
__device__ __forceinline__ uint64_t mk_desc(uint32_t addr, uint32_t lbo, uint32_t sbo) {
  return (uint64_t)(((addr & 0x3FFFF) >> 4) | ((lbo >> 4) << 16)) | ((uint64_t)((sbo >> 4) | (1u << 30)) << 32);
}
__device__ __forceinline__ uint64_t desc_k(uint32_t addr)  { return mk_desc(addr, 16, 1024); }
__device__ __forceinline__ uint64_t desc_mn(uint32_t addr) { return mk_desc(addr, 8192, 1024); }
__device__ __forceinline__ uint64_t desc_add(uint64_t d, uint32_t bytes) { return d + (bytes >> 4); }

__device__ __forceinline__ void wgmma_ss_n256_tb(float (&d)[128], uint64_t da, uint64_t db, int sd) {
  asm volatile("{\n.reg .pred p;\nsetp.ne.b32 p, %130, 0;\n"
    "wgmma.mma_async.sync.aligned.m64n256k16.f32.bf16.bf16 "
    "{%0, %1, %2, %3, %4, %5, %6, %7, %8, %9, %10, %11, %12, %13, %14, %15, "
    "%16, %17, %18, %19, %20, %21, %22, %23, %24, %25, %26, %27, %28, %29, %30, %31, "
    "%32, %33, %34, %35, %36, %37, %38, %39, %40, %41, %42, %43, %44, %45, %46, %47, "
    "%48, %49, %50, %51, %52, %53, %54, %55, %56, %57, %58, %59, %60, %61, %62, %63, "
    "%64, %65, %66, %67, %68, %69, %70, %71, %72, %73, %74, %75, %76, %77, %78, %79, "
    "%80, %81, %82, %83, %84, %85, %86, %87, %88, %89, %90, %91, %92, %93, %94, %95, "
    "%96, %97, %98, %99, %100, %101, %102, %103, %104, %105, %106, %107, %108, %109, %110, %111, "
    "%112, %113, %114, %115, %116, %117, %118, %119, %120, %121, %122, %123, %124, %125, %126, %127}, "
    "%128, %129, p, 1, 1, 0, 1;\n}"
    : "+f"(d[0]), "+f"(d[1]), "+f"(d[2]), "+f"(d[3]), "+f"(d[4]), "+f"(d[5]), "+f"(d[6]), "+f"(d[7]),
      "+f"(d[8]), "+f"(d[9]), "+f"(d[10]), "+f"(d[11]), "+f"(d[12]), "+f"(d[13]), "+f"(d[14]), "+f"(d[15]),
      "+f"(d[16]), "+f"(d[17]), "+f"(d[18]), "+f"(d[19]), "+f"(d[20]), "+f"(d[21]), "+f"(d[22]), "+f"(d[23]),
      "+f"(d[24]), "+f"(d[25]), "+f"(d[26]), "+f"(d[27]), "+f"(d[28]), "+f"(d[29]), "+f"(d[30]), "+f"(d[31]),
      "+f"(d[32]), "+f"(d[33]), "+f"(d[34]), "+f"(d[35]), "+f"(d[36]), "+f"(d[37]), "+f"(d[38]), "+f"(d[39]),
      "+f"(d[40]), "+f"(d[41]), "+f"(d[42]), "+f"(d[43]), "+f"(d[44]), "+f"(d[45]), "+f"(d[46]), "+f"(d[47]),
      "+f"(d[48]), "+f"(d[49]), "+f"(d[50]), "+f"(d[51]), "+f"(d[52]), "+f"(d[53]), "+f"(d[54]), "+f"(d[55]),
      "+f"(d[56]), "+f"(d[57]), "+f"(d[58]), "+f"(d[59]), "+f"(d[60]), "+f"(d[61]), "+f"(d[62]), "+f"(d[63]),
      "+f"(d[64]), "+f"(d[65]), "+f"(d[66]), "+f"(d[67]), "+f"(d[68]), "+f"(d[69]), "+f"(d[70]), "+f"(d[71]),
      "+f"(d[72]), "+f"(d[73]), "+f"(d[74]), "+f"(d[75]), "+f"(d[76]), "+f"(d[77]), "+f"(d[78]), "+f"(d[79]),
      "+f"(d[80]), "+f"(d[81]), "+f"(d[82]), "+f"(d[83]), "+f"(d[84]), "+f"(d[85]), "+f"(d[86]), "+f"(d[87]),
      "+f"(d[88]), "+f"(d[89]), "+f"(d[90]), "+f"(d[91]), "+f"(d[92]), "+f"(d[93]), "+f"(d[94]), "+f"(d[95]),
      "+f"(d[96]), "+f"(d[97]), "+f"(d[98]), "+f"(d[99]), "+f"(d[100]), "+f"(d[101]), "+f"(d[102]), "+f"(d[103]),
      "+f"(d[104]), "+f"(d[105]), "+f"(d[106]), "+f"(d[107]), "+f"(d[108]), "+f"(d[109]), "+f"(d[110]), "+f"(d[111]),
      "+f"(d[112]), "+f"(d[113]), "+f"(d[114]), "+f"(d[115]), "+f"(d[116]), "+f"(d[117]), "+f"(d[118]), "+f"(d[119]),
      "+f"(d[120]), "+f"(d[121]), "+f"(d[122]), "+f"(d[123]), "+f"(d[124]), "+f"(d[125]), "+f"(d[126]), "+f"(d[127])
    : "l"(da), "l"(db), "r"(sd));
}
__device__ __forceinline__ void wgmma_ss_n64(float (&d)[32], uint64_t da, uint64_t db, int sd) {
  asm volatile("{\n.reg .pred p;\nsetp.ne.b32 p, %34, 0;\n"
    "wgmma.mma_async.sync.aligned.m64n64k16.f32.bf16.bf16 "
    "{%0, %1, %2, %3, %4, %5, %6, %7, %8, %9, %10, %11, %12, %13, %14, %15, "
    "%16, %17, %18, %19, %20, %21, %22, %23, %24, %25, %26, %27, %28, %29, %30, %31}, "
    "%32, %33, p, 1, 1, 0, 0;\n}"
    : "+f"(d[0]), "+f"(d[1]), "+f"(d[2]), "+f"(d[3]), "+f"(d[4]), "+f"(d[5]), "+f"(d[6]), "+f"(d[7]),
      "+f"(d[8]), "+f"(d[9]), "+f"(d[10]), "+f"(d[11]), "+f"(d[12]), "+f"(d[13]), "+f"(d[14]), "+f"(d[15]),
      "+f"(d[16]), "+f"(d[17]), "+f"(d[18]), "+f"(d[19]), "+f"(d[20]), "+f"(d[21]), "+f"(d[22]), "+f"(d[23]),
      "+f"(d[24]), "+f"(d[25]), "+f"(d[26]), "+f"(d[27]), "+f"(d[28]), "+f"(d[29]), "+f"(d[30]), "+f"(d[31])
    : "l"(da), "l"(db), "r"(sd));
}
__device__ __forceinline__ void wgmma_rs_n256_tb(float (&d)[128], uint32_t a0, uint32_t a1, uint32_t a2, uint32_t a3, uint64_t db, int sd) {
  asm volatile("{\n.reg .pred p;\nsetp.ne.b32 p, %133, 0;\n"
    "wgmma.mma_async.sync.aligned.m64n256k16.f32.bf16.bf16 "
    "{%0, %1, %2, %3, %4, %5, %6, %7, %8, %9, %10, %11, %12, %13, %14, %15, "
    "%16, %17, %18, %19, %20, %21, %22, %23, %24, %25, %26, %27, %28, %29, %30, %31, "
    "%32, %33, %34, %35, %36, %37, %38, %39, %40, %41, %42, %43, %44, %45, %46, %47, "
    "%48, %49, %50, %51, %52, %53, %54, %55, %56, %57, %58, %59, %60, %61, %62, %63, "
    "%64, %65, %66, %67, %68, %69, %70, %71, %72, %73, %74, %75, %76, %77, %78, %79, "
    "%80, %81, %82, %83, %84, %85, %86, %87, %88, %89, %90, %91, %92, %93, %94, %95, "
    "%96, %97, %98, %99, %100, %101, %102, %103, %104, %105, %106, %107, %108, %109, %110, %111, "
    "%112, %113, %114, %115, %116, %117, %118, %119, %120, %121, %122, %123, %124, %125, %126, %127}, "
    "{%128, %129, %130, %131}, %132, p, 1, 1, 1;\n}"
    : "+f"(d[0]), "+f"(d[1]), "+f"(d[2]), "+f"(d[3]), "+f"(d[4]), "+f"(d[5]), "+f"(d[6]), "+f"(d[7]),
      "+f"(d[8]), "+f"(d[9]), "+f"(d[10]), "+f"(d[11]), "+f"(d[12]), "+f"(d[13]), "+f"(d[14]), "+f"(d[15]),
      "+f"(d[16]), "+f"(d[17]), "+f"(d[18]), "+f"(d[19]), "+f"(d[20]), "+f"(d[21]), "+f"(d[22]), "+f"(d[23]),
      "+f"(d[24]), "+f"(d[25]), "+f"(d[26]), "+f"(d[27]), "+f"(d[28]), "+f"(d[29]), "+f"(d[30]), "+f"(d[31]),
      "+f"(d[32]), "+f"(d[33]), "+f"(d[34]), "+f"(d[35]), "+f"(d[36]), "+f"(d[37]), "+f"(d[38]), "+f"(d[39]),
      "+f"(d[40]), "+f"(d[41]), "+f"(d[42]), "+f"(d[43]), "+f"(d[44]), "+f"(d[45]), "+f"(d[46]), "+f"(d[47]),
      "+f"(d[48]), "+f"(d[49]), "+f"(d[50]), "+f"(d[51]), "+f"(d[52]), "+f"(d[53]), "+f"(d[54]), "+f"(d[55]),
      "+f"(d[56]), "+f"(d[57]), "+f"(d[58]), "+f"(d[59]), "+f"(d[60]), "+f"(d[61]), "+f"(d[62]), "+f"(d[63]),
      "+f"(d[64]), "+f"(d[65]), "+f"(d[66]), "+f"(d[67]), "+f"(d[68]), "+f"(d[69]), "+f"(d[70]), "+f"(d[71]),
      "+f"(d[72]), "+f"(d[73]), "+f"(d[74]), "+f"(d[75]), "+f"(d[76]), "+f"(d[77]), "+f"(d[78]), "+f"(d[79]),
      "+f"(d[80]), "+f"(d[81]), "+f"(d[82]), "+f"(d[83]), "+f"(d[84]), "+f"(d[85]), "+f"(d[86]), "+f"(d[87]),
      "+f"(d[88]), "+f"(d[89]), "+f"(d[90]), "+f"(d[91]), "+f"(d[92]), "+f"(d[93]), "+f"(d[94]), "+f"(d[95]),
      "+f"(d[96]), "+f"(d[97]), "+f"(d[98]), "+f"(d[99]), "+f"(d[100]), "+f"(d[101]), "+f"(d[102]), "+f"(d[103]),
      "+f"(d[104]), "+f"(d[105]), "+f"(d[106]), "+f"(d[107]), "+f"(d[108]), "+f"(d[109]), "+f"(d[110]), "+f"(d[111]),
      "+f"(d[112]), "+f"(d[113]), "+f"(d[114]), "+f"(d[115]), "+f"(d[116]), "+f"(d[117]), "+f"(d[118]), "+f"(d[119]),
      "+f"(d[120]), "+f"(d[121]), "+f"(d[122]), "+f"(d[123]), "+f"(d[124]), "+f"(d[125]), "+f"(d[126]), "+f"(d[127])
    : "r"(a0), "r"(a1), "r"(a2), "r"(a3), "l"(db), "r"(sd));
}
__device__ __forceinline__ void wgmma_rs_n64_tb(float (&d)[32], uint32_t a0, uint32_t a1, uint32_t a2, uint32_t a3, uint64_t db, int sd) {
  asm volatile("{\n.reg .pred p;\nsetp.ne.b32 p, %37, 0;\n"
    "wgmma.mma_async.sync.aligned.m64n64k16.f32.bf16.bf16 "
    "{%0, %1, %2, %3, %4, %5, %6, %7, %8, %9, %10, %11, %12, %13, %14, %15, "
    "%16, %17, %18, %19, %20, %21, %22, %23, %24, %25, %26, %27, %28, %29, %30, %31}, "
    "{%32, %33, %34, %35}, %36, p, 1, 1, 1;\n}"
    : "+f"(d[0]), "+f"(d[1]), "+f"(d[2]), "+f"(d[3]), "+f"(d[4]), "+f"(d[5]), "+f"(d[6]), "+f"(d[7]),
      "+f"(d[8]), "+f"(d[9]), "+f"(d[10]), "+f"(d[11]), "+f"(d[12]), "+f"(d[13]), "+f"(d[14]), "+f"(d[15]),
      "+f"(d[16]), "+f"(d[17]), "+f"(d[18]), "+f"(d[19]), "+f"(d[20]), "+f"(d[21]), "+f"(d[22]), "+f"(d[23]),
      "+f"(d[24]), "+f"(d[25]), "+f"(d[26]), "+f"(d[27]), "+f"(d[28]), "+f"(d[29]), "+f"(d[30]), "+f"(d[31])
    : "r"(a0), "r"(a1), "r"(a2), "r"(a3), "l"(db), "r"(sd));
}

__device__ __forceinline__ uint4 lds16(uint32_t a) {
  uint4 v; asm volatile("ld.shared.v4.u32 {%0, %1, %2, %3}, [%4];" : "=r"(v.x), "=r"(v.y), "=r"(v.z), "=r"(v.w) : "r"(a) : "memory"); return v;
}
__device__ __forceinline__ void sts16(uint32_t a, uint32_t x, uint32_t y, uint32_t z, uint32_t w) {
  asm volatile("st.shared.v4.u32 [%0], {%1, %2, %3, %4};" :: "r"(a), "r"(x), "r"(y), "r"(z), "r"(w) : "memory");
}
__device__ __forceinline__ uint32_t lds4(uint32_t a) { uint32_t v; asm volatile("ld.shared.u32 %0, [%1];" : "=r"(v) : "r"(a) : "memory"); return v; }
__device__ __forceinline__ uint32_t lds4v(uint32_t a) { uint32_t v; asm volatile("ld.volatile.shared.u32 %0, [%1];" : "=r"(v) : "r"(a) : "memory"); return v; }
__device__ __forceinline__ uint32_t bmul(uint32_t a, uint32_t b) { uint32_t r; asm("mul.rn.bf16x2 %0, %1, %2;" : "=r"(r) : "r"(a), "r"(b)); return r; }
__device__ __forceinline__ uint32_t badd(uint32_t a, uint32_t b) { uint32_t r; asm("add.rn.bf16x2 %0, %1, %2;" : "=r"(r) : "r"(a), "r"(b)); return r; }

__device__ __forceinline__ void ldsm4(uint32_t (&r)[4], uint32_t a) {
  asm volatile("ldmatrix.sync.aligned.m8n8.x4.shared.b16 {%0, %1, %2, %3}, [%4];" : "=r"(r[0]), "=r"(r[1]), "=r"(r[2]), "=r"(r[3]) : "r"(a) : "memory");
}
__device__ __forceinline__ uint32_t transpose8(uint32_t a) { uint32_t d; asm volatile("movmatrix.sync.aligned.m8n8.trans.b16 %0, %1;" : "=r"(d) : "r"(a)); return d; }

__device__ __forceinline__ void mma16816(float (&d)[4], const uint32_t (&a)[4], uint32_t b0, uint32_t b1) {
  asm volatile("mma.sync.aligned.m16n8k16.row.col.f32.bf16.bf16.f32 {%0, %1, %2, %3}, {%4, %5, %6, %7}, {%8, %9}, {%0, %1, %2, %3};"
               : "+f"(d[0]), "+f"(d[1]), "+f"(d[2]), "+f"(d[3]) : "r"(a[0]), "r"(a[1]), "r"(a[2]), "r"(a[3]), "r"(b0), "r"(b1));
}

#define P1_SPLIT 0
#define O_ROT 1
#define STG_K1 3
#define STG_K2 9
#define STG_Q1 0
#define STG_Q2 3
#define ARRIVE_KK 12
#define SIDE_DELAY_NS 4000
#define KVH(h) (h)
#define HEAD_MAP 1
#define EARLY_LD 3
constexpr int RED_BAR = 6;
constexpr int CV_BAR = 5;
constexpr int PP_BAR = 3;
template <int V> struct Int { static constexpr int value = V; };
struct Ring {
  uint32_t slot, phase;
  __device__ __forceinline__ void next() { if (++slot == NSLOT) { slot = 0; phase ^= 1; } }
};
__device__ __forceinline__ uint32_t bar_addr(uint32_t sb, uint32_t i) { return sb + BARS + 8 * i; }
constexpr int FILLS_BEFORE_FINAL = 3 + 11 + 2 * (2 * 15 + 4);
constexpr int FINAL_STG_SLOT = FILLS_BEFORE_FINAL % NSLOT, FINAL_STG_PHASE = (FILLS_BEFORE_FINAL / NSLOT) & 1;
__device__ __forceinline__ constexpr uint32_t fin_slot(int i4) { return (FINAL_STG_SLOT + 1 + i4) % NSLOT; }
__device__ __forceinline__ constexpr uint32_t fin_wrap(int i4) { return (FINAL_STG_SLOT + 1 + i4) >= NSLOT; }

__device__ __forceinline__ int q_tile(int h, int j, int which) { return ((h < 8) == (which == 0)) ? 15 - j : j; }

__device__ __forceinline__ int o_chunk(int h, int c) { const int x = c + O_ROT * (h & 7); return x % 7; }

struct Seg { int kv0, nt; bool diag, shared; };
__device__ __forceinline__ int num_segs(int h, int j, int which) { return q_tile(h, j, which) > q_tile(h, j ^ 1, which) ? 2 : 1; }
__device__ __forceinline__ Seg get_seg(int h, int j, int which, int sg) {
  const int qt = q_tile(h, j, which), qo = q_tile(h, j ^ 1, which);
  if (qt < qo) return Seg{0, 2 * qt + 2, true, true};
  const bool own = (sg == 1) == (which == 0);
  return own ? Seg{2 * qt, 2, true, false} : Seg{0, 2 * qt, false, true};
}
__device__ __forceinline__ void ring_acquire(uint32_t sb, Ring& r, uint32_t bytes) {
  mbar_wait(bar_addr(sb, B_RG_EMPTY + r.slot), r.phase ^ 1);
  mbar_expect_tx(bar_addr(sb, B_RG_FULL + r.slot), bytes);
}
__device__ __forceinline__ void load_tile4(uint32_t dst, const CUtensorMap* m, uint32_t full, int row, int blk0, int rank, bool shared) {
  if (shared) {
    tma_ld3_mc(dst + rank * 16384, m, full, 0, row, blk0 + 2 * rank);
  } else {
    tma_ld3(dst, m, full, 0, row, blk0);
    tma_ld3(dst + 16384, m, full, 0, row, blk0 + 2);
  }
}
__device__ __forceinline__ void producer_main(const Params& p, uint32_t sb, int h, int j) {
  const int rank = j & 1;
  const unsigned epoch = load_epoch();
  for (int it = EARLY_LD; it < 71; it++) {
    const int t = it >> 4, k = it & 15, s = it & 3;
    mbar_wait(bar_addr(sb, B_P1_EMPTY + s), ((it >> 2) & 1) ^ 1);
    const uint32_t full = bar_addr(sb, B_P1_FULL + s), dst = sb + s * P1_STAGE;
    mbar_expect_tx(full, P1_STAGE);
    if (t < 4) {
      tma_ld2(dst, &p.ckv, full, k * 64, (2 * j + (t & 1)) * 128);
      load_tile4(dst + 16384, (t >> 1) ? &p.wuv : &p.wuk, full, k * 64, h * 4, rank, true);
    } else {
      tma_ld2(dst, &p.x, full, k * 64, q_tile(h, j, 0) * 128);
      load_tile4(dst + 16384, &p.wq, full, k * 64, h * 4, rank, true);
    }
  }
  Ring r{0, 0};
  int nfill = 0;
  auto first5 = [&]() {
    if (nfill < 5) { if (nfill != 2) mbar_wait(bar_addr(sb, B_P1_EMPTY + (nfill < 2 ? nfill : nfill - 1)), nfill == 4 ? 0 : 1); nfill++; }
  };
  int hs = 5;
  auto shared_acquire = [&]() {
    mbar_wait(bar_addr(sb, B_RG_EMPTY + r.slot), r.phase ^ 1);
    if (hs < 5) {
      mbar_arrive_remote(bar_addr(sb, B_PFREE + r.slot), rank ^ 1);
      mbar_wait(bar_addr(sb, B_PFREE + r.slot), 0);
      hs++;
    }
    mbar_expect_tx(bar_addr(sb, B_RG_FULL + r.slot), 32768);
  };
  {
    first5();
    mbar_wait(bar_addr(sb, B_XS), 0);
    const uint32_t full = bar_addr(sb, B_RG_FULL + 0);
    const int cc = h * 8 + j;
    ring_acquire(sb, r, 2 * XS_PLANE + SEQ * 2);
    bulk_ld(sb + CV_X, g_xs + (size_t)cc * 2 * XS_PLANE, XS_PLANE, full);
    bulk_ld(sb + CV_X + CV_PLANE, g_xs + (size_t)cc * 2 * XS_PLANE + XS_PLANE, XS_PLANE, full);
    bulk_ld(sb + CV_HRAW, p.a_ssmk + (size_t)(D_SPARE + cc) * SEQ, SEQ * 2, full);
    r.next();
    for (int i = 0; i < 2; i++) {
      first5();
      mbar_wait(bar_addr(sb, B_RG_EMPTY + r.slot), r.phase ^ 1);
      mbar_arrive(bar_addr(sb, B_RG_FULL + r.slot));
      r.next();
    }
  }
  for (int which = 0; which < 2; which++) {
    const int qt = q_tile(h, j, which);
    if (which == 1) {
      for (int kc = 0; kc < 7; kc++) {
        if ((kc & 1) == 0) {
          ring_acquire(sb, r, kc == 6 ? 16384 : 32768);
          const uint32_t full = bar_addr(sb, B_RG_FULL + r.slot), dst = sb + r.slot * SLOT;
          tma_ld2(dst, &p.x, full, kc * 64, qt * 128);
          if (kc < 6) tma_ld2(dst + 16384, &p.x, full, kc * 64 + 64, qt * 128);
          r.next();
        }
        ring_acquire(sb, r, 32768);
        load_tile4(sb + r.slot * SLOT, &p.wq, bar_addr(sb, B_RG_FULL + r.slot), kc * 64, h * 4, rank, false);
        r.next();
      }
    }
    if (which == 0) { flag_wait(&g_flags.kv_ready[h].v, 16, epoch); fence_async_all(); }
    const int nseg = num_segs(h, j, which);
    for (int sg = 0; sg < nseg; sg++) {
      const Seg S = get_seg(h, j, which, sg);
      if (which == 1 && S.shared) hs = 0;
      for (int f = 0; f < 2 * S.nt; f++) {
        const bool isK = (f == 0) || ((f & 1) && f < 2 * S.nt - 1);
        const int tile = S.kv0 + (f == 0 ? 0 : (isK ? (f + 1) >> 1 : (f == 2 * S.nt - 1 ? S.nt - 1 : (f >> 1) - 1)));
        first5();
        shared_acquire();
        load_tile4(sb + r.slot * SLOT, &p.kv, bar_addr(sb, B_RG_FULL + r.slot), ((isK ? 0 : NH) + KVH(h)) * SEQ + tile * 64, 0, rank, S.shared);
        r.next();
      }
    }
  }
  mbar_wait(bar_addr(sb, B_RG_EMPTY + FINAL_STG_SLOT), FINAL_STG_PHASE ^ 1);
  mbar_arrive(bar_addr(sb, B_RG_FULL + FINAL_STG_SLOT));
  for (int i = 0; i < 14; i++) {
    const uint32_t sl = fin_slot(i & 3), ph = FINAL_STG_PHASE ^ fin_wrap(i & 3) ^ ((i >> 2) & 1);
    mbar_wait(bar_addr(sb, B_RG_EMPTY + sl), ph ^ 1);
    const uint32_t full = bar_addr(sb, B_RG_FULL + sl);
    mbar_expect_tx(full, 32768);
    tma_ld2_mc(sb + sl * SLOT + rank * 16384, &p.wo, full, o_chunk(h, i >> 1) * 64, ((i & 1) ? h ^ 8 : h) * HD + rank * 128);
  }
}

__device__ __forceinline__ void storer_main(const Params& p, uint32_t sb, int h, int j, int w) {
  const uint32_t full = bar_addr(sb, B_ST_FULL + w), empty = bar_addr(sb, B_ST_EMPTY + w);
  const int lane = threadIdx.x & 31;
  const unsigned epoch = load_epoch();
  for (int job = 0; job < 8; job++) {
    const int t = job >> 1, half = job & 1;
    mbar_wait(full, job & 1);
    const uint32_t src = sb + P1_STG + w * 16384 + (lane >> 3) * 128;
    bf16* dst = g_kv + (size_t)(((t >> 1) * NH + KVH(h)) * SEQ + (2 * j + (t & 1)) * 128 + w * 64 + (lane >> 3)) * HD + half * 128 + (lane & 7) * 8;
#pragma unroll 4
    for (int i = 0; i < 32; i++) {
      const int r4 = (i & 15) * 4;
      const uint4 v = lds16(src + (i >> 4) * 8192 + r4 * 128 + (((lane & 7) ^ ((r4 + (lane >> 3)) & 7)) << 4));
      *reinterpret_cast<uint4*>(dst + r4 * HD + (i >> 4) * 64) = v;
    }
    __syncwarp();
    if (lane == 0) mbar_arrive(empty);
  }
  __syncwarp();
  if (lane == 0) flag_signal(&g_flags.kv_ready[h].v);
  const int cta = h * 8 + j, qt = q_tile(h, j, 1);
  {
    mbar_wait(full, 0);
    if (lane == 0) {
      tma_st3(&p.ctx, sb + QREG + w * 32768, 0, cta * 128 + w * 64, 0);
      bulk_commit();
    }
    uint4* z = reinterpret_cast<uint4*>(p.out + (size_t)(qt * 128 + w * 64 + (h & 7) * 8 + (lane >> 2)) * OUTW + DA) + (lane & 3);
#pragma unroll
    for (int i = 0; i < 14; i++) z[4 * i] = make_uint4(0, 0, 0, 0);
    __syncwarp();
    if (lane != 0) return;
    bulk_wait_read();
    mbar_arrive(empty);
    bulk_wait_all();
    flag_signal(&g_flags.ctx_ready[cta * 2 + w].v);
    flag_signal_after_bulk(&g_flags.part_ready[qt * 2 + w].v);
  }
  {
    flag_wait(&g_flags.ctx_ready[(cta ^ 64) * 2 + w].v, 1, epoch);
    flag_wait(&g_flags.part_ready[qt * 2 + w].v, 8, epoch);
    fence_async_all();
    mbar_wait(bar_addr(sb, B_QFREE + w), 0);
    mbar_expect_tx(bar_addr(sb, B_CTXF + w), 32768);
    tma_ld3(sb + QREG + w * 32768, &p.ctx, bar_addr(sb, B_CTXF + w), 0, (cta ^ 64) * 128 + w * 64, 0);
    const uint32_t stg = sb + FINAL_STG_SLOT * SLOT;
    for (int ch = 0; ch < 7; ch++) {
      const int b = ch & 1;
      mbar_wait(bar_addr(sb, B_S2_FULL + w * 2 + b), (ch >> 1) & 1);
      tma_red2(&p.part, stg + w * 16384 + b * 8192, DA + o_chunk(h, ch) * 64, qt * 128 + w * 64);
      bulk_commit();
      bulk_wait_read();
      mbar_arrive(bar_addr(sb, B_S2_EMPTY + w * 2 + b));
    }
    GT(48 + w);
    bulk_wait_all();
    GT(50 + w); GT(52 + w); GT(56);
  }
}

template <int OFF, int NB, int NREG>
__device__ __forceinline__ void store_blocks(uint32_t base, uint32_t lanebase, const uint32_t (&pk)[NREG]) {
#pragma unroll
  for (int J = 0; J < NB * 8; J += 2) {
    const uint32_t a = base + (J >> 3) * 8192 + (lanebase ^ ((J & 7) << 4));
    stsm4(a, pk[OFF + 2 * J], pk[OFF + 2 * J + 1], pk[OFF + 2 * J + 2], pk[OFF + 2 * J + 3]);
  }
}
__device__ __forceinline__ void warp_arrive(uint32_t bar, int lane) { __syncwarp(); if (lane == 0) mbar_arrive(bar); }
__device__ __forceinline__ void release(uint32_t bar, int lane, int rank, bool shared) {
  if (shared) { if (lane < 2) mbar_arrive_remote(bar, rank ^ lane); }
  else if (lane == 0) mbar_arrive_n(bar, 2);
}

__device__ __forceinline__ void consumer_main(const Params& p, uint32_t sb, int h, int j, int w) {
  const int lane = threadIdx.x & 31;
  const int rank = j & 1;
  const uint32_t st_full = bar_addr(sb, B_ST_FULL + w), st_empty = bar_addr(sb, B_ST_EMPTY + w);
  const uint32_t stg = sb + P1_STG + w * 16384;

  auto turn_begin = [&]() { named_sync(PP_BAR + w, 256); };
  auto turn_end = [&]() { named_arrive(PP_BAR + (w ^ 1), 256); };
  if (w == 1) named_arrive(PP_BAR, 256);
  float acc[128];
#pragma unroll
  for (int i = 0; i < 128; i++) acc[i] = 0.f;
  uint32_t pk[64];
#pragma unroll
  for (int i = 0; i < 64; i++) pk[i] = 0;
  PDECL;
  TR_DECL;
  TR(0);
  TSG(0); TS(1);
  const uint32_t qreg = sb + QREG + w * 32768;
  for (int t = 0; t < 5; t++) {
    const int nk = t < 4 ? 16 : 7;
#pragma unroll 1
    for (int k = 0; k < nk; k++) {
      const int it = t * 16 + k, s = k & 3;
      mbar_wait(bar_addr(sb, B_P1_FULL + s), (it >> 2) & 1);
      TR(1);
      const uint64_t da = desc_k(sb + s * P1_STAGE + w * 8192), db = desc_mn(sb + s * P1_STAGE + 16384);
      turn_begin();
      TR(2);
      wg_fence();
#pragma unroll
      for (int kk = 0; kk < 4; kk++) wgmma_ss_n256_tb(acc, desc_add(da, kk * 32), desc_add(db, kk * 2048), (k | kk) != 0);
      wg_commit();
      turn_end();
      TR(3);
      const int k1 = t < 4 ? STG_K1 : STG_Q1, k2 = t < 4 ? STG_K2 : STG_Q2;
      if (t > 0 && (k == k1 || k == k2)) {
        const int job = 2 * (t - 1) + (k != k1);
        if (job > 0) mbar_wait(st_empty, (job - 1) & 1);
        if (k == k1) store_blocks<0, 2>(stg, lane_base16(), pk); else store_blocks<32, 2>(stg, lane_base16(), pk);
        warp_arrive(st_full, lane);
      }
      TR(4);
      wg_wait<1>();
      TR(5);
      if (k > 0) release(bar_addr(sb, B_P1_EMPTY + ((k - 1) & 3)), lane, rank, true);
    }
    wg_wait<0>();
    TR(6);
    reg_fence(acc);
    release(bar_addr(sb, B_P1_EMPTY + ((nk - 1) & 3)), lane, rank, true);
#pragma unroll
    for (int i = 0; i < 64; i++) pk[i] = pack_bf16(acc[2 * i], acc[2 * i + 1]);
    TS(t < 4 ? 2 + t : 60);
    TR(7);
  }
  mbar_wait(st_empty, 1);
  mbar_wait(bar_addr(sb, B_ST_EMPTY + (w ^ 1)), 1);
  mbar_wait(bar_addr(sb, B_P1_EMPTY + 3), 0);
  TR(8);
  store_blocks<0, 4>(qreg, lane_base16(), pk);
  fence_async_smem();
  named_sync(1 + w, 128);
  TR(9);
  TS(6);

  Ring r{0, 0};
  {
    const uint32_t ft = fresh_tid() - 128, wi = ft >> 5, ln = ft & 31, g = ln >> 2, c = ln & 3;
#pragma unroll
    for (int i = 0; i < 3; i++) { mbar_wait(bar_addr(sb, B_RG_FULL + i), 0); r.next(); }
    TS(19);
    const uint32_t hE = sb + CV_HE, hO = hE + CV_HCOPY;
    {
      const uint32_t o = ft * 16;
      const uint4 wv = lds16(sb + CV_HRAW + o);
      const uint32_t nx = ft < 255 ? lds4(sb + CV_HRAW + o + 16) : 0u;
      sts16(hE + 32 + o, wv.x, wv.y, wv.z, wv.w);
      sts16(hO + 32 + o, __byte_perm(wv.x, wv.y, 0x5432), __byte_perm(wv.y, wv.z, 0x5432), __byte_perm(wv.z, wv.w, 0x5432), __byte_perm(wv.w, nx, 0x5432));
      if (ft == 0) { sts16(hE, 0, 0, 0, 0); sts16(hE + 16, 0, 0, 0, 0); sts16(hO, 0, 0, 0, 0); sts16(hO + 16, 0, 0, 0, wv.x << 16); }
    }
    named_sync(CV_BAR, 256);
    TS(20);
    float ca[16][4];
#pragma unroll
    for (int i = 0; i < 16; i++) { ca[i][0] = 0.f; ca[i][1] = 0.f; ca[i][2] = 0.f; ca[i][3] = 0.f; }
    const uint32_t abase = ((g & 1) == 0 ? hE + (7 - g + 2 * c + 1) * 2 : hO + (7 - g + 2 * c) * 2) + wi * 32;
    const uint32_t baddr = sb + CV_X + ((ln >> 3) & 1) * CV_PLANE + (16 + (ln >> 4) * 8 + (ln & 7)) * 16 - wi * 16;
    {
      uint32_t fa[16][4], fb[8][4];
#pragma unroll
      for (int i = 0; i < 8; i++) ldsm4(fb[i], baddr + i * 256);
#pragma unroll
      for (int jj = 0; jj < 16; jj++) {
        const uint32_t ad = abase + jj * 256;
        fa[jj][0] = lds4(ad); fa[jj][1] = lds4(ad + 16); fa[jj][2] = lds4v(ad + 16); fa[jj][3] = lds4(ad + 32);
      }
#pragma unroll
      for (int jj = 0; jj < 16; jj++)
#pragma unroll
        for (int sx = 0; sx < 16 - jj; sx++)
          mma16816(ca[jj + sx], fa[jj], fb[sx >> 1][2 * (sx & 1)], fb[sx >> 1][2 * (sx & 1) + 1]);
    }
    TS(21);
#pragma unroll
    for (int i = 0; i < 16; i++)
      sts16(sb + CV_R + ((wi * 16 + i) * 32 + ln) * 16, __float_as_uint(ca[i][0]), __float_as_uint(ca[i][1]), __float_as_uint(ca[i][2]), __float_as_uint(ca[i][3]));
    named_sync(CV_BAR, 256);
    TS(22);
    const int cc = h * 8 + j;
    const uint32_t Dd = (uint32_t)__ldg(reinterpret_cast<const unsigned short*>(p.a_D + D_SPARE + cc)) * 0x10001u;
#pragma unroll
    for (int e = 0; e < 2; e++) {
      const int nt = 2 * wi + e;
      float y[4] = {0.f, 0.f, 0.f, 0.f};
#pragma unroll
      for (int v = 0; v < 8; v++) {
        const uint4 t = lds16(sb + CV_R + ((v * 16 + nt) * 32 + ln) * 16);
        y[0] += __uint_as_float(t.x); y[1] += __uint_as_float(t.y); y[2] += __uint_as_float(t.z); y[3] += __uint_as_float(t.w);
      }
      const uint32_t lo = transpose8(pack_bf16(y[0], y[1])), hi = transpose8(pack_bf16(y[2], y[3]));
      const uint32_t ro = (16 + 8 * nt) * 16 + ln * 4;
      const uint32_t x1 = lds4(sb + CV_X + CV_PLANE + ro), x0 = lds4(sb + CV_X + ro);
      uint8_t* gz = g_xs + (size_t)cc * 2 * XS_PLANE + ro;
      *reinterpret_cast<uint32_t*>(gz + XS_PLANE) = badd(lo, bmul(x1, Dd));
      *reinterpret_cast<uint32_t*>(gz)            = badd(hi, bmul(x0, Dd));
    }
    TS(23);
    fence_async_smem();
    __syncwarp();
    if (lane == 0) mbar_arrive(bar_addr(sb, B_CONV));
#pragma unroll
    for (int i = 0; i < 3; i++) release(bar_addr(sb, B_RG_EMPTY + i), lane, rank, true);
  }
  TS(15);
  TR(10);
  constexpr float SC = 0.0625f * 1.4426950408889634f;
  for (int which = 0; which < 2; which++) {
    if (which == 1) {
#pragma unroll
      for (int i = 0; i < 128; i++) acc[i] = 0.f;
      uint32_t xaddr = 0, xslot = 0, prev_w = 0;
#pragma unroll 1
      for (int kc = 0; kc < 7; kc++) {
        if ((kc & 1) == 0) {
          mbar_wait(bar_addr(sb, B_RG_FULL + r.slot), r.phase);
          xaddr = sb + r.slot * SLOT + w * 8192;
          if (kc > 0) { prev_w |= xslot << 8 | 0x10000; }
          xslot = r.slot;
          r.next();
        } else {
          xaddr += 16384;
        }
        mbar_wait(bar_addr(sb, B_RG_FULL + r.slot), r.phase);
        TR(11);
        const uint64_t da = desc_k(xaddr), db = desc_mn(sb + r.slot * SLOT);
        turn_begin();
        wg_fence();
#pragma unroll
        for (int kk = 0; kk < 4; kk++) wgmma_ss_n256_tb(acc, desc_add(da, kk * 32), desc_add(db, kk * 2048), (kc | kk) != 0);
        wg_commit();
        turn_end();
        TR(13);
        wg_wait<1>();
        TR(15);
        if (kc > 0) {
          if (prev_w & 0x10000) release(bar_addr(sb, B_RG_EMPTY + ((prev_w >> 8) & 0xff)), lane, rank, false);
          release(bar_addr(sb, B_RG_EMPTY + (prev_w & 0xff)), lane, rank, false);
        }
        prev_w = r.slot;
        r.next();
      }
      wg_wait<0>();
      reg_fence(acc);
      TS(61); TR(16);
      release(bar_addr(sb, B_RG_EMPTY + xslot), lane, rank, false);
      release(bar_addr(sb, B_RG_EMPTY + prev_w), lane, rank, false);
#pragma unroll
      for (int i = 0; i < 64; i++) pk[i] = pack_bf16(acc[2 * i], acc[2 * i + 1]);
      mbar_wait(st_empty, 0);
      store_blocks<0, 4>(qreg, lane_base16(), pk);
      fence_async_smem();
      named_sync(1 + w, 128);
      TS(9); TR(19);
    }
#pragma unroll
    for (int i = 0; i < 128; i++) acc[i] = 0.f;
    float s[32];
#pragma unroll
    for (int i = 0; i < 32; i++) s[i] = 0.f;
    uint32_t pa[16];
    float m0 = -INFINITY, m1 = -INFINITY, l0 = 0.f, l1 = 0.f;
    const uint64_t dq = desc_k(qreg);
    uint64_t dk = 0, dqq = 0, dv = 0;
    auto prep_qk = [&](uint32_t kaddr) { dk = desc_k(kaddr); dqq = dq + (kaddr >> 31); asm volatile("" : "+l"(dk), "+l"(dqq)); };
    auto prep_pv = [&](uint32_t vaddr) { dv = desc_mn(vaddr); asm volatile("" : "+l"(dv)); };
    auto issue_qk = [&]() {
#pragma unroll
      for (int kk = 0; kk < 16; kk++)
        wgmma_ss_n64(s, desc_add(dqq, (kk >> 2) * 8192 + (kk & 3) * 32), desc_add(dk, (kk >> 2) * 8192 + (kk & 3) * 32), kk != 0);
    };
    auto issue_pv = [&](int accumulate) {
#pragma unroll
      for (int kk = 0; kk < 4; kk++)
        wgmma_rs_n256_tb(acc, pa[4 * kk], pa[4 * kk + 1], pa[4 * kk + 2], pa[4 * kk + 3], desc_add(dv, kk * 2048), accumulate | kk);
    };
    auto mask_diag = [&]() {
      const uint32_t ft = fresh_tid();
      const int r0 = 16 * ((ft >> 5) & 3) + ((ft & 31) >> 2), c = ft & 3;
#pragma unroll
      for (int jj = 0; jj < 8; jj++) {
        const int cc = 8 * jj + 2 * c;
        if (cc > r0)         s[4 * jj]     = -INFINITY;
        if (cc + 1 > r0)     s[4 * jj + 1] = -INFINITY;
        if (cc > r0 + 8)     s[4 * jj + 2] = -INFINITY;
        if (cc + 1 > r0 + 8) s[4 * jj + 3] = -INFINITY;
      }
    };
    float a0, a1;
    auto softmax = [&]() -> bool {
      float x0 = fmaxf(s[0], s[1]), x1 = fmaxf(s[2], s[3]);
#pragma unroll
      for (int jj = 1; jj < 8; jj++) {
        x0 = fmaxf(x0, fmaxf(s[4 * jj], s[4 * jj + 1]));
        x1 = fmaxf(x1, fmaxf(s[4 * jj + 2], s[4 * jj + 3]));
      }
      x0 = fmaxf(x0, __shfl_xor_sync(0xffffffffu, x0, 1));
      x1 = fmaxf(x1, __shfl_xor_sync(0xffffffffu, x1, 1));
      x0 = fmaxf(x0, __shfl_xor_sync(0xffffffffu, x0, 2));
      x1 = fmaxf(x1, __shfl_xor_sync(0xffffffffu, x1, 2));
      const bool grow = __any_sync(0xffffffffu, fmaxf(x0 - m0, x1 - m1) * SC > 8.f);
      if (grow) {
        x0 = fmaxf(x0, m0); x1 = fmaxf(x1, m1);
        a0 = ex2((m0 - x0) * SC); a1 = ex2((m1 - x1) * SC);
        m0 = x0; m1 = x1;
        l0 *= a0; l1 *= a1;
      }
      const float b0 = -m0 * SC, b1 = -m1 * SC;
      float t0 = 0.f, t1 = 0.f, t2 = 0.f, t3 = 0.f;
#pragma unroll
      for (int jj = 0; jj < 8; jj++) {
        s[4 * jj]     = ex2(fmaf(s[4 * jj], SC, b0));
        s[4 * jj + 1] = ex2(fmaf(s[4 * jj + 1], SC, b0));
        s[4 * jj + 2] = ex2(fmaf(s[4 * jj + 2], SC, b1));
        s[4 * jj + 3] = ex2(fmaf(s[4 * jj + 3], SC, b1));
        t0 += s[4 * jj]; t1 += s[4 * jj + 1]; t2 += s[4 * jj + 2]; t3 += s[4 * jj + 3];
      }
      l0 += t0 + t1; l1 += t2 + t3;
      return grow;
    };
    auto softmax_fast = [&]() -> bool {
      const float b0 = -m0 * SC, b1 = -m1 * SC;
      float t0 = 0.f, t1 = 0.f, t2 = 0.f, t3 = 0.f;
#pragma unroll
      for (int jj = 0; jj < 8; jj++) {
        s[4 * jj]     = ex2(fmaf(s[4 * jj], SC, b0));
        s[4 * jj + 1] = ex2(fmaf(s[4 * jj + 1], SC, b0));
        s[4 * jj + 2] = ex2(fmaf(s[4 * jj + 2], SC, b1));
        s[4 * jj + 3] = ex2(fmaf(s[4 * jj + 3], SC, b1));
        t0 += s[4 * jj]; t1 += s[4 * jj + 1]; t2 += s[4 * jj + 2]; t3 += s[4 * jj + 3];
      }
      t0 += t1; t2 += t3;
      uint32_t redo;
      asm volatile("{\n.reg .pred p, q;\nsetp.le.f32 p, %1, 0f47800000;\nbarrier.cta.red.or.aligned.pred q, %2, 128, !p;\nselp.u32 %0, 1, 0, q;\n}"
                   : "=r"(redo) : "f"(fmaxf(t0, t2) + (t0 - t0) + (t2 - t2)), "r"(RED_BAR + w) : "memory");
      if (!redo) { l0 += t0; l1 += t2; }
      return redo;
    };
    auto rescale = [&]() {
#pragma unroll
      for (int i = 0; i < 32; i++) { acc[4 * i] *= a0; acc[4 * i + 1] *= a0; acc[4 * i + 2] *= a1; acc[4 * i + 3] *= a1; }
    };
    auto to_p = [&]() {
#pragma unroll
      for (int i = 0; i < 16; i++) pa[i] = pack_bf16(s[2 * i], s[2 * i + 1]);
    };

    const int nseg = num_segs(h, j, which);
#pragma unroll 1
    for (int sg = 0; sg < nseg; sg++) {
      const Seg S = get_seg(h, j, which, sg);
      const bool skip = S.diag && w == 0;
      const int n = S.nt - (skip ? 1 : 0);
      auto take = [&]() { const uint32_t sl = r.slot; mbar_wait(bar_addr(sb, B_RG_FULL + sl), r.phase); r.next(); return sl; };
      auto give = [&](uint32_t sl) { release(bar_addr(sb, B_RG_EMPTY + sl), lane, rank, S.shared); };
      uint32_t ks = take();
      if (sg == 0) TS(62 + which);
      TR(20);
      prep_qk(sb + ks * SLOT);
      turn_begin();
      wg_fence();
      issue_qk();
      wg_commit();
      turn_end();
      TR(21);
      wg_wait<0>();
      TR(22);
      reg_fence(s);
      give(ks);
      const bool lastseg = which == 1 && sg == nseg - 1;
      if (lastseg && n == 1 && lane == 0) mbar_arrive(bar_addr(sb, B_QFREE + w));
      if (S.diag && n == 1) mask_diag();
      if (softmax() && sg > 0) rescale();
      to_p();
#pragma unroll 1
      for (int jj = 1; jj < n; jj++) {
        PCLK(c0);
        ks = take();
        PACC(pw_k, c0);
        PCLK(c1);
        const uint32_t vs = take();
        PACC(pw_v, c1);
        TR(30);
        prep_qk(sb + ks * SLOT);
        prep_pv(sb + vs * SLOT);
        PCLK(c5);
        turn_begin();
        PACC(pw_p1, c5);
        PCLK(c6);
        wg_fence();
        issue_qk();
        wg_commit();
        issue_pv((sg > 0) | (jj > 1));
        wg_commit();
        turn_end();
        PACC(pw_p1w, c6);
        PCLK(c2);
        TR(31);
        wg_wait<1>();
        TR(32);
        PACC(pw_qk, c2);
        reg_fence(s);
        PCLK(c3);
        if (S.diag && jj == n - 1) mask_diag();
        bool grow = false;
        if (softmax_fast()) {
          wg_fence();
          issue_qk();
          wg_commit();
          wg_wait<0>();
          reg_fence(s);
          if (S.diag && jj == n - 1) mask_diag();
          grow = softmax();
        }
        give(ks);
        if (lastseg && jj == n - 1 && lane == 0) mbar_arrive(bar_addr(sb, B_QFREE + w));
        PACC(pw_sm, c3);
        PCLK(c4);
        wg_wait<0>();
        PACC(pw_pv, c4);
        reg_fence(acc);
        reg_fence(pa);
        give(vs);
        if (grow) rescale();
        to_p();
      }
      if (skip) { give(take()); turn_begin(); turn_end(); }
      {
        const uint32_t vs = take();
        TR(40);
        prep_pv(sb + vs * SLOT);
        turn_begin();
        wg_fence();
        issue_pv((sg > 0) | (n > 1));
        wg_commit();
        turn_end();
        TR(41);
        wg_wait<0>();
        TR(42);
        reg_fence(acc);
        reg_fence(pa);
        give(vs);
      }
      if (skip) give(take());
    }
    TS(7 + 3 * which); TR(45);
    l0 += __shfl_xor_sync(0xffffffffu, l0, 1); l1 += __shfl_xor_sync(0xffffffffu, l1, 1);
    l0 += __shfl_xor_sync(0xffffffffu, l0, 2); l1 += __shfl_xor_sync(0xffffffffu, l1, 2);
    const float i0 = 1.f / l0, i1 = 1.f / l1;
#pragma unroll
    for (int i = 0; i < 32; i++) {
      pk[2 * i]     = pack_bf16(acc[4 * i] * i0, acc[4 * i + 1] * i0);
      pk[2 * i + 1] = pack_bf16(acc[4 * i + 2] * i1, acc[4 * i + 3] * i1);
    }
    if (which == 0) {
      store_blocks<0, 4>(qreg, lane_base16(), pk);
      fence_async_smem();
      warp_arrive(st_full, lane);
    }
    TS(8 + 3 * which); TR(46);
    if (which == 0) TS(31);
  }

  {
    float oa[32], ob[32];
#pragma unroll
    for (int i = 0; i < 32; i++) { oa[i] = 0.f; ob[i] = 0.f; }
    mbar_wait(bar_addr(sb, B_RG_FULL + FINAL_STG_SLOT), FINAL_STG_PHASE);
    const uint32_t stg2 = sb + FINAL_STG_SLOT * SLOT + w * 16384;
    auto stage_o = [&](float (&o)[32], int ch) {
      reg_fence(o);
      uint32_t q[16];
#pragma unroll
      for (int i = 0; i < 16; i++) q[i] = pack_bf16(o[2 * i], o[2 * i + 1]);
      if (ch >= 2) mbar_wait(bar_addr(sb, B_S2_EMPTY + w * 2 + (ch & 1)), ((ch >> 1) - 1) & 1);
      store_blocks<0, 1>(stg2 + (ch & 1) * 8192, lane_base16(), q);
    };
    auto hand_over = [&](int ch) {
      fence_async_smem();
      warp_arrive(bar_addr(sb, B_S2_FULL + w * 2 + (ch & 1)), lane);
    };
    uint32_t pk2[64];
#pragma unroll
    for (int i = 0; i < 64; i++) pk2[i] = 0;
    uint32_t p2 = 0;
    auto chunk = [&](int ch, auto odd, float (&o)[32], float (&oprev)[32]) {
      constexpr int I4 = decltype(odd)::value * 2;
      constexpr uint32_t s1 = fin_slot(I4), s2 = fin_slot(I4 + 1);
      const uint32_t f1 = FINAL_STG_PHASE ^ fin_wrap(I4) ^ ((ch >> 1) & 1), f2 = FINAL_STG_PHASE ^ fin_wrap(I4 + 1) ^ ((ch >> 1) & 1);
      const uint32_t z = (uint32_t)ch >> 8;
      mbar_wait(bar_addr(sb, B_RG_FULL + s1), f1);
      TR(50);
      const uint64_t d1 = desc_mn(sb + s1 * SLOT) + z;
      turn_begin();
      wg_fence();
#pragma unroll
      for (int kk = 0; kk < 16; kk++) {
        wgmma_rs_n64_tb(o, pk[4 * kk], pk[4 * kk + 1], pk[4 * kk + 2], pk[4 * kk + 3], desc_add(d1, kk * 2048), kk != 0);
        if (kk == ARRIVE_KK) turn_end();
      }
      wg_commit();
      TR(51);
      if (ch >= 1) {
        wg_wait<1>();
        if (ch <= 5) release(bar_addr(sb, B_RG_EMPTY + p2), lane, rank, true);
        stage_o(oprev, ch - 1);
      }
      mbar_wait(bar_addr(sb, B_RG_FULL + s2), f2);
      if (ch == 0) {
        mbar_wait(bar_addr(sb, B_CTXF + w), 0);
        const uint32_t t = fresh_tid(), ln = t & 31, row = 16 * ((t >> 5) & 3) + (ln & 15);
#pragma unroll
        for (int kk = 0; kk < 16; kk++) {
          uint32_t f[4];
          ldsm4(f, qreg + (kk >> 2) * 8192 + row * 128 + (((2 * (kk & 3) + (ln >> 4)) ^ (row & 7)) << 4));
          pk2[4 * kk] = f[0]; pk2[4 * kk + 1] = f[1]; pk2[4 * kk + 2] = f[2]; pk2[4 * kk + 3] = f[3];
        }
      }
      TR(53);
      const uint64_t d2 = desc_mn(sb + s2 * SLOT) + z;
      turn_begin();
      wg_fence();
#pragma unroll
      for (int kk = 0; kk < 16; kk++) {
        wgmma_rs_n64_tb(o, pk2[4 * kk], pk2[4 * kk + 1], pk2[4 * kk + 2], pk2[4 * kk + 3], desc_add(d2, kk * 2048), 1);
        if (kk == ARRIVE_KK && (ch < 6 || w == 0)) turn_end();
      }
      wg_commit();
      TR(54);
      if (ch >= 1) hand_over(ch - 1);
      wg_wait<1>();
      TR(55);
      if (ch <= 4) release(bar_addr(sb, B_RG_EMPTY + s1), lane, rank, true);
      p2 = s2;
    };
#pragma unroll 1
    for (int ch = 0; ch < 6; ch += 2) { chunk(ch, Int<0>(), oa, ob); chunk(ch + 1, Int<1>(), ob, oa); }
    chunk(6, Int<0>(), oa, ob);
    wg_wait<0>();
    TR(58);
    reg_fence(pk);
    reg_fence(pk2);
    stage_o(oa, 6);
    hand_over(6);
  }
  TS(12); TR(59);
  if ((threadIdx.x & 127) == 0) GT(54 + w);

  TS(16); TS(18); TS(17);
  TR(99); TR_END();
  TS(13); TSG(14);
}

#define CONV_STAGGER_NS 1200
namespace ssm {
constexpr int GROUPS = D_SPARE / 8 / NCONV;
constexpr uint32_t ZROWS = 16;
constexpr uint32_t PLANE = 2368;
constexpr uint32_t CHAN = 2 * PLANE + 16;
constexpr uint32_t XBUF = 8 * CHAN;
constexpr uint32_t OFF_X = 0;
constexpr uint32_t HCOPY = 4160;
constexpr uint32_t OFF_H = 2 * XBUF;
constexpr uint32_t HWARP = 3 * HCOPY;
constexpr uint32_t KBUF = 128 + 4096;
constexpr int NKV = 3;
constexpr uint32_t OFF_K = (OFF_H + 8 * HWARP + 127) / 128 * 128, OFF_V = OFF_K + NKV * KBUF, OFF_Q = OFF_V + NKV * 4096;
constexpr uint32_t END = OFF_Q + 3 * 4096;
static_assert(OFF_K % 128 == 0 && OFF_H % 16 == 0, "TMA destination alignment");
static_assert(END <= BARS, "smem");
enum : uint32_t { B_XREADY = 0, B_ZDONE = 2, B_KV = 4, B_Q = 8, B_HRAW = 12 };
constexpr int IO_BAR = 3, CW_BAR = 4;

__device__ __forceinline__ uint32_t row_addr(uint32_t xb, int beta) { return xb + ((beta & 1) ? 0 : PLANE) + (uint32_t)((beta >> 1) + ZROWS) * 16; }

__device__ __forceinline__ void io_warpgroup(const Params& p, uint32_t sb, int cidx) {
  const int tid = threadIdx.x & 127, lane = threadIdx.x & 31, wq = tid >> 5;
  constexpr int NCH = GROUPS * 8, NCQ = (GROUPS - 1) * 8;
  auto load_kv = [&](int sidx) {
    const int d0 = (cidx * GROUPS + (sidx >> 3)) * 8, row = (sidx & 7) * 256, b = sidx % NKV;
    const uint32_t bar = bar_addr(sb, B_KV + b);
    mbar_expect_tx(bar, KBUF + 4096);
    tma_ld2(sb + OFF_K + b * KBUF, &p.ak8, bar, d0, row - 8);
    tma_ld2(sb + OFF_K + b * KBUF + 128, &p.ak, bar, d0, row);
    tma_ld2(sb + OFF_V + b * 4096, &p.av, bar, d0, row);
  };
  auto load_q = [&](int e) {
    const uint32_t bar = bar_addr(sb, B_Q + e % 3);
    mbar_expect_tx(bar, 4096);
    tma_ld2(sb + OFF_Q + (e % 3) * 4096, &p.aq, bar, (cidx * GROUPS + (e >> 3)) * 8, (e & 7) * 256);
  };
  if (tid == 0) { for (int i = 0; i < NKV; i++) load_kv(i); load_q(0); load_q(1); }
  const uint32_t rowoff = (uint32_t)(8 * (8 * wq + (lane >> 3)) + 7 - (lane & 7)) * 16;
  const uint32_t xlane = (lane >> 2) * CHAN + (lane & 3) * 4;
  uint32_t sh[4];
  auto load_taps = [&](int grp) {
    const int d0 = (cidx * GROUPS + grp) * 8;
    const uint2 s0 = __ldg(reinterpret_cast<const uint2*>(p.a_shift + (d0 + 2 * (lane & 3)) * 4));
    const uint2 s1 = __ldg(reinterpret_cast<const uint2*>(p.a_shift + (d0 + 2 * (lane & 3) + 1) * 4));
    sh[0] = __byte_perm(s0.x, s1.x, 0x5410); sh[1] = __byte_perm(s0.x, s1.x, 0x7632);
    sh[2] = __byte_perm(s0.y, s1.y, 0x5410); sh[3] = __byte_perm(s0.y, s1.y, 0x7632);
  };
  auto pro_chunk = [&](int grp, int c) {
    const uint32_t xb = sb + OFF_X + (grp & 1) * XBUF + xlane;
    const int sidx = grp * 8 + c, b = sidx % NKV;
    mbar_wait(bar_addr(sb, B_KV + b), (sidx / NKV) & 1);
#pragma unroll
    for (int u = 0; u < 2; u++) {
      const uint32_t ka = sb + OFF_K + b * KBUF + 128 + rowoff + u * 512, va = sb + OFF_V + b * 4096 + rowoff + u * 512;
      uint32_t k0[4], k1[4], k2[4], k3[4], vv[4];
      ldsm4(k0, ka - 48); ldsm4(k1, ka - 32); ldsm4(k2, ka - 16); ldsm4(k3, ka); ldsm4(vv, va);
#pragma unroll
      for (int m = 0; m < 4; m++) {
        uint32_t ks = bmul(k0[m], sh[3]);
        ks = badd(ks, bmul(k1[m], sh[2]));
        ks = badd(ks, bmul(k2[m], sh[1]));
        ks = badd(ks, bmul(k3[m], sh[0]));
        const uint32_t x = transpose8(bmul(ks, vv[m]));
        const int beta = 32 * c + 8 * wq + 4 * u + m;
        asm volatile("st.shared.u32 [%0], %1;" :: "r"(row_addr(xb, beta)), "r"(x) : "memory");
      }
    }
  };
  auto epi_chunk = [&](int grp, int c) {
    const uint32_t xb = sb + OFF_X + (grp & 1) * XBUF + xlane;
    const int e = grp * 8 + c;
    const uint32_t qb = sb + OFF_Q + (e % 3) * 4096;
    mbar_wait(bar_addr(sb, B_Q + e % 3), (e / 3) & 1);
#pragma unroll
    for (int u = 0; u < 2; u++) {
      uint32_t qq[4], o[4];
      ldsm4(qq, qb + rowoff + u * 512);
#pragma unroll
      for (int m = 0; m < 4; m++) {
        const int beta = 32 * c + 8 * wq + 4 * u + m;
        o[m] = bmul(qq[m], transpose8(lds4(row_addr(xb, beta))));
      }
      stsm4(qb + rowoff + u * 512, o[0], o[1], o[2], o[3]);
    }
    fence_async_smem();
  };
#pragma unroll 1
  for (int grp = 0; grp < 2; grp++) {
    load_taps(grp);
#pragma unroll 1
    for (int c = 0; c < 8; c++) {
      pro_chunk(grp, c);
      named_sync(IO_BAR, 128);
      if (tid == 0 && grp * 8 + c + NKV < NCH) load_kv(grp * 8 + c + NKV);
    }
    warp_arrive(bar_addr(sb, B_XREADY + (grp & 1)), lane);
  }
#pragma unroll 1
  for (int grp = 0; grp + 1 < GROUPS; grp++) {
    const bool more = grp + 2 < GROUPS;
    if (more) load_taps(grp + 2);
    PCLK(c0);
    mbar_wait(bar_addr(sb, B_ZDONE + (grp & 1)), (grp >> 1) & 1);
    PACC(tp, c0);
    PCLK(c1);
#pragma unroll 1
    for (int c = 0; c < 8; c++) {
      epi_chunk(grp, c);
      if (more) pro_chunk(grp + 2, c);
      named_sync(IO_BAR, 128);
      if (tid == 0) {
        const int e = grp * 8 + c;
        tma_st2(&p.ao, sb + OFF_Q + (e % 3) * 4096, (cidx * GROUPS + grp) * 8, c * 256);
        bulk_commit();
        if (more && (grp + 2) * 8 + c + NKV < NCH) load_kv((grp + 2) * 8 + c + NKV);
        if (e + 2 < NCQ) {
          asm volatile("cp.async.bulk.wait_group.read 1;" ::: "memory");
          load_q(e + 2);
        }
      }
    }
    if (more) warp_arrive(bar_addr(sb, B_XREADY + (grp & 1)), lane);
    PACC(te, c1);
  }
  if (tid == 0) bulk_wait_all();
}

__device__ __forceinline__ void conv_warp(const Params& p, uint32_t sb, int cidx, int ch) {
  const int lane = threadIdx.x & 31, g = lane >> 2, c = lane & 3;
  const uint32_t hE0 = sb + OFF_H + ch * HWARP, hO = hE0 + HCOPY;
  const uint32_t hbar = bar_addr(sb, B_HRAW + ch);
  const int dbase = cidx * GROUPS * 8 + ch;
  auto fetch_h = [&](int grp) {
    if (lane == 0) {
      mbar_expect_tx(hbar, 4096);
      asm volatile("cp.async.bulk.shared::cluster.global.mbarrier::complete_tx::bytes [%0], [%1], %2, [%3];"
                   :: "r"(hE0 + (grp & 1) * 2 * HCOPY + 32), "l"(p.a_ssmk + (size_t)(dbase + 8 * grp) * SEQ), "r"(4096), "r"(hbar) : "memory");
    }
  };
  fetch_h(0);
  const uint32_t xlane = (uint32_t)g * CHAN + c * 4;
#pragma unroll 1
  for (int grp = 0; grp < GROUPS; grp++) {
    const uint32_t xc = sb + OFF_X + (grp & 1) * XBUF + ch * CHAN;
    const uint32_t Dd = (uint32_t)__ldg(reinterpret_cast<const unsigned short*>(p.a_D + dbase + 8 * grp)) * 0x10001u;
    PCLK(k0);
    mbar_wait(hbar, grp & 1);
    const uint32_t hE = hE0 + (grp & 1) * 2 * HCOPY;
    if (grp + 1 < GROUPS) fetch_h(grp + 1);
#pragma unroll
    for (int i = 0; i < 8; i++) {
      const uint32_t o = 32 + (i * 32 + lane) * 16;
      const uint4 w = lds16(hE + o);
      const uint32_t nx = lds4(hE + o + 16);
      sts16(hO + o, __byte_perm(w.x, w.y, 0x5432), __byte_perm(w.y, w.z, 0x5432), __byte_perm(w.z, w.w, 0x5432), __byte_perm(w.w, nx, 0x5432));
      if (o == 32) asm volatile("st.shared.u32 [%0], %1;" :: "r"(hO + 28), "r"(w.x << 16) : "memory");
    }
    __syncwarp();
    const uint32_t abase = (g & 1) == 0 ? hE + (7 - g + 2 * c + 1) * 2 : hO + (7 - g + 2 * c) * 2;
    mbar_wait(bar_addr(sb, B_XREADY + (grp & 1)), (grp >> 1) & 1);
    if (grp == 0 && ch >= 4) __nanosleep(CONV_STAGGER_NS);
    PACC(tw, k0);
    PCLK(k1);
    float acc[16][4];
#pragma unroll
    for (int i = 0; i < 16; i++) { acc[i][0] = 0.f; acc[i][1] = 0.f; acc[i][2] = 0.f; acc[i][3] = 0.f; }
    const uint32_t baddr = xc + ((lane >> 3) & 1) * PLANE + (ZROWS + (lane >> 4) * 8 + (lane & 7)) * 16;
#pragma unroll 1
    for (int r = 0; r < 8; r++) {
      uint32_t fa[16][4], fb[8][4];
#pragma unroll
      for (int i = 0; i < 8; i++) ldsm4(fb[i], baddr + i * 256 - r * 16);
#pragma unroll
      for (int jj = 0; jj < 16; jj++) {
        const uint32_t ad = abase + jj * 256 + r * 32;
        fa[jj][0] = lds4(ad); fa[jj][1] = lds4(ad + 16); fa[jj][2] = lds4v(ad + 16); fa[jj][3] = lds4(ad + 32);
      }
#pragma unroll
      for (int jj = 0; jj < 16; jj++)
#pragma unroll
        for (int sx = 0; sx < 16 - jj; sx++)
          mma16816(acc[jj + sx], fa[jj], fb[sx >> 1][2 * (sx & 1)], fb[sx >> 1][2 * (sx & 1) + 1]);
    }
    PACC(tm, k1);
    PCLK(k2);
#pragma unroll
    for (int nt = 0; nt < 16; nt++) {
      const uint32_t lo = transpose8(pack_bf16(acc[nt][0], acc[nt][1]));
      const uint32_t hi = transpose8(pack_bf16(acc[nt][2], acc[nt][3]));
      const uint32_t ad = xc + (ZROWS + 8 * nt) * 16 + lane * 4;
      const uint32_t x1 = lds4(ad + PLANE), x0 = lds4(ad);
      asm volatile("st.shared.u32 [%0], %1;" :: "r"(ad + PLANE), "r"(badd(lo, bmul(x1, Dd))) : "memory");
      asm volatile("st.shared.u32 [%0], %1;" :: "r"(ad), "r"(badd(hi, bmul(x0, Dd))) : "memory");
    }
    if (grp + 1 < GROUPS) warp_arrive(bar_addr(sb, B_ZDONE + (grp & 1)), lane);
    PACC(tr, k2);
  }
  {
    const int d0 = (cidx * GROUPS + GROUPS - 1) * 8;
    const uint32_t* qp = reinterpret_cast<const uint32_t*>(p.a_q + (size_t)(256 * ch + 7 - g) * DA + d0) + c;
    uint32_t qv[32];
#pragma unroll
    for (int i = 0; i < 32; i++) qv[i] = __ldg(qp + i * 8 * (DA / 2));
    named_sync(CW_BAR, 256);
    const uint32_t xb = sb + OFF_X + ((GROUPS - 1) & 1) * XBUF + xlane;
    uint32_t* op = reinterpret_cast<uint32_t*>(p.out + (size_t)(256 * ch + 7 - g) * OUTW + d0) + c;
#pragma unroll
    for (int i = 0; i < 32; i++) op[i * 8 * (OUTW / 2)] = bmul(qv[i], transpose8(lds4(row_addr(xb, 32 * ch + i))));
  }
}

__device__ __forceinline__ void init(uint32_t sb) {
  for (uint32_t i = threadIdx.x; i < END / 16; i += NTHREADS) sts16(sb + i * 16, 0, 0, 0, 0);
  if (threadIdx.x == 0) {
    for (int i = 0; i < 2; i++) { mbar_init(bar_addr(sb, B_XREADY + i), 4); mbar_init(bar_addr(sb, B_ZDONE + i), 8); }
    for (int i = 0; i < NKV; i++) mbar_init(bar_addr(sb, B_KV + i), 1);
    for (int i = 0; i < 3; i++) mbar_init(bar_addr(sb, B_Q + i), 1);
    for (int i = 0; i < 8; i++) mbar_init(bar_addr(sb, B_HRAW + i), 1);
  }
  fence_async_smem();
}
}

__device__ __forceinline__ void ssm_side_work(const Params& p, uint32_t sb, int h, int j, unsigned epoch) {
  const int lane = threadIdx.x & 31, g = lane >> 2, c = lane & 3;
  const int d0 = D_SPARE + 8 * h;
  uint8_t* xs = g_xs + (size_t)(h * 8 + g) * 2 * XS_PLANE + c * 4;
  auto xrow = [&](int beta) { return xs + ((beta & 1) ? 0 : XS_PLANE) + (16 + (beta >> 1)) * 16; };
  {
    const uint2 s0 = __ldg(reinterpret_cast<const uint2*>(p.a_shift + (d0 + 2 * c) * 4)), s1 = __ldg(reinterpret_cast<const uint2*>(p.a_shift + (d0 + 2 * c + 1) * 4));
    const uint32_t sh0 = __byte_perm(s0.x, s1.x, 0x5410), sh1 = __byte_perm(s0.x, s1.x, 0x7632);
    const uint32_t sh2 = __byte_perm(s0.y, s1.y, 0x5410), sh3 = __byte_perm(s0.y, s1.y, 0x7632);
    const uint32_t* kp = reinterpret_cast<const uint32_t*>(p.a_k + (size_t)(256 * j + 7 - g) * DA + d0) + c;
    const uint32_t* vp = reinterpret_cast<const uint32_t*>(p.a_v + (size_t)(256 * j + 7 - g) * DA + d0) + c;
    uint32_t kprev = j > 0 ? __ldg(kp - 8 * (DA / 2)) : 0u;
#pragma unroll 1
    for (int i0 = 0; i0 < 32; i0 += 8) {
      uint32_t kk[8], vv[8];
#pragma unroll
      for (int i = 0; i < 8; i++) { kk[i] = __ldg(kp + (i0 + i) * 8 * (DA / 2)); vv[i] = __ldg(vp + (i0 + i) * 8 * (DA / 2)); }
#pragma unroll
      for (int i = 0; i < 8; i++) {
        const uint32_t k2 = __shfl_sync(0xffffffffu, g < 1 ? kprev : kk[i], (lane + 4) & 31);
        const uint32_t k1 = __shfl_sync(0xffffffffu, g < 2 ? kprev : kk[i], (lane + 8) & 31);
        const uint32_t k0 = __shfl_sync(0xffffffffu, g < 3 ? kprev : kk[i], (lane + 12) & 31);
        uint32_t ks = bmul(k0, sh3);
        ks = badd(ks, bmul(k1, sh2)); ks = badd(ks, bmul(k2, sh1)); ks = badd(ks, bmul(kk[i], sh0));
        *reinterpret_cast<uint32_t*>(xrow(32 * j + i0 + i)) = transpose8(bmul(ks, vv[i]));
        kprev = kk[i];
      }
    }
    __syncwarp();
    if (lane == 0) {
      flag_signal(&g_flags.xs_ready[h].v);
      flag_wait(&g_flags.xs_ready[h].v, 8, epoch);
      fence_async_all();
      mbar_arrive(bar_addr(sb, B_XS));
    }
  }
  if (lane == 0) {
    mbar_wait(bar_addr(sb, B_CONV), 0);
    flag_signal(&g_flags.zs_ready[h].v);
    flag_wait(&g_flags.zs_ready[h].v, 8, epoch);
  }
  __syncwarp();
#pragma unroll 1
  for (int i0 = 0; i0 < 32; i0 += 8) {
    uint32_t zz[8], qv[8];
#pragma unroll
    for (int i = 0; i < 8; i++) {
      zz[i] = __ldcg(reinterpret_cast<const uint32_t*>(xrow(32 * j + i0 + i)));
      qv[i] = __ldg(reinterpret_cast<const uint32_t*>(p.a_q + (size_t)(256 * j + 8 * (i0 + i) + 7 - g) * DA + d0) + c);
    }
#pragma unroll
    for (int i = 0; i < 8; i++)
      reinterpret_cast<uint32_t*>(p.out + (size_t)(256 * j + 8 * (i0 + i) + 7 - g) * OUTW + d0)[c] = bmul(qv[i], transpose8(zz[i]));
  }
}

__global__ void __cluster_dims__(2, 1, 1) __launch_bounds__(NTHREADS, 1)
concat_heads__ssm_conv_h3__compressed_kv_cla__prompt_kernel(const __grid_constant__ Params p) {
  extern __shared__ uint8_t smem_raw[];
  const uint32_t sb = (smem_u32(smem_raw) + 1023) & ~1023u;
  const int warp = __shfl_sync(0xffffffffu, threadIdx.x >> 5, 0);
  const int wg = warp >> 2;
  const int cta = blockIdx.x;
  const bool attn = cta < NMAIN;
  int h, u;
  {
    const int c = cta >> 1;
    if (c < 4) { h = 15; u = c; }
    else if (c < 36) { h = (c - 4) & 7; u = (c - 4) >> 3; }
    else { h = 8 + (c - 36) % 7; u = (c - 36) / 7; }
  }
  const int j = 2 * u + (cta & 1);
  if (!attn) ssm::init(sb);
  if (attn && threadIdx.x == 0) {
    for (int i = 0; i < 4; i++) { mbar_init(bar_addr(sb, B_P1_FULL + i), 1); mbar_init(bar_addr(sb, B_P1_EMPTY + i), 16); }
    for (int i = 0; i < NSLOT; i++) {
      mbar_init(bar_addr(sb, B_RG_FULL + i), 1); mbar_init(bar_addr(sb, B_RG_EMPTY + i), 16); mbar_init(bar_addr(sb, B_PFREE + i), 1);
    }
    for (int i = 0; i < 2; i++) { mbar_init(bar_addr(sb, B_ST_FULL + i), 4); mbar_init(bar_addr(sb, B_ST_EMPTY + i), 1); }
    mbar_init(bar_addr(sb, B_XS), 1); mbar_init(bar_addr(sb, B_CONV), 8);
    for (int i = 0; i < 4; i++) { mbar_init(bar_addr(sb, B_S2_FULL + i), 4); mbar_init(bar_addr(sb, B_S2_EMPTY + i), 1); }
    for (int i = 0; i < 2; i++) { mbar_init(bar_addr(sb, B_QFREE + i), 4); mbar_init(bar_addr(sb, B_CTXF + i), 1); }
    asm volatile("fence.mbarrier_init.release.cluster;" ::: "memory");
  }
  if (attn && threadIdx.x == 32) {
    prefetch_map(&p.ckv); prefetch_map(&p.wuk); prefetch_map(&p.wuv); prefetch_map(&p.x); prefetch_map(&p.wq);
    prefetch_map(&p.kv); prefetch_map(&p.part); prefetch_map(&p.wo); prefetch_map(&p.ctx);
  }
  __syncwarp();
  asm volatile("barrier.cluster.arrive.release.aligned;" ::: "memory");
  if (attn && threadIdx.x == 0) {
    for (int k = 0; k < EARLY_LD; k++) {
      const uint32_t full = bar_addr(sb, B_P1_FULL + k), dst = sb + k * P1_STAGE;
      mbar_expect_tx(full, P1_STAGE);
      tma_ld2(dst, &p.ckv, full, k * 64, 2 * j * 128);
      load_tile4(dst + 16384, &p.wuk, full, k * 64, h * 4, j & 1, false);
    }
  }
  __syncwarp();
  asm volatile("barrier.cluster.wait.acquire.aligned;" ::: "memory");

  const int lane = threadIdx.x & 31;
  if (wg == 0) {
    if (!attn) {
      asm volatile("setmaxnreg.dec.sync.aligned.u32 72;");
      if (threadIdx.x == 0) GT(0);
      if (p.out != nullptr) ssm::io_warpgroup(p, sb, cta - NMAIN);
      if (threadIdx.x == 0) GT(14);
      return;
    }
    asm volatile("setmaxnreg.dec.sync.aligned.u32 40;");
    if (warp == 0) {
      if (lane == 0) producer_main(p, sb, h, j);
    } else if (warp < 3) {
      storer_main(p, sb, h, j, warp - 1);
    } else {
      const unsigned epoch = load_epoch();
      mbar_wait(bar_addr(sb, B_P1_FULL + 3), 0);
      __nanosleep(SIDE_DELAY_NS);
      ssm_side_work(p, sb, h, j, epoch);
      if (lane == 0) {
        asm volatile("red.relaxed.gpu.global.add.u64 [%0], 1;" :: "l"(&g_flags.done) : "memory");
      }
    }
  } else {
    if (!attn) {
      asm volatile("setmaxnreg.inc.sync.aligned.u32 216;");
      if (threadIdx.x == 128) { GT(12); PT(10); }
      if (p.out != nullptr) ssm::conv_warp(p, sb, cta - NMAIN, warp - 4);
      if (threadIdx.x == 128) { PT(9); GT(13); }
      return;
    }
    asm volatile("setmaxnreg.inc.sync.aligned.u32 232;");
    if (p.out != nullptr) {
      consumer_main(p, sb, h, j, wg - 1);
    }
  }
}

typedef CUresult (*EncodeTiledFn)(CUtensorMap*, CUtensorMapDataType, cuuint32_t, void*, const cuuint64_t*, const cuuint64_t*,
                                  const cuuint32_t*, const cuuint32_t*, CUtensorMapInterleave, CUtensorMapSwizzle,
                                  CUtensorMapL2promotion, CUtensorMapFloatOOBfill);

void make_map(EncodeTiledFn enc, CUtensorMap* m, const void* ptr, int rank, const uint64_t* dims, const uint64_t* strides, const uint32_t* box) {
  cuuint64_t d[3], s[2]; cuuint32_t b[3], e[3] = {1, 1, 1};
  for (int i = 0; i < rank; i++) { d[i] = dims[i]; b[i] = box[i]; if (i) s[i - 1] = strides[i - 1]; }
  enc(m, CU_TENSOR_MAP_DATA_TYPE_BFLOAT16, rank, const_cast<void*>(ptr), d, s, b, e, CU_TENSOR_MAP_INTERLEAVE_NONE,
      CU_TENSOR_MAP_SWIZZLE_128B, CU_TENSOR_MAP_L2_PROMOTION_L2_256B, CU_TENSOR_MAP_FLOAT_OOB_FILL_NONE);
}
void map2(EncodeTiledFn enc, CUtensorMap* m, const void* ptr, uint64_t cols, uint64_t rows, uint32_t bc, uint32_t br) {
  const uint64_t dims[2] = {cols, rows}, st[1] = {cols * 2}; const uint32_t box[2] = {bc, br};
  make_map(enc, m, ptr, 2, dims, st, box);
}
void map2_plain(EncodeTiledFn enc, CUtensorMap* m, const void* ptr, uint64_t cols, uint64_t rows, uint32_t bc, uint32_t br) {
  cuuint64_t d[2] = {cols, rows}, st[1] = {cols * 2}; cuuint32_t b[2] = {bc, br}, e[2] = {1, 1};
  enc(m, CU_TENSOR_MAP_DATA_TYPE_BFLOAT16, 2, const_cast<void*>(ptr), d, st, b, e, CU_TENSOR_MAP_INTERLEAVE_NONE,
      CU_TENSOR_MAP_SWIZZLE_NONE, CU_TENSOR_MAP_L2_PROMOTION_L2_128B, CU_TENSOR_MAP_FLOAT_OOB_FILL_NONE);
}
void map3(EncodeTiledFn enc, CUtensorMap* m, const void* ptr, uint64_t rows, uint32_t nblk) {
  const uint64_t dims[3] = {64, rows, 64}, st[2] = {8192, 128}; const uint32_t box[3] = {64, 64, nblk};
  make_map(enc, m, ptr, 3, dims, st, box);
}

}

extern "C" void kernel_launch(void* const* d_in, const int* in_sizes, int n_in, void* d_out, int out_size) {
  (void)in_sizes; (void)n_in; (void)out_size;
  static EncodeTiledFn enc = nullptr;
  static void *kv_ptr = nullptr, *acc_ptr = nullptr;
  if (!enc) {
    void* fn = nullptr; cudaDriverEntryPointQueryResult qr;
    cudaGetDriverEntryPoint("cuTensorMapEncodeTiled", &fn, cudaEnableDefault, &qr);
    enc = (EncodeTiledFn)fn;
    cudaGetSymbolAddress(&kv_ptr, g_kv);
    cudaGetSymbolAddress(&acc_ptr, g_ctx);
    cudaFuncSetAttribute(concat_heads__ssm_conv_h3__compressed_kv_cla__prompt_kernel, cudaFuncAttributeMaxDynamicSharedMemorySize, SMEM_BYTES);
  }
  Params p;
  p.a_q = (const bf16*)d_in[0]; p.a_k = (const bf16*)d_in[1]; p.a_v = (const bf16*)d_in[2];
  map2_plain(enc, &p.aq, d_in[0], DA, SEQ, 8, 256);
  map2_plain(enc, &p.ak, d_in[1], DA, SEQ, 8, 256);
  map2_plain(enc, &p.ak8, d_in[1], DA, SEQ, 8, 8);
  map2_plain(enc, &p.av, d_in[2], DA, SEQ, 8, 256);
  map2_plain(enc, &p.ao, d_out, OUTW, SEQ, 8, 256);
  p.a_shift = (const bf16*)d_in[3]; p.a_ssmk = (const bf16*)d_in[4]; p.a_D = (const bf16*)d_in[5];
  p.out = (bf16*)d_out;
  map2(enc, &p.x, d_in[6], DM, SEQ, 64, 128);
  map2(enc, &p.ckv, d_in[7], DC, SEQ, 64, 128);
  map3(enc, &p.wq, d_in[8], DM, 2);
  map3(enc, &p.wuk, d_in[9], DC, 2);
  map3(enc, &p.wuv, d_in[10], DC, 2);
  map2(enc, &p.wo, d_in[11], DM, NH * HD, 64, 128);
  {
    const uint64_t dims[3] = {64, 2 * NH * SEQ, 4}, st[2] = {HD * 2, 128}; const uint32_t box[3] = {64, 64, 2};
    make_map(enc, &p.kv, kv_ptr, 3, dims, st, box);
  }
  map2(enc, &p.part, d_out, OUTW, SEQ, 64, 64);
  {
    const uint64_t dims[3] = {64, NMAIN * 128, 4}, st[2] = {HD * 2, 128}; const uint32_t box[3] = {64, 64, 4};
    make_map(enc, &p.ctx, acc_ptr, 3, dims, st, box);
  }
  concat_heads__ssm_conv_h3__compressed_kv_cla__prompt_kernel<<<NCTA, NTHREADS, SMEM_BYTES>>>(p);
}
```

```cpp
#include <cuda_runtime.h>
#include <cuda_bf16.h>
#include <cuda.h>
#include <stdint.h>

namespace {

typedef __nv_bfloat16 bf16;

constexpr int SEQ  = 2048;
constexpr int DA   = 448;
constexpr int NH   = 16;
constexpr int HD   = 256;
constexpr int DM   = 448;
constexpr int DC   = 1024;
constexpr int OUTW = DA + DM;
constexpr int NMAIN = 128;
constexpr int NCONV = 4;
constexpr int NCTA  = NMAIN + NCONV;
constexpr int NTHREADS = 384;
constexpr int D_SPARE = 320;

__device__ __align__(1024) bf16 g_kv[2ull * SEQ * NH * HD];
__device__ __align__(1024) bf16 g_ctx[(size_t)NMAIN * 128 * HD];
constexpr uint32_t CV_PLANE = 2368, CV_HE = 2 * CV_PLANE, CV_HCOPY = 4160, CV_D = CV_HE + 4144, CV_BYTES = CV_HE + 2 * CV_HCOPY;
__device__ __align__(128) uint8_t g_xs[NMAIN * CV_BYTES];
struct alignas(128) Flag { unsigned v; unsigned pad[31]; };
struct Flags {
  Flag kv_ready[2 * NH];
  Flag ctx_ready[NMAIN * 2];
  Flag out_ready[16 * 2];
  Flag xs_ready[NH];
  Flag zs_ready[NH];
  alignas(128) unsigned long long done;
};
__device__ Flags g_flags;
#define TS(i)
#define TSG(i)
#define GT(i)
#define PT(i)
#define WHICH_TS 0
#define PCLK(var)
#define PACC(acc, t0)
#define PDECL
#define PDUMP()

#define TR_DECL
#define TR(tag)
#define TR_END()

struct alignas(64) Params {
  CUtensorMap ckv;
  CUtensorMap wuk;
  CUtensorMap wuv;
  CUtensorMap x;
  CUtensorMap wq;
  CUtensorMap kv;
  CUtensorMap part;
  CUtensorMap ctx;
  CUtensorMap ctxs;
  CUtensorMap wo;
  CUtensorMap ak, ak8, av, aq, ao;
  const bf16 *a_q, *a_k, *a_v, *a_shift, *a_ssmk, *a_D, *b_x, *b_wo;
  bf16* out;
};

constexpr uint32_t P1_STAGE = 49152;
constexpr uint32_t P1_STG   = 196608;
constexpr uint32_t SLOT     = 32768;
constexpr int      NSLOT    = 5;
constexpr uint32_t QREG     = 163840;
constexpr uint32_t CV_X = 4 * SLOT + 16384, CV_R = 3 * SLOT;
static_assert(CV_BYTES <= 16384 && CV_BYTES % 128 == 0, "SSM operands");
constexpr uint32_t BARS     = 229376;
constexpr uint32_t SMEM_BYTES = BARS + 512 + 1024;
enum : uint32_t {
  B_P1_FULL = 0, B_P1_EMPTY = 4, B_RG_FULL = 8, B_RG_EMPTY = 13, B_ST_FULL = 18, B_ST_EMPTY = 20,
  B_XS = 22, B_PFREE = 23, B_S2_FULL = 28, B_S2_EMPTY = 32, B_QFREE = 36, B_CTXF = 38, B_KV = 40, B_CONV = 42, B_GATE = 43, B_CTXS = 44, B_GFREE = 52, B_COUNT = 53
};

__device__ __forceinline__ uint32_t smem_u32(const void* p) { return (uint32_t)__cvta_generic_to_shared(p); }
__device__ __forceinline__ void mbar_init(uint32_t bar, uint32_t cnt) {
  asm volatile("mbarrier.init.shared::cta.b64 [%0], %1;" :: "r"(bar), "r"(cnt) : "memory");
}
__device__ __forceinline__ void mbar_expect_tx(uint32_t bar, uint32_t bytes) {
  asm volatile("mbarrier.arrive.expect_tx.shared::cta.b64 _, [%0], %1;" :: "r"(bar), "r"(bytes) : "memory");
}
__device__ __forceinline__ void mbar_arrive(uint32_t bar) {
  asm volatile("mbarrier.arrive.shared::cta.b64 _, [%0];" :: "r"(bar) : "memory");
}
__device__ __forceinline__ void mbar_arrive_n(uint32_t bar, uint32_t n) {
  asm volatile("mbarrier.arrive.shared::cta.b64 _, [%0], %1;" :: "r"(bar), "r"(n) : "memory");
}
__device__ __forceinline__ void mbar_arrive_remote(uint32_t bar, uint32_t cta) {
  asm volatile("{\n.reg .b32 ra;\nmapa.shared::cluster.u32 ra, %0, %1;\n"
               "mbarrier.arrive.shared::cluster.b64 _, [ra];\n}" :: "r"(bar), "r"(cta) : "memory");
}
__device__ __forceinline__ void mbar_arrive_remote_n(uint32_t bar, uint32_t cta, uint32_t n) {
  asm volatile("{\n.reg .b32 ra;\nmapa.shared::cluster.u32 ra, %0, %1;\n"
               "mbarrier.arrive.shared::cluster.b64 _, [ra], %2;\n}" :: "r"(bar), "r"(cta), "r"(n) : "memory");
}
__device__ __forceinline__ bool mbar_try(uint32_t bar, uint32_t parity) {
  uint32_t ok;
  asm volatile("{\n.reg .pred p;\nmbarrier.try_wait.parity.shared::cta.b64 p, [%1], %2;\nselp.u32 %0, 1, 0, p;\n}"
               : "=r"(ok) : "r"(bar), "r"(parity) : "memory");
  return ok;
}
constexpr uint32_t SPIN_LIMIT = 1u << 24;
__device__ __forceinline__ void mbar_wait(uint32_t bar, uint32_t parity) {
  if (mbar_try(bar, parity)) return;
  uint32_t n = 0;
  while (!mbar_try(bar, parity)) { if (++n > SPIN_LIMIT) __trap(); }
}
__device__ __forceinline__ void mbar_wait_slow(uint32_t bar, uint32_t parity) {
  uint32_t n = 0;
  while (!mbar_try(bar, parity)) { if (++n > (SPIN_LIMIT >> 4)) __trap(); __nanosleep(500); }
}
__device__ __forceinline__ unsigned load_epoch() {
  unsigned long long e; asm volatile("ld.relaxed.gpu.global.u64 %0, [%1];" : "=l"(e) : "l"(&g_flags.done) : "memory"); return (unsigned)(e / NMAIN);
}
__device__ __forceinline__ void flag_wait(const unsigned* f, unsigned count, unsigned epoch) {
  const unsigned target = (epoch + 1) * count;
  uint32_t n = 0;
  while (true) {
    unsigned v;
    asm volatile("ld.acquire.gpu.global.u32 %0, [%1];" : "=r"(v) : "l"(f) : "memory");
    if ((int)(v - target) >= 0) break;
    if (++n > SPIN_LIMIT) __trap();
    __nanosleep(20);
  }
}
__device__ __forceinline__ void flag_wait_fast(const unsigned* f, unsigned count, unsigned epoch) {
  const unsigned target = (epoch + 1) * count;
  uint32_t n = 0;
  while (true) {
    unsigned v;
    asm volatile("ld.acquire.gpu.global.u32 %0, [%1];" : "=r"(v) : "l"(f) : "memory");
    if ((int)(v - target) >= 0) break;
    if (++n > SPIN_LIMIT) __trap();
  }
}
__device__ __forceinline__ void fence_async_all() { asm volatile("fence.proxy.async;" ::: "memory"); }
__device__ __forceinline__ void flag_signal(unsigned* f) {
  asm volatile("fence.acq_rel.gpu;" ::: "memory");
  asm volatile("red.relaxed.gpu.global.add.u32 [%0], 1;" :: "l"(f) : "memory");
}
__device__ __forceinline__ void flag_signal_after_bulk(unsigned* f) {
  asm volatile("red.relaxed.gpu.global.add.u32 [%0], 1;" :: "l"(f) : "memory");
}
__device__ __forceinline__ void fence_async_smem() { asm volatile("fence.proxy.async.shared::cta;" ::: "memory"); }
__device__ __forceinline__ void tma_ld2(uint32_t dst, const CUtensorMap* m, uint32_t bar, int c0, int c1) {
  asm volatile("cp.async.bulk.tensor.2d.shared::cluster.global.mbarrier::complete_tx::bytes [%0], [%1, {%3, %4}], [%2];"
               :: "r"(dst), "l"(m), "r"(bar), "r"(c0), "r"(c1) : "memory");
}
__device__ __forceinline__ void tma_ld3(uint32_t dst, const CUtensorMap* m, uint32_t bar, int c0, int c1, int c2) {
  asm volatile("cp.async.bulk.tensor.3d.shared::cluster.global.mbarrier::complete_tx::bytes [%0], [%1, {%3, %4, %5}], [%2];"
               :: "r"(dst), "l"(m), "r"(bar), "r"(c0), "r"(c1), "r"(c2) : "memory");
}
__device__ __forceinline__ void tma_ld3_mc(uint32_t dst, const CUtensorMap* m, uint32_t bar, int c0, int c1, int c2) {
  asm volatile("cp.async.bulk.tensor.3d.shared::cluster.global.mbarrier::complete_tx::bytes.multicast::cluster [%0], [%1, {%3, %4, %5}], [%2], %6;"
               :: "r"(dst), "l"(m), "r"(bar), "r"(c0), "r"(c1), "r"(c2), "h"((uint16_t)3) : "memory");
}
__device__ __forceinline__ void bulk_ld(uint32_t dst, const void* src, uint32_t bytes, uint32_t bar) {
  asm volatile("cp.async.bulk.shared::cluster.global.mbarrier::complete_tx::bytes [%0], [%1], %2, [%3];"
               :: "r"(dst), "l"(src), "r"(bytes), "r"(bar) : "memory");
}
__device__ __forceinline__ void tma_st3(const CUtensorMap* m, uint32_t src, int c0, int c1, int c2) {
  asm volatile("cp.async.bulk.tensor.3d.global.shared::cta.bulk_group [%0, {%2, %3, %4}], [%1];"
               :: "l"(m), "r"(src), "r"(c0), "r"(c1), "r"(c2) : "memory");
}
__device__ __forceinline__ void tma_ld2_mc(uint32_t dst, const CUtensorMap* m, uint32_t bar, int c0, int c1) {
  asm volatile("cp.async.bulk.tensor.2d.shared::cluster.global.mbarrier::complete_tx::bytes.multicast::cluster [%0], [%1, {%3, %4}], [%2], %5;"
               :: "r"(dst), "l"(m), "r"(bar), "r"(c0), "r"(c1), "h"((uint16_t)3) : "memory");
}
__device__ __forceinline__ void tma_st2(const CUtensorMap* m, uint32_t src, int c0, int c1) {
  asm volatile("cp.async.bulk.tensor.2d.global.shared::cta.bulk_group [%0, {%2, %3}], [%1];"
               :: "l"(m), "r"(src), "r"(c0), "r"(c1) : "memory");
}
__device__ __forceinline__ void tma_red2(const CUtensorMap* m, uint32_t src, int c0, int c1) {
  asm volatile("cp.reduce.async.bulk.tensor.2d.global.shared::cta.add.tile.bulk_group [%0, {%2, %3}], [%1];"
               :: "l"(m), "r"(src), "r"(c0), "r"(c1) : "memory");
}
__device__ __forceinline__ void tma_pf3(const CUtensorMap* m, int c0, int c1, int c2) {
  asm volatile("cp.async.bulk.prefetch.tensor.3d.L2.global.tile [%0, {%1, %2, %3}];" :: "l"(m), "r"(c0), "r"(c1), "r"(c2) : "memory");
}
__device__ __forceinline__ void bulk_prefetch(const void* src, uint32_t bytes) {
  asm volatile("cp.async.bulk.prefetch.L2.global [%0], %1;" :: "l"(src), "r"(bytes) : "memory");
}
__device__ __forceinline__ void bulk_commit() { asm volatile("cp.async.bulk.commit_group;" ::: "memory"); }
__device__ __forceinline__ void bulk_wait_read() { asm volatile("cp.async.bulk.wait_group.read 0;" ::: "memory"); }
__device__ __forceinline__ void bulk_wait_all() { asm volatile("cp.async.bulk.wait_group 0;" ::: "memory"); }
__device__ __forceinline__ void prefetch_map(const CUtensorMap* m) { asm volatile("prefetch.tensormap [%0];" :: "l"(m) : "memory"); }
__device__ __forceinline__ void wg_fence() { asm volatile("wgmma.fence.sync.aligned;" ::: "memory"); }
__device__ __forceinline__ void wg_commit() { asm volatile("wgmma.commit_group.sync.aligned;" ::: "memory"); }
template <int N> __device__ __forceinline__ void wg_wait() { asm volatile("wgmma.wait_group.sync.aligned %0;" :: "n"(N) : "memory"); }
template <int N> __device__ __forceinline__ void reg_fence(float (&d)[N]) {
#pragma unroll
  for (int i = 0; i < N; i++) asm volatile("" : "+f"(d[i]) :: "memory");
}
template <int N> __device__ __forceinline__ void reg_fence(uint32_t (&d)[N]) {
#pragma unroll
  for (int i = 0; i < N; i++) asm volatile("" : "+r"(d[i]) :: "memory");
}
__device__ __forceinline__ uint32_t fresh_tid() { uint32_t t; asm volatile("mov.u32 %0, %%tid.x;" : "=r"(t)); return t; }
__device__ __forceinline__ uint32_t lane_base16() {
  const uint32_t t = fresh_tid(), lane = t & 31, wq = (t >> 5) & 3;
  return (16 * wq + (lane & 7) + 8 * ((lane >> 3) & 1)) * 128 + (((lane >> 4) ^ (lane & 7)) << 4);
}
__device__ __forceinline__ void named_sync(int id, int n) { asm volatile("bar.sync %0, %1;" :: "r"(id), "r"(n) : "memory"); }
__device__ __forceinline__ void named_arrive(int id, int n) { asm volatile("bar.arrive %0, %1;" :: "r"(id), "r"(n) : "memory"); }
__device__ __forceinline__ uint32_t pack_bf16(float lo, float hi) {
  uint32_t r; asm("cvt.rn.bf16x2.f32 %0, %1, %2;" : "=r"(r) : "f"(hi), "f"(lo)); return r;
}
__device__ __forceinline__ float ex2(float x) { float y; asm("ex2.approx.ftz.f32 %0, %1;" : "=f"(y) : "f"(x)); return y; }
__device__ __forceinline__ void stsm4(uint32_t addr, uint32_t a, uint32_t b, uint32_t c, uint32_t d) {
  asm volatile("stmatrix.sync.aligned.m8n8.x4.shared.b16 [%0], {%1, %2, %3, %4};" :: "r"(addr), "r"(a), "r"(b), "r"(c), "r"(d) : "memory");
}
__device__ __forceinline__ uint64_t mk_desc(uint32_t addr, uint32_t lbo, uint32_t sbo) {
  return (uint64_t)(((addr & 0x3FFFF) >> 4) | ((lbo >> 4) << 16)) | ((uint64_t)((sbo >> 4) | (1u << 30)) << 32);
}
__device__ __forceinline__ uint64_t desc_k(uint32_t addr)  { return mk_desc(addr, 16, 1024); }
__device__ __forceinline__ uint64_t desc_mn(uint32_t addr) { return mk_desc(addr, 8192, 1024); }
__device__ __forceinline__ uint64_t desc_add(uint64_t d, uint32_t bytes) { return d + (bytes >> 4); }

__device__ __forceinline__ void wgmma_ss_n256_tb(float (&d)[128], uint64_t da, uint64_t db, int sd) {
  asm volatile("{\n.reg .pred p;\nsetp.ne.b32 p, %130, 0;\n"
    "wgmma.mma_async.sync.aligned.m64n256k16.f32.bf16.bf16 "
    "{%0, %1, %2, %3, %4, %5, %6, %7, %8, %9, %10, %11, %12, %13, %14, %15, "
    "%16, %17, %18, %19, %20, %21, %22, %23, %24, %25, %26, %27, %28, %29, %30, %31, "
    "%32, %33, %34, %35, %36, %37, %38, %39, %40, %41, %42, %43, %44, %45, %46, %47, "
    "%48, %49, %50, %51, %52, %53, %54, %55, %56, %57, %58, %59, %60, %61, %62, %63, "
    "%64, %65, %66, %67, %68, %69, %70, %71, %72, %73, %74, %75, %76, %77, %78, %79, "
    "%80, %81, %82, %83, %84, %85, %86, %87, %88, %89, %90, %91, %92, %93, %94, %95, "
    "%96, %97, %98, %99, %100, %101, %102, %103, %104, %105, %106, %107, %108, %109, %110, %111, "
    "%112, %113, %114, %115, %116, %117, %118, %119, %120, %121, %122, %123, %124, %125, %126, %127}, "
    "%128, %129, p, 1, 1, 0, 1;\n}"
    : "+f"(d[0]), "+f"(d[1]), "+f"(d[2]), "+f"(d[3]), "+f"(d[4]), "+f"(d[5]), "+f"(d[6]), "+f"(d[7]),
      "+f"(d[8]), "+f"(d[9]), "+f"(d[10]), "+f"(d[11]), "+f"(d[12]), "+f"(d[13]), "+f"(d[14]), "+f"(d[15]),
      "+f"(d[16]), "+f"(d[17]), "+f"(d[18]), "+f"(d[19]), "+f"(d[20]), "+f"(d[21]), "+f"(d[22]), "+f"(d[23]),
      "+f"(d[24]), "+f"(d[25]), "+f"(d[26]), "+f"(d[27]), "+f"(d[28]), "+f"(d[29]), "+f"(d[30]), "+f"(d[31]),
      "+f"(d[32]), "+f"(d[33]), "+f"(d[34]), "+f"(d[35]), "+f"(d[36]), "+f"(d[37]), "+f"(d[38]), "+f"(d[39]),
      "+f"(d[40]), "+f"(d[41]), "+f"(d[42]), "+f"(d[43]), "+f"(d[44]), "+f"(d[45]), "+f"(d[46]), "+f"(d[47]),
      "+f"(d[48]), "+f"(d[49]), "+f"(d[50]), "+f"(d[51]), "+f"(d[52]), "+f"(d[53]), "+f"(d[54]), "+f"(d[55]),
      "+f"(d[56]), "+f"(d[57]), "+f"(d[58]), "+f"(d[59]), "+f"(d[60]), "+f"(d[61]), "+f"(d[62]), "+f"(d[63]),
      "+f"(d[64]), "+f"(d[65]), "+f"(d[66]), "+f"(d[67]), "+f"(d[68]), "+f"(d[69]), "+f"(d[70]), "+f"(d[71]),
      "+f"(d[72]), "+f"(d[73]), "+f"(d[74]), "+f"(d[75]), "+f"(d[76]), "+f"(d[77]), "+f"(d[78]), "+f"(d[79]),
      "+f"(d[80]), "+f"(d[81]), "+f"(d[82]), "+f"(d[83]), "+f"(d[84]), "+f"(d[85]), "+f"(d[86]), "+f"(d[87]),
      "+f"(d[88]), "+f"(d[89]), "+f"(d[90]), "+f"(d[91]), "+f"(d[92]), "+f"(d[93]), "+f"(d[94]), "+f"(d[95]),
      "+f"(d[96]), "+f"(d[97]), "+f"(d[98]), "+f"(d[99]), "+f"(d[100]), "+f"(d[101]), "+f"(d[102]), "+f"(d[103]),
      "+f"(d[104]), "+f"(d[105]), "+f"(d[106]), "+f"(d[107]), "+f"(d[108]), "+f"(d[109]), "+f"(d[110]), "+f"(d[111]),
      "+f"(d[112]), "+f"(d[113]), "+f"(d[114]), "+f"(d[115]), "+f"(d[116]), "+f"(d[117]), "+f"(d[118]), "+f"(d[119]),
      "+f"(d[120]), "+f"(d[121]), "+f"(d[122]), "+f"(d[123]), "+f"(d[124]), "+f"(d[125]), "+f"(d[126]), "+f"(d[127])
    : "l"(da), "l"(db), "r"(sd));
}
__device__ __forceinline__ void wgmma_ss_n64(float (&d)[32], uint64_t da, uint64_t db, int sd) {
  asm volatile("{\n.reg .pred p;\nsetp.ne.b32 p, %34, 0;\n"
    "wgmma.mma_async.sync.aligned.m64n64k16.f32.bf16.bf16 "
    "{%0, %1, %2, %3, %4, %5, %6, %7, %8, %9, %10, %11, %12, %13, %14, %15, "
    "%16, %17, %18, %19, %20, %21, %22, %23, %24, %25, %26, %27, %28, %29, %30, %31}, "
    "%32, %33, p, 1, 1, 0, 0;\n}"
    : "+f"(d[0]), "+f"(d[1]), "+f"(d[2]), "+f"(d[3]), "+f"(d[4]), "+f"(d[5]), "+f"(d[6]), "+f"(d[7]),
      "+f"(d[8]), "+f"(d[9]), "+f"(d[10]), "+f"(d[11]), "+f"(d[12]), "+f"(d[13]), "+f"(d[14]), "+f"(d[15]),
      "+f"(d[16]), "+f"(d[17]), "+f"(d[18]), "+f"(d[19]), "+f"(d[20]), "+f"(d[21]), "+f"(d[22]), "+f"(d[23]),
      "+f"(d[24]), "+f"(d[25]), "+f"(d[26]), "+f"(d[27]), "+f"(d[28]), "+f"(d[29]), "+f"(d[30]), "+f"(d[31])
    : "l"(da), "l"(db), "r"(sd));
}
__device__ __forceinline__ void wgmma_rs_n256_tb(float (&d)[128], uint32_t a0, uint32_t a1, uint32_t a2, uint32_t a3, uint64_t db, int sd) {
  asm volatile("{\n.reg .pred p;\nsetp.ne.b32 p, %133, 0;\n"
    "wgmma.mma_async.sync.aligned.m64n256k16.f32.bf16.bf16 "
    "{%0, %1, %2, %3, %4, %5, %6, %7, %8, %9, %10, %11, %12, %13, %14, %15, "
    "%16, %17, %18, %19, %20, %21, %22, %23, %24, %25, %26, %27, %28, %29, %30, %31, "
    "%32, %33, %34, %35, %36, %37, %38, %39, %40, %41, %42, %43, %44, %45, %46, %47, "
    "%48, %49, %50, %51, %52, %53, %54, %55, %56, %57, %58, %59, %60, %61, %62, %63, "
    "%64, %65, %66, %67, %68, %69, %70, %71, %72, %73, %74, %75, %76, %77, %78, %79, "
    "%80, %81, %82, %83, %84, %85, %86, %87, %88, %89, %90, %91, %92, %93, %94, %95, "
    "%96, %97, %98, %99, %100, %101, %102, %103, %104, %105, %106, %107, %108, %109, %110, %111, "
    "%112, %113, %114, %115, %116, %117, %118, %119, %120, %121, %122, %123, %124, %125, %126, %127}, "
    "{%128, %129, %130, %131}, %132, p, 1, 1, 1;\n}"
    : "+f"(d[0]), "+f"(d[1]), "+f"(d[2]), "+f"(d[3]), "+f"(d[4]), "+f"(d[5]), "+f"(d[6]), "+f"(d[7]),
      "+f"(d[8]), "+f"(d[9]), "+f"(d[10]), "+f"(d[11]), "+f"(d[12]), "+f"(d[13]), "+f"(d[14]), "+f"(d[15]),
      "+f"(d[16]), "+f"(d[17]), "+f"(d[18]), "+f"(d[19]), "+f"(d[20]), "+f"(d[21]), "+f"(d[22]), "+f"(d[23]),
      "+f"(d[24]), "+f"(d[25]), "+f"(d[26]), "+f"(d[27]), "+f"(d[28]), "+f"(d[29]), "+f"(d[30]), "+f"(d[31]),
      "+f"(d[32]), "+f"(d[33]), "+f"(d[34]), "+f"(d[35]), "+f"(d[36]), "+f"(d[37]), "+f"(d[38]), "+f"(d[39]),
      "+f"(d[40]), "+f"(d[41]), "+f"(d[42]), "+f"(d[43]), "+f"(d[44]), "+f"(d[45]), "+f"(d[46]), "+f"(d[47]),
      "+f"(d[48]), "+f"(d[49]), "+f"(d[50]), "+f"(d[51]), "+f"(d[52]), "+f"(d[53]), "+f"(d[54]), "+f"(d[55]),
      "+f"(d[56]), "+f"(d[57]), "+f"(d[58]), "+f"(d[59]), "+f"(d[60]), "+f"(d[61]), "+f"(d[62]), "+f"(d[63]),
      "+f"(d[64]), "+f"(d[65]), "+f"(d[66]), "+f"(d[67]), "+f"(d[68]), "+f"(d[69]), "+f"(d[70]), "+f"(d[71]),
      "+f"(d[72]), "+f"(d[73]), "+f"(d[74]), "+f"(d[75]), "+f"(d[76]), "+f"(d[77]), "+f"(d[78]), "+f"(d[79]),
      "+f"(d[80]), "+f"(d[81]), "+f"(d[82]), "+f"(d[83]), "+f"(d[84]), "+f"(d[85]), "+f"(d[86]), "+f"(d[87]),
      "+f"(d[88]), "+f"(d[89]), "+f"(d[90]), "+f"(d[91]), "+f"(d[92]), "+f"(d[93]), "+f"(d[94]), "+f"(d[95]),
      "+f"(d[96]), "+f"(d[97]), "+f"(d[98]), "+f"(d[99]), "+f"(d[100]), "+f"(d[101]), "+f"(d[102]), "+f"(d[103]),
      "+f"(d[104]), "+f"(d[105]), "+f"(d[106]), "+f"(d[107]), "+f"(d[108]), "+f"(d[109]), "+f"(d[110]), "+f"(d[111]),
      "+f"(d[112]), "+f"(d[113]), "+f"(d[114]), "+f"(d[115]), "+f"(d[116]), "+f"(d[117]), "+f"(d[118]), "+f"(d[119]),
      "+f"(d[120]), "+f"(d[121]), "+f"(d[122]), "+f"(d[123]), "+f"(d[124]), "+f"(d[125]), "+f"(d[126]), "+f"(d[127])
    : "r"(a0), "r"(a1), "r"(a2), "r"(a3), "l"(db), "r"(sd));
}
__device__ __forceinline__ void wgmma_rs_n64_tb(float (&d)[32], uint32_t a0, uint32_t a1, uint32_t a2, uint32_t a3, uint64_t db, int sd) {
  asm volatile("{\n.reg .pred p;\nsetp.ne.b32 p, %37, 0;\n"
    "wgmma.mma_async.sync.aligned.m64n64k16.f32.bf16.bf16 "
    "{%0, %1, %2, %3, %4, %5, %6, %7, %8, %9, %10, %11, %12, %13, %14, %15, "
    "%16, %17, %18, %19, %20, %21, %22, %23, %24, %25, %26, %27, %28, %29, %30, %31}, "
    "{%32, %33, %34, %35}, %36, p, 1, 1, 1;\n}"
    : "+f"(d[0]), "+f"(d[1]), "+f"(d[2]), "+f"(d[3]), "+f"(d[4]), "+f"(d[5]), "+f"(d[6]), "+f"(d[7]),
      "+f"(d[8]), "+f"(d[9]), "+f"(d[10]), "+f"(d[11]), "+f"(d[12]), "+f"(d[13]), "+f"(d[14]), "+f"(d[15]),
      "+f"(d[16]), "+f"(d[17]), "+f"(d[18]), "+f"(d[19]), "+f"(d[20]), "+f"(d[21]), "+f"(d[22]), "+f"(d[23]),
      "+f"(d[24]), "+f"(d[25]), "+f"(d[26]), "+f"(d[27]), "+f"(d[28]), "+f"(d[29]), "+f"(d[30]), "+f"(d[31])
    : "r"(a0), "r"(a1), "r"(a2), "r"(a3), "l"(db), "r"(sd));
}

__device__ __forceinline__ uint4 lds16(uint32_t a) {
  uint4 v; asm volatile("ld.shared.v4.u32 {%0, %1, %2, %3}, [%4];" : "=r"(v.x), "=r"(v.y), "=r"(v.z), "=r"(v.w) : "r"(a) : "memory"); return v;
}
__device__ __forceinline__ void sts16(uint32_t a, uint32_t x, uint32_t y, uint32_t z, uint32_t w) {
  asm volatile("st.shared.v4.u32 [%0], {%1, %2, %3, %4};" :: "r"(a), "r"(x), "r"(y), "r"(z), "r"(w) : "memory");
}
__device__ __forceinline__ uint32_t lds4(uint32_t a) { uint32_t v; asm volatile("ld.shared.u32 %0, [%1];" : "=r"(v) : "r"(a) : "memory"); return v; }
__device__ __forceinline__ uint32_t lds4v(uint32_t a) { uint32_t v; asm volatile("ld.volatile.shared.u32 %0, [%1];" : "=r"(v) : "r"(a) : "memory"); return v; }
__device__ __forceinline__ uint32_t bmul(uint32_t a, uint32_t b) { uint32_t r; asm("mul.rn.bf16x2 %0, %1, %2;" : "=r"(r) : "r"(a), "r"(b)); return r; }
__device__ __forceinline__ uint32_t badd(uint32_t a, uint32_t b) { uint32_t r; asm("add.rn.bf16x2 %0, %1, %2;" : "=r"(r) : "r"(a), "r"(b)); return r; }

__device__ __forceinline__ void ldsm4(uint32_t (&r)[4], uint32_t a) {
  asm volatile("ldmatrix.sync.aligned.m8n8.x4.shared.b16 {%0, %1, %2, %3}, [%4];" : "=r"(r[0]), "=r"(r[1]), "=r"(r[2]), "=r"(r[3]) : "r"(a) : "memory");
}
__device__ __forceinline__ void ldsm4t(uint32_t (&r)[4], uint32_t a) {
  asm volatile("ldmatrix.sync.aligned.m8n8.x4.trans.shared.b16 {%0, %1, %2, %3}, [%4];" : "=r"(r[0]), "=r"(r[1]), "=r"(r[2]), "=r"(r[3]) : "r"(a) : "memory");
}
__device__ __forceinline__ uint32_t transpose8(uint32_t a) { uint32_t d; asm volatile("movmatrix.sync.aligned.m8n8.trans.b16 %0, %1;" : "=r"(d) : "r"(a)); return d; }

__device__ __forceinline__ void mma16816(float (&d)[4], const uint32_t (&a)[4], uint32_t b0, uint32_t b1) {
  asm volatile("mma.sync.aligned.m16n8k16.row.col.f32.bf16.bf16.f32 {%0, %1, %2, %3}, {%4, %5, %6, %7}, {%8, %9}, {%0, %1, %2, %3};"
               : "+f"(d[0]), "+f"(d[1]), "+f"(d[2]), "+f"(d[3]) : "r"(a[0]), "r"(a[1]), "r"(a[2]), "r"(a[3]), "r"(b0), "r"(b1));
}

#define P1_SPLIT 0
#define O_ROT 1
#define STG_K1 2
#define STG_K2 10
#define STG_Q1 2
#define STG_Q2 6
#define CTX_K 0
#define PF_QA 99
#define PF_WV 99
#define PF_END 0
#define PF_CV 1
#define PACE_A 850
#define PACE_B 400
#define ARRIVE_KK 12
#define SIDE_DELAY_NS 4000
#define KVH(h) (h)
#define HEAD_MAP 1
#define EARLY_LD 3
constexpr int RED_BAR = 6;
constexpr int CV_BAR = 5;
constexpr int PP_BAR = 3;
template <int V> struct Int { static constexpr int value = V; };
struct Ring {
  uint32_t slot, phase;
  __device__ __forceinline__ void next() { if (++slot == NSLOT) { slot = 0; phase ^= 1; } }
};
__device__ __forceinline__ uint32_t bar_addr(uint32_t sb, uint32_t i) { return sb + BARS + 8 * i; }
__device__ __forceinline__ uint32_t q_region(uint32_t sb, int w) { return sb + QREG + (w ^ 1) * 32768; }

struct Role { int h, j; };
__device__ __forceinline__ Role get_role() {
  int cta; asm volatile("mov.u32 %0, %%ctaid.x;" : "=r"(cta));
  const int c = cta >> 1;
  int h, u;
  if (c < 4) { h = 15; u = c; }
  else if (c < 36) { h = (c - 4) & 7; u = (c - 4) >> 3; }
  else { h = 8 + (c - 36) % 7; u = (c - 36) / 7; }
  return Role{h, 2 * u + (cta & 1)};
}
__device__ __forceinline__ int fresh_warp() { return __shfl_sync(0xffffffffu, fresh_tid() >> 5, 0); }

__device__ __forceinline__ int q_tile(int h, int j, int which) { return ((h < 8) == (which == 0)) ? 15 - j : j; }

__device__ __forceinline__ int o_chunk(int h, int c) { const int x = c + O_ROT * (h & 7); return x % 7; }

__device__ __forceinline__ int num_private(int qt) { return (qt & 1) ? 5 : 1; }
__device__ __forceinline__ void ring_acquire(uint32_t sb, Ring& r, uint32_t bytes) {
  mbar_wait(bar_addr(sb, B_RG_EMPTY + r.slot), r.phase ^ 1);
  mbar_expect_tx(bar_addr(sb, B_RG_FULL + r.slot), bytes);
}
__device__ __forceinline__ void load_tile4(uint32_t dst, const CUtensorMap* m, uint32_t full, int row, int blk0, int rank, bool shared) {
  if (shared) {
    tma_ld3_mc(dst + rank * 16384, m, full, 0, row, blk0 + 2 * rank);
  } else {
    tma_ld3(dst, m, full, 0, row, blk0);
    tma_ld3(dst + 16384, m, full, 0, row, blk0 + 2);
  }
}
__device__ __forceinline__ void producer_main(const Params& p, uint32_t sb) {
  const Role ro = get_role();
  const int h = ro.h, j = ro.j, rank = j & 1;
  auto prefetch_q = [&](int qt) {
    bulk_prefetch(p.b_x + (size_t)(qt * 128 + (h & 7) * 16) * DM, 16 * DM * 2);
    if (j < 7) { tma_pf3(&p.wq, 0, j * 64, h * 4); tma_pf3(&p.wq, 0, j * 64, h * 4 + 2); }
  };
  for (int it = EARLY_LD; it < 71; it++) {
    const int t = it >> 4, k = it & 15, s = it & 3;
    mbar_wait(bar_addr(sb, B_P1_EMPTY + s), ((it >> 2) & 1) ^ 1);
    const uint32_t full = bar_addr(sb, B_P1_FULL + s), dst = sb + s * P1_STAGE;
    mbar_expect_tx(full, P1_STAGE);
    if (t < 4) {
      tma_ld2(dst, &p.ckv, full, k * 64, (2 * j + (t & 1)) * 128);
      load_tile4(dst + 16384, (t >> 1) ? &p.wuv : &p.wuk, full, k * 64, h * 4, rank, true);
    } else {
      tma_ld2(dst, &p.x, full, k * 64, q_tile(h, j, 0) * 128);
      load_tile4(dst + 16384, &p.wq, full, k * 64, h * 4, rank, true);
    }
    if (it == PF_QA) prefetch_q(q_tile(h, j, 0));
    if (it == PF_WV) { for (int i = 0; i < 4; i++) tma_pf3(&p.wuv, 0, (2 * j + (i >> 1)) * 64, h * 4 + 2 * (i & 1)); }
  }
  mbar_wait(bar_addr(sb, B_P1_EMPTY + 3), 0);
  mbar_wait(bar_addr(sb, B_XS), 0);
  mbar_expect_tx(bar_addr(sb, B_RG_FULL + 4), CV_BYTES);
  bulk_ld(sb + CV_X, g_xs + (size_t)(h * 8 + j) * CV_BYTES, CV_BYTES, bar_addr(sb, B_RG_FULL + 4));
  Ring r{0, 1};
  int hs = 5;
  auto acquire = [&](bool shared) {
    mbar_wait(bar_addr(sb, B_RG_EMPTY + r.slot), r.phase ^ 1);
    if (shared && hs < 5) {
      mbar_arrive_remote(bar_addr(sb, B_PFREE + r.slot), rank ^ 1);
      mbar_wait(bar_addr(sb, B_PFREE + r.slot), 0);
      hs++;
    }
    mbar_expect_tx(bar_addr(sb, B_RG_FULL + r.slot), 32768);
  };
  mbar_wait(bar_addr(sb, B_KV), 0);
  for (int which = 0; which < 2; which++) {
    const int qt = q_tile(h, j, which);
    if (which == 1) {
      for (int kc = 0; kc < 7; kc++) {
        ring_acquire(sb, r, 32768);
        load_tile4(sb + r.slot * SLOT, &p.wq, bar_addr(sb, B_RG_FULL + r.slot), kc * 64, h * 4, rank, false);
        r.next();
        if (kc == 0 || (kc & 1)) {
          ring_acquire(sb, r, kc == 0 ? 16384 : 32768);
          const uint32_t full = bar_addr(sb, B_RG_FULL + r.slot), dst = sb + r.slot * SLOT;
          tma_ld2(dst, &p.x, full, kc * 64, qt * 128);
          if (kc > 0) tma_ld2(dst + 16384, &p.x, full, kc * 64 + 64, qt * 128);
          r.next();
        }
      }
      hs = 0;
    }
    const int n = 2 * qt + 2, npriv = num_private(qt), nb = qt & ~1;
    for (int f = 0; f < 2 * n; f++) {
      if (PF_END && f == max(2 * n - PF_END, 0)) {
        if (which == 0) bulk_prefetch(p.b_x + (size_t)((15 - qt) * 128 + (h & 7) * 16) * DM, 16 * DM * 2);
        else bulk_prefetch(p.b_wo + (size_t)(h * HD + j * 32) * DM, 32 * DM * 2);
      }
      const bool isK = (f == 0) || ((f & 1) && f < 2 * n - 1);
      const int i = isK ? (f + 1) >> 1 : (f == 2 * n - 1 ? n - 1 : (f >> 1) - 1);
      int tile = n - 1 - i;
      if (which == 0) { const int b = i >> 1; tile = b >= nb ? i : 2 * (2 * b < nb ? 2 * b : 2 * b - nb + 1) + (i & 1); }
      if (!isK && (tile & 2)) mbar_wait(bar_addr(sb, B_KV + 1), 0);
      if (which == 0 && f < 2) mbar_wait(bar_addr(sb, B_P1_EMPTY + f), 1);
      const bool shared = (which ? f : 2 * n - 1 - f) >= npriv;
      acquire(shared);
      load_tile4(sb + r.slot * SLOT, &p.kv, bar_addr(sb, B_RG_FULL + r.slot), ((isK ? 0 : NH) + KVH(h)) * SEQ + tile * 64, 0, rank, shared);
      r.next();
    }
  }
  for (int i = 0; i < 14; i++) {
    acquire(true);
    tma_ld2_mc(sb + r.slot * SLOT + rank * 16384, &p.wo, bar_addr(sb, B_RG_FULL + r.slot), o_chunk(h, i >> 1) * 64, ((i & 1) ? h ^ 8 : h) * HD + rank * 128);
    r.next();
  }
}

__device__ __forceinline__ void storer_main(const Params& p, uint32_t sb) {
  const Role ro = get_role();
  const int h = ro.h, j = ro.j, w = fresh_warp() - 1;
  const uint32_t full = bar_addr(sb, B_ST_FULL + w), empty = bar_addr(sb, B_ST_EMPTY + w);
  const int lane = threadIdx.x & 31;
  const unsigned epoch = load_epoch();
  for (int job = 0; job < 8; job++) {
    const int t = job >> 1, half = job & 1;
    mbar_wait(full, job & 1);
    const uint32_t src = sb + P1_STG + w * 16384 + (lane >> 3) * 128;
    bf16* dst = g_kv + (size_t)(((t >> 1) * NH + KVH(h)) * SEQ + (2 * j + (t & 1)) * 128 + w * 64 + (lane >> 3)) * HD + half * 128 + (lane & 7) * 8;
    const uint32_t t0 = (uint32_t)clock(), pace = job < 6 ? PACE_A : PACE_B;
#pragma unroll 1
    for (int i0 = 0; i0 < 32; i0 += 4) {
      while ((uint32_t)clock() - t0 < (i0 >> 2) * pace) __nanosleep(40);
#pragma unroll
      for (int i = i0; i < i0 + 4; i++) {
        const int r4 = (i & 15) * 4;
        const uint4 v = lds16(src + (i >> 4) * 8192 + r4 * 128 + (((lane & 7) ^ ((r4 + (lane >> 3)) & 7)) << 4));
        *reinterpret_cast<uint4*>(dst + r4 * HD + (i >> 4) * 64) = v;
      }
    }
    __syncwarp();
    if (lane == 0) {
      mbar_arrive(empty);
      if (job == 5 || job == 7) flag_signal(&g_flags.kv_ready[2 * h + (job == 7)].v);
    }
    __syncwarp();
  }
  const int cta = h * 8 + j, qt = q_tile(h, j, 1);
  const uint32_t qreg = q_region(sb, w);
  {
    mbar_wait(bar_addr(sb, B_CTXS + 4 * w), 0);
    uint4* z = reinterpret_cast<uint4*>(p.out + (size_t)(qt * 128 + w * 64 + (h & 7) * 8 + (lane >> 2)) * OUTW + DA) + (lane & 3);
#pragma unroll
    for (int i = 0; i < 14; i++) z[4 * i] = make_uint4(0, 0, 0, 0);
    __syncwarp();
    if (lane != 0) return;
    for (int b = 0; b < 4; b++) {
      mbar_wait(bar_addr(sb, B_CTXS + 4 * w + b), 0);
      tma_st3(&p.ctxs, qreg + b * 8192, 0, cta * 128 + w * 64, b);
      bulk_commit();
    }
    bulk_wait_read();
    mbar_arrive(empty);
    bulk_wait_all();
    flag_signal(&g_flags.ctx_ready[cta * 2 + w].v);
    flag_signal_after_bulk(&g_flags.out_ready[qt * 2 + w].v);
  }
  {
    const int wx = w ^ 1;
    flag_wait(&g_flags.ctx_ready[(cta ^ 64) * 2 + wx].v, 1, epoch);
    flag_wait(&g_flags.out_ready[qt * 2 + wx].v, 8, epoch);
    fence_async_all();
    mbar_wait(bar_addr(sb, B_QFREE + w), 0);
    mbar_expect_tx(bar_addr(sb, B_CTXF + w), 32768);
    tma_ld3(qreg, &p.ctx, bar_addr(sb, B_CTXF + w), 0, (cta ^ 64) * 128 + wx * 64, 0);
    for (int ch = 0; ch < 7; ch++) {
      const int b = ch & 1;
      mbar_wait(bar_addr(sb, B_S2_FULL + w * 2 + b), (ch >> 1) & 1);
      tma_red2(&p.part, qreg + b * 8192, DA + o_chunk(h, ch) * 64, qt * 128 + wx * 64);
      bulk_commit();
      if (ch == 0 && w == 1) mbar_arrive(bar_addr(sb, B_GFREE));
      bulk_wait_read();
      mbar_arrive(bar_addr(sb, B_S2_EMPTY + w * 2 + b));
    }
    GT(48 + w);
    bulk_wait_all();
    GT(50 + w); GT(52 + w); GT(56);
  }
}

template <int OFF, int NB, int NREG>
__device__ __forceinline__ void store_blocks(uint32_t base, uint32_t lanebase, const uint32_t (&pk)[NREG]) {
#pragma unroll
  for (int J = 0; J < NB * 8; J += 2) {
    const uint32_t a = base + (J >> 3) * 8192 + (lanebase ^ ((J & 7) << 4));
    stsm4(a, pk[OFF + 2 * J], pk[OFF + 2 * J + 1], pk[OFF + 2 * J + 2], pk[OFF + 2 * J + 3]);
  }
}
__device__ __forceinline__ void warp_arrive(uint32_t bar, int lane) { __syncwarp(); if (lane == 0) mbar_arrive(bar); }
__device__ __forceinline__ void release(uint32_t bar, int lane, int rank, bool shared) {
  if (shared) { if (lane < 2) mbar_arrive_remote(bar, rank ^ lane); }
  else if (lane == 0) mbar_arrive_n(bar, 2);
}

template <int W> __device__ __forceinline__ constexpr int cv_tile(int u) { return 2 * u + ((u ^ W) & 1); }
template <int W>
__device__ __forceinline__ void conv_mma(float (&ca)[8][4], uint32_t abase, uint32_t baddr) {
#pragma unroll 1
  for (int rr = 0; rr < 2; rr++) {
    uint32_t fa[16][4], fb[8][4];
#pragma unroll
    for (int i = 0; i < 8; i++) ldsm4(fb[i], baddr + i * 256 - rr * 16);
#pragma unroll
    for (int jj = 0; jj < 16 - W; jj++) {
      const uint32_t ad = abase + jj * 256 + rr * 32;
      fa[jj][0] = lds4(ad); fa[jj][1] = lds4(ad + 16); fa[jj][2] = lds4v(ad + 16); fa[jj][3] = lds4(ad + 32);
    }
#pragma unroll
    for (int jj = 0; jj < 16 - W; jj++)
#pragma unroll
      for (int u = 0; u < 8; u++) {
        const int sx = cv_tile<W>(u) - jj;
        if (sx >= 0) mma16816(ca[u], fa[jj], fb[(sx >> 1) & 7][2 * (sx & 1)], fb[(sx >> 1) & 7][2 * (sx & 1) + 1]);
      }
  }
}

__device__ __forceinline__ void consumer_main(const Params& p, uint32_t sb) {
  const int lane = fresh_tid() & 31, w = (fresh_warp() >> 2) - 1;
  const uint32_t lb = lane_base16();
  int qt, rank;
  { const Role ro = get_role(); qt = q_tile(ro.h, ro.j, 0); rank = ro.j & 1; }
  const uint32_t st_full = bar_addr(sb, B_ST_FULL + w), st_empty = bar_addr(sb, B_ST_EMPTY + w);
  const uint32_t stg = sb + P1_STG + w * 16384;

  auto turn_begin = [&]() { named_sync(PP_BAR + w, 256); };
  auto turn_end = [&]() { named_arrive(PP_BAR + (w ^ 1), 256); };
  if (w == 0) named_arrive(PP_BAR + 1, 256);
  float acc[128];
#pragma unroll
  for (int i = 0; i < 128; i++) acc[i] = 0.f;
  uint32_t pk[64];
#pragma unroll
  for (int i = 0; i < 64; i++) pk[i] = 0;
  PDECL;
  TR_DECL;
  TR(0);
  TSG(0); TS(1);
  const uint32_t qreg = q_region(sb, w);
  for (int t = 0; t < 5; t++) {
    const int nk = t < 4 ? 16 : 7;
#pragma unroll 1
    for (int k = 0; k < nk; k++) {
      const int it = t * 16 + k, s = k & 3;
      mbar_wait(bar_addr(sb, B_P1_FULL + s), (it >> 2) & 1);
      TR(1);
      const uint64_t da = desc_k(sb + s * P1_STAGE + w * 8192), db = desc_mn(sb + s * P1_STAGE + 16384);
      turn_begin();
      wg_fence();
#pragma unroll
      for (int kk = 0; kk < 4; kk++) wgmma_ss_n256_tb(acc, desc_add(da, kk * 32), desc_add(db, kk * 2048), (k | kk) != 0);
      wg_commit();
      turn_end();
      TR(3);
      wg_wait<1>();
      if (k > 0) release(bar_addr(sb, B_P1_EMPTY + ((k - 1) & 3)), lane, rank, true);
      const int k1 = t < 4 ? STG_K1 : STG_Q1, k2 = t < 4 ? STG_K2 : STG_Q2;
      if (t > 0 && (k == k1 || k == k2)) {
        const int job = 2 * (t - 1) + (k != k1);
        if (job > 0) mbar_wait(st_empty, (job - 1) & 1);
        if (k == k1) store_blocks<0, 2>(stg, lb, pk); else store_blocks<32, 2>(stg, lb, pk);
        warp_arrive(st_full, lane);
      }
      TR(5);
    }
    wg_wait<0>();
    TR(6);
    reg_fence(acc);
    release(bar_addr(sb, B_P1_EMPTY + ((nk - 1) & 3)), lane, rank, true);
#pragma unroll
    for (int i = 0; i < 64; i++) pk[i] = pack_bf16(acc[2 * i], acc[2 * i + 1]);
    TS(t < 4 ? 2 + t : 60);
  }
  TS(6);
  {
    const uint32_t ft = fresh_tid(), wq = (ft >> 5) & 3, ln = ft & 31, g = ln >> 2, c = ln & 3;
    const uint32_t cx = sb + CV_X, hE = cx + CV_HE, hO = hE + CV_HCOPY;
    float ca[8][4];
#pragma unroll
    for (int i = 0; i < 8; i++) { ca[i][0] = 0.f; ca[i][1] = 0.f; ca[i][2] = 0.f; ca[i][3] = 0.f; }
    const uint32_t abase = ((g & 1) == 0 ? hE + (7 - g + 2 * c + 1) * 2 : hO + (7 - g + 2 * c) * 2) + wq * 64;
    const uint32_t baddr = cx + ((ln >> 3) & 1) * CV_PLANE + (16 + (ln >> 4) * 8 + (ln & 7)) * 16 - wq * 32;
    mbar_wait(bar_addr(sb, B_RG_FULL + 4), 0);
    TR(7); TS(19); TS(20);
    if (w) conv_mma<1>(ca, abase, baddr); else conv_mma<0>(ca, abase, baddr);
    TR(8); TS(21);
    mbar_wait(bar_addr(sb, B_P1_EMPTY + 2), 1);
    const uint32_t ex = sb + CV_R + w * 16384 + ln * 16;
#pragma unroll
    for (int u = 0; u < 8; u++)
      sts16(ex + (wq * 8 + u) * 512, __float_as_uint(ca[u][0]), __float_as_uint(ca[u][1]), __float_as_uint(ca[u][2]), __float_as_uint(ca[u][3]));
    if (w == 0) { mbar_wait(st_empty, 1); mbar_wait(bar_addr(sb, B_ST_EMPTY + 1), 1); }
    store_blocks<0, 4>(qreg, lb, pk);
    named_sync(1 + w, 128);
    TR(9); TS(22);
    const uint32_t Dd = lds4(cx + CV_D);
    uint32_t z[2][2];
#pragma unroll
    for (int e = 0; e < 2; e++) {
      const uint32_t u = 2 * wq + e, nt = 2 * u + ((e ^ w) & 1);
      float y[4] = {0.f, 0.f, 0.f, 0.f};
#pragma unroll
      for (int v = 0; v < 4; v++) {
        const uint4 t = lds16(ex + (v * 8 + u) * 512);
        y[0] += __uint_as_float(t.x); y[1] += __uint_as_float(t.y); y[2] += __uint_as_float(t.z); y[3] += __uint_as_float(t.w);
      }
      const uint32_t lo = transpose8(pack_bf16(y[0], y[1])), hi = transpose8(pack_bf16(y[2], y[3]));
      const uint32_t ro = (16 + 8 * nt) * 16 + ln * 4;
      z[e][1] = badd(lo, bmul(lds4(cx + CV_PLANE + ro), Dd));
      z[e][0] = badd(hi, bmul(lds4(cx + ro), Dd));
    }
    TS(23);
    fence_async_smem();
    __syncwarp();
    release(bar_addr(sb, B_RG_EMPTY + 3), lane, rank, true);
    release(bar_addr(sb, B_RG_EMPTY + 4), lane, rank, true);
    const Role ro = get_role();
#pragma unroll
    for (int e = 0; e < 2; e++) {
      uint8_t* gz = g_xs + (size_t)(ro.h * 8 + ro.j) * CV_BYTES + (16 + 8 * (4 * wq + 2 * e + ((e ^ w) & 1))) * 16 + ln * 4;
      *reinterpret_cast<uint32_t*>(gz) = z[e][0];
      *reinterpret_cast<uint32_t*>(gz + CV_PLANE) = z[e][1];
    }
    warp_arrive(bar_addr(sb, B_CONV), lane);
#pragma unroll
    for (int i = 0; i < 128; i++) acc[i] = 0.f;
  }
  TS(15);
  TR(10);
  Ring r{0, 1};
  auto take = [&]() { const uint32_t sl = r.slot; mbar_wait(bar_addr(sb, B_RG_FULL + sl), r.phase); r.next(); return sl; };
  constexpr float SC = 0.0625f * 1.4426950408889634f;
#pragma unroll 1
  for (int which = 0; which < 2; which++) {
    if (which == 1) {
      uint32_t xaddr = 0, xs = 0, pw = 0, px = 0;
#pragma unroll 1
      for (int kc = 0; kc < 7; kc++) {
        const uint32_t ws = take();
        if (kc == 0 || (kc & 1)) { xs = take(); xaddr = sb + xs * SLOT + (w ^ 1) * 8192; } else xaddr += 16384;
        TR(11);
        const uint64_t da = desc_k(xaddr), db = desc_mn(sb + ws * SLOT);
        turn_begin();
        wg_fence();
#pragma unroll
        for (int kk = 0; kk < 4; kk++) wgmma_ss_n256_tb(acc, desc_add(da, kk * 32), desc_add(db, kk * 2048), (kc | kk) != 0);
        wg_commit();
        turn_end();
        TR(13);
        wg_wait<1>();
        if (kc > 0) {
          release(bar_addr(sb, B_RG_EMPTY + pw), lane, rank, false);
          if (kc & 1) release(bar_addr(sb, B_RG_EMPTY + px), lane, rank, false);
        }
        pw = ws; px = xs;
        const int cb = kc - CTX_K;
        if (cb >= 1 && cb <= 4) { fence_async_smem(); warp_arrive(bar_addr(sb, B_CTXS + 4 * w + cb - 1), lane); }
        if (cb == 0) store_blocks<0, 1>(qreg, lb, pk);
        else if (cb == 1) store_blocks<16, 1>(qreg + 8192, lb, pk);
        else if (cb == 2) store_blocks<32, 1>(qreg + 16384, lb, pk);
        else if (cb == 3) store_blocks<48, 1>(qreg + 24576, lb, pk);
        TR(15);
      }
      mbar_wait(st_empty, 0);
      wg_wait<0>();
      reg_fence(acc);
      TS(61); TR(16);
      release(bar_addr(sb, B_RG_EMPTY + pw), lane, rank, false);
      release(bar_addr(sb, B_RG_EMPTY + px), lane, rank, false);
#pragma unroll
      for (int i = 0; i < 64; i++) pk[i] = pack_bf16(acc[2 * i], acc[2 * i + 1]);
      store_blocks<0, 4>(qreg, lb, pk);
      fence_async_smem();
      TS(9); TR(19);
      qt = 15 - qt;
    }
    float s[32];
#pragma unroll
    for (int i = 0; i < 32; i++) s[i] = 0.f;
    uint32_t pa[16];
    float m0 = -INFINITY, m1 = -INFINITY, l0 = 0.f, l1 = 0.f;
    const uint64_t dq = desc_k(qreg);
    uint64_t dk = 0, dqq = 0, dv = 0;
    auto prep_qk = [&](uint32_t kaddr) { dk = desc_k(kaddr); dqq = dq + (kaddr >> 31); asm volatile("" : "+l"(dk), "+l"(dqq)); };
    auto prep_pv = [&](uint32_t vaddr) { dv = desc_mn(vaddr); asm volatile("" : "+l"(dv)); };
    auto issue_qk = [&]() {
#pragma unroll
      for (int kk = 0; kk < 16; kk++)
        wgmma_ss_n64(s, desc_add(dqq, (kk >> 2) * 8192 + (kk & 3) * 32), desc_add(dk, (kk >> 2) * 8192 + (kk & 3) * 32), kk != 0);
    };
    auto issue_pv = [&](int accumulate) {
#pragma unroll
      for (int kk = 0; kk < 4; kk++)
        wgmma_rs_n256_tb(acc, pa[4 * kk], pa[4 * kk + 1], pa[4 * kk + 2], pa[4 * kk + 3], desc_add(dv, kk * 2048), accumulate | kk);
    };
    auto mask_diag = [&]() {
      const int d = (int)((lb >> 11) << 4) + (lane >> 2) - 2 * (lane & 3);
#pragma unroll
      for (int jj = 0; jj < 8; jj++) {
        if (8 * jj > d)     s[4 * jj]     = -INFINITY;
        if (8 * jj + 1 > d) s[4 * jj + 1] = -INFINITY;
        if (8 * jj - 8 > d) s[4 * jj + 2] = -INFINITY;
        if (8 * jj - 7 > d) s[4 * jj + 3] = -INFINITY;
      }
    };
    float a0, a1;
    auto softmax = [&]() -> bool {
      float x0 = fmaxf(s[0], s[1]), x1 = fmaxf(s[2], s[3]);
#pragma unroll
      for (int jj = 1; jj < 8; jj++) {
        x0 = fmaxf(x0, fmaxf(s[4 * jj], s[4 * jj + 1]));
        x1 = fmaxf(x1, fmaxf(s[4 * jj + 2], s[4 * jj + 3]));
      }
      x0 = fmaxf(x0, __shfl_xor_sync(0xffffffffu, x0, 1));
      x1 = fmaxf(x1, __shfl_xor_sync(0xffffffffu, x1, 1));
      x0 = fmaxf(x0, __shfl_xor_sync(0xffffffffu, x0, 2));
      x1 = fmaxf(x1, __shfl_xor_sync(0xffffffffu, x1, 2));
      const bool grow = __any_sync(0xffffffffu, fmaxf(x0 - m0, x1 - m1) * SC > 8.f);
      if (grow) {
        x0 = fmaxf(x0, m0); x1 = fmaxf(x1, m1);
        a0 = ex2((m0 - x0) * SC); a1 = ex2((m1 - x1) * SC);
        m0 = x0; m1 = x1;
        l0 *= a0; l1 *= a1;
      }
      const float b0 = -m0 * SC, b1 = -m1 * SC;
      float t0 = 0.f, t1 = 0.f, t2 = 0.f, t3 = 0.f;
#pragma unroll
      for (int jj = 0; jj < 8; jj++) {
        s[4 * jj]     = ex2(fmaf(s[4 * jj], SC, b0));
        s[4 * jj + 1] = ex2(fmaf(s[4 * jj + 1], SC, b0));
        s[4 * jj + 2] = ex2(fmaf(s[4 * jj + 2], SC, b1));
        s[4 * jj + 3] = ex2(fmaf(s[4 * jj + 3], SC, b1));
        t0 += s[4 * jj]; t1 += s[4 * jj + 1]; t2 += s[4 * jj + 2]; t3 += s[4 * jj + 3];
      }
      l0 += t0 + t1; l1 += t2 + t3;
      return grow;
    };
    auto softmax_fast = [&]() -> bool {
      const float b0 = -m0 * SC, b1 = -m1 * SC;
      float t0 = 0.f, t1 = 0.f, t2 = 0.f, t3 = 0.f;
#pragma unroll
      for (int jj = 0; jj < 8; jj++) {
        s[4 * jj]     = ex2(fmaf(s[4 * jj], SC, b0));
        s[4 * jj + 1] = ex2(fmaf(s[4 * jj + 1], SC, b0));
        s[4 * jj + 2] = ex2(fmaf(s[4 * jj + 2], SC, b1));
        s[4 * jj + 3] = ex2(fmaf(s[4 * jj + 3], SC, b1));
        t0 += s[4 * jj]; t1 += s[4 * jj + 1]; t2 += s[4 * jj + 2]; t3 += s[4 * jj + 3];
      }
      t0 += t1; t2 += t3;
      uint32_t redo;
      asm volatile("{\n.reg .pred p, q;\nsetp.le.f32 p, %1, 0f47800000;\nbarrier.cta.red.or.aligned.pred q, %2, 128, !p;\nselp.u32 %0, 1, 0, q;\n}"
                   : "=r"(redo) : "f"(fmaxf(t0, t2) + (t0 - t0) + (t2 - t2)), "r"(RED_BAR + w) : "memory");
      if (!redo) { l0 += t0; l1 += t2; }
      return redo;
    };
    auto rescale = [&]() {
#pragma unroll
      for (int i = 0; i < 32; i++) { acc[4 * i] *= a0; acc[4 * i + 1] *= a0; acc[4 * i + 2] *= a1; acc[4 * i + 3] *= a1; }
    };
    auto to_p = [&]() {
#pragma unroll
      for (int i = 0; i < 16; i++) pa[i] = pack_bf16(s[2 * i], s[2 * i + 1]);
    };

    const bool up = w == which;
    const int n = 2 * qt + 2, nw = n - up, npriv = num_private(qt);
    int fd = which ? 0 : 2 * n - 1;
    const int dir = which ? 1 : -1;
    auto skip = [&]() { r.next(); fd += dir; };
    auto give = [&](uint32_t sl, int d) {
      if (lane < 2) mbar_arrive_remote_n(bar_addr(sb, B_RG_EMPTY + sl), d < npriv ? rank : rank ^ lane, (d & ~2) == 0 ? 2 : 1);
    };
    if (which && up) skip();
    uint32_t ks = take();
    TS(62 + which);
    TR(20);
    prep_qk(sb + ks * SLOT);
    turn_begin();
    wg_fence();
    issue_qk();
    wg_commit();
    turn_end();
    TR(21);
    wg_wait<0>();
    TR(22);
    reg_fence(s);
    give(ks, fd);
    fd += dir;
    if (which && up) skip();
    if (which && nw == 1 && lane == 0) mbar_arrive(bar_addr(sb, B_QFREE + w));
    if (which || nw == 1) mask_diag();
    softmax();
    to_p();
#pragma unroll 1
    for (int jj = 1; jj < nw; jj++) {
      ks = take();
      const uint32_t vs = take();
      TR(30);
      prep_qk(sb + ks * SLOT);
      prep_pv(sb + vs * SLOT);
      turn_begin();
      wg_fence();
      issue_qk();
      wg_commit();
      issue_pv(jj > 1);
      wg_commit();
      turn_end();
      TR(31);
      wg_wait<1>();
      TR(32);
      reg_fence(s);
      const bool diag = !which && jj == nw - 1;
      if (diag) mask_diag();
      bool grow = false;
      if (softmax_fast()) {
#pragma unroll 1
        for (int kb = 0; kb < 4; kb++) {
          const uint64_t da = desc_k(qreg + kb * 8192), db = desc_k(sb + ks * SLOT + kb * 8192);
          wg_fence();
#pragma unroll
          for (int kk = 0; kk < 4; kk++) wgmma_ss_n64(s, desc_add(da, kk * 32), desc_add(db, kk * 32), (kb | kk) != 0);
          wg_commit();
          wg_wait<0>();
          reg_fence(s);
        }
        if (diag) mask_diag();
        grow = softmax();
      }
      give(ks, fd);
      if (which && jj == nw - 1 && lane == 0) mbar_arrive(bar_addr(sb, B_QFREE + w));
      wg_wait<0>();
      reg_fence(acc);
      reg_fence(pa);
      give(vs, fd + dir);
      fd += 2 * dir;
      if (grow) rescale();
      to_p();
    }
    if (!which && up) skip();
    const uint32_t vs = take();
    TR(40);
    prep_pv(sb + vs * SLOT);
    turn_begin();
    wg_fence();
    issue_pv(nw > 1);
    wg_commit();
    turn_end();
    TR(41);
    l0 += __shfl_xor_sync(0xffffffffu, l0, 1); l1 += __shfl_xor_sync(0xffffffffu, l1, 1);
    l0 += __shfl_xor_sync(0xffffffffu, l0, 2); l1 += __shfl_xor_sync(0xffffffffu, l1, 2);
    float i0 = 1.f / l0, i1 = 1.f / l1;
    asm volatile("" : "+f"(i0), "+f"(i1) :: "memory");
    wg_wait<0>();
    TR(42);
    reg_fence(acc);
    reg_fence(pa);
    give(vs, fd);
    if (!which && up) r.next();
    TS(7 + 3 * which);
#pragma unroll
    for (int i = 0; i < 32; i++) {
      pk[2 * i]     = pack_bf16(acc[4 * i] * i0, acc[4 * i + 1] * i0);
      pk[2 * i + 1] = pack_bf16(acc[4 * i + 2] * i1, acc[4 * i + 3] * i1);
    }
    TS(8 + 3 * which); TR(46);
    if (which == 0) TS(31);
  }

  {
    float oa[32], ob[32];
#pragma unroll
    for (int i = 0; i < 32; i++) { oa[i] = 0.f; ob[i] = 0.f; }
    auto stage_o = [&](float (&o)[32], int ch) {
      reg_fence(o);
      uint32_t q[16];
#pragma unroll
      for (int i = 0; i < 16; i++) q[i] = pack_bf16(o[2 * i], o[2 * i + 1]);
      if (ch >= 2) mbar_wait(bar_addr(sb, B_S2_EMPTY + w * 2 + (ch & 1)), ((ch >> 1) - 1) & 1);
      store_blocks<0, 1>(qreg + (ch & 1) * 8192, lb, q);
    };
    auto hand_over = [&](int ch) {
      fence_async_smem();
      warp_arrive(bar_addr(sb, B_S2_FULL + w * 2 + (ch & 1)), lane);
    };
    uint32_t pk2[64];
#pragma unroll
    for (int i = 0; i < 64; i++) pk2[i] = 0;
    uint32_t p2 = 0;
    auto chunk = [&](int ch, float (&o)[32], float (&oprev)[32]) {
      const uint32_t s1 = take();
      TR(50);
      const uint64_t d1 = desc_mn(sb + s1 * SLOT);
      turn_begin();
      wg_fence();
#pragma unroll
      for (int kk = 0; kk < 16; kk++) {
        wgmma_rs_n64_tb(o, pk[4 * kk], pk[4 * kk + 1], pk[4 * kk + 2], pk[4 * kk + 3], desc_add(d1, kk * 2048), kk != 0);
        if (kk == ARRIVE_KK) turn_end();
      }
      wg_commit();
      TR(51);
      if (ch >= 1) {
        wg_wait<1>();
        if (ch <= 4) release(bar_addr(sb, B_RG_EMPTY + p2), lane, rank, true);
        stage_o(oprev, ch - 1);
      } else {
        mbar_wait(bar_addr(sb, B_CTXF + w), 0);
#pragma unroll
        for (int kk = 0; kk < 16; kk++) {
          uint32_t f[4];
          ldsm4(f, qreg + (kk >> 2) * 8192 + (lb ^ ((kk & 3) << 5)));
          pk2[4 * kk] = f[0]; pk2[4 * kk + 1] = f[1]; pk2[4 * kk + 2] = f[2]; pk2[4 * kk + 3] = f[3];
        }
      }
      const uint32_t s2 = take();
      TR(53);
      const uint64_t d2 = desc_mn(sb + s2 * SLOT);
      turn_begin();
      wg_fence();
#pragma unroll
      for (int kk = 0; kk < 16; kk++) {
        wgmma_rs_n64_tb(o, pk2[4 * kk], pk2[4 * kk + 1], pk2[4 * kk + 2], pk2[4 * kk + 3], desc_add(d2, kk * 2048), 1);
        if (kk == ARRIVE_KK && (ch < 6 || w == 1)) turn_end();
      }
      wg_commit();
      TR(54);
      if (ch >= 1) hand_over(ch - 1);
      wg_wait<1>();
      TR(55);
      if (ch <= 4) release(bar_addr(sb, B_RG_EMPTY + s1), lane, rank, true);
      p2 = s2;
    };
#pragma unroll 1
    for (int ch = 0; ch < 6; ch += 2) { chunk(ch, oa, ob); chunk(ch + 1, ob, oa); }
    chunk(6, oa, ob);
    wg_wait<0>();
    TR(58);
    reg_fence(pk);
    reg_fence(pk2);
    stage_o(oa, 6);
    hand_over(6);
  }
  TS(12); TR(59);
  if ((threadIdx.x & 127) == 0) GT(54 + w);

  TS(16); TS(18); TS(17);
  TR(99); TR_END();
  TS(13); TSG(14);
}

#define CONV_STAGGER_NS 1200
namespace ssm {
constexpr int GROUPS = D_SPARE / 8 / NCONV;
constexpr uint32_t ZROWS = 16;
constexpr uint32_t PLANE = 2368;
constexpr uint32_t CHAN = 2 * PLANE + 16;
constexpr uint32_t XBUF = 8 * CHAN;
constexpr uint32_t OFF_X = 0;
constexpr uint32_t HCOPY = 4160;
constexpr uint32_t OFF_H = 2 * XBUF;
constexpr uint32_t HWARP = 3 * HCOPY;
constexpr uint32_t KBUF = 128 + 4096;
constexpr int NKV = 3;
constexpr uint32_t OFF_K = (OFF_H + 8 * HWARP + 127) / 128 * 128, OFF_V = OFF_K + NKV * KBUF, OFF_Q = OFF_V + NKV * 4096;
constexpr uint32_t END = OFF_Q + 3 * 4096;
static_assert(OFF_K % 128 == 0 && OFF_H % 16 == 0, "TMA destination alignment");
static_assert(END <= BARS, "smem");
enum : uint32_t { B_XREADY = 0, B_ZDONE = 2, B_KV = 4, B_Q = 8, B_HRAW = 12 };
constexpr int IO_BAR = 3, CW_BAR = 4;

__device__ __forceinline__ uint32_t row_addr(uint32_t xb, int beta) { return xb + ((beta & 1) ? 0 : PLANE) + (uint32_t)((beta >> 1) + ZROWS) * 16; }

__device__ __forceinline__ void io_warpgroup(const Params& p, uint32_t sb, int cidx) {
  const int tid = threadIdx.x & 127, lane = threadIdx.x & 31, wq = tid >> 5;
  constexpr int NCH = GROUPS * 8, NCQ = (GROUPS - 1) * 8;
  auto load_kv = [&](int sidx) {
    const int d0 = (cidx * GROUPS + (sidx >> 3)) * 8, row = (sidx & 7) * 256, b = sidx % NKV;
    const uint32_t bar = bar_addr(sb, B_KV + b);
    mbar_expect_tx(bar, KBUF + 4096);
    tma_ld2(sb + OFF_K + b * KBUF, &p.ak8, bar, d0, row - 8);
    tma_ld2(sb + OFF_K + b * KBUF + 128, &p.ak, bar, d0, row);
    tma_ld2(sb + OFF_V + b * 4096, &p.av, bar, d0, row);
  };
  auto load_q = [&](int e) {
    const uint32_t bar = bar_addr(sb, B_Q + e % 3);
    mbar_expect_tx(bar, 4096);
    tma_ld2(sb + OFF_Q + (e % 3) * 4096, &p.aq, bar, (cidx * GROUPS + (e >> 3)) * 8, (e & 7) * 256);
  };
  if (tid == 0) { for (int i = 0; i < NKV; i++) load_kv(i); load_q(0); load_q(1); }
  const uint32_t rowoff = (uint32_t)(8 * (8 * wq + (lane >> 3)) + 7 - (lane & 7)) * 16;
  const uint32_t xlane = (lane >> 2) * CHAN + (lane & 3) * 4;
  uint32_t sh[4];
  auto load_taps = [&](int grp) {
    const int d0 = (cidx * GROUPS + grp) * 8;
    const uint2 s0 = __ldg(reinterpret_cast<const uint2*>(p.a_shift + (d0 + 2 * (lane & 3)) * 4));
    const uint2 s1 = __ldg(reinterpret_cast<const uint2*>(p.a_shift + (d0 + 2 * (lane & 3) + 1) * 4));
    sh[0] = __byte_perm(s0.x, s1.x, 0x5410); sh[1] = __byte_perm(s0.x, s1.x, 0x7632);
    sh[2] = __byte_perm(s0.y, s1.y, 0x5410); sh[3] = __byte_perm(s0.y, s1.y, 0x7632);
  };
  auto pro_chunk = [&](int grp, int c) {
    const uint32_t xb = sb + OFF_X + (grp & 1) * XBUF + xlane;
    const int sidx = grp * 8 + c, b = sidx % NKV;
    mbar_wait(bar_addr(sb, B_KV + b), (sidx / NKV) & 1);
#pragma unroll
    for (int u = 0; u < 2; u++) {
      const uint32_t ka = sb + OFF_K + b * KBUF + 128 + rowoff + u * 512, va = sb + OFF_V + b * 4096 + rowoff + u * 512;
      uint32_t k0[4], k1[4], k2[4], k3[4], vv[4];
      ldsm4(k0, ka - 48); ldsm4(k1, ka - 32); ldsm4(k2, ka - 16); ldsm4(k3, ka); ldsm4(vv, va);
#pragma unroll
      for (int m = 0; m < 4; m++) {
        uint32_t ks = bmul(k0[m], sh[3]);
        ks = badd(ks, bmul(k1[m], sh[2]));
        ks = badd(ks, bmul(k2[m], sh[1]));
        ks = badd(ks, bmul(k3[m], sh[0]));
        const uint32_t x = transpose8(bmul(ks, vv[m]));
        const int beta = 32 * c + 8 * wq + 4 * u + m;
        asm volatile("st.shared.u32 [%0], %1;" :: "r"(row_addr(xb, beta)), "r"(x) : "memory");
      }
    }
  };
  auto epi_chunk = [&](int grp, int c) {
    const uint32_t xb = sb + OFF_X + (grp & 1) * XBUF + xlane;
    const int e = grp * 8 + c;
    const uint32_t qb = sb + OFF_Q + (e % 3) * 4096;
    mbar_wait(bar_addr(sb, B_Q + e % 3), (e / 3) & 1);
#pragma unroll
    for (int u = 0; u < 2; u++) {
      uint32_t qq[4], o[4];
      ldsm4(qq, qb + rowoff + u * 512);
#pragma unroll
      for (int m = 0; m < 4; m++) {
        const int beta = 32 * c + 8 * wq + 4 * u + m;
        o[m] = bmul(qq[m], transpose8(lds4(row_addr(xb, beta))));
      }
      stsm4(qb + rowoff + u * 512, o[0], o[1], o[2], o[3]);
    }
    fence_async_smem();
  };
#pragma unroll 1
  for (int grp = 0; grp < 2; grp++) {
    load_taps(grp);
#pragma unroll 1
    for (int c = 0; c < 8; c++) {
      pro_chunk(grp, c);
      named_sync(IO_BAR, 128);
      if (tid == 0 && grp * 8 + c + NKV < NCH) load_kv(grp * 8 + c + NKV);
    }
    warp_arrive(bar_addr(sb, B_XREADY + (grp & 1)), lane);
  }
#pragma unroll 1
  for (int grp = 0; grp + 1 < GROUPS; grp++) {
    const bool more = grp + 2 < GROUPS;
    if (more) load_taps(grp + 2);
    PCLK(c0);
    mbar_wait(bar_addr(sb, B_ZDONE + (grp & 1)), (grp >> 1) & 1);
    PACC(tp, c0);
    PCLK(c1);
#pragma unroll 1
    for (int c = 0; c < 8; c++) {
      epi_chunk(grp, c);
      if (more) pro_chunk(grp + 2, c);
      named_sync(IO_BAR, 128);
      if (tid == 0) {
        const int e = grp * 8 + c;
        tma_st2(&p.ao, sb + OFF_Q + (e % 3) * 4096, (cidx * GROUPS + grp) * 8, c * 256);
        bulk_commit();
        if (more && (grp + 2) * 8 + c + NKV < NCH) load_kv((grp + 2) * 8 + c + NKV);
        if (e + 2 < NCQ) {
          asm volatile("cp.async.bulk.wait_group.read 1;" ::: "memory");
          load_q(e + 2);
        }
      }
    }
    if (more) warp_arrive(bar_addr(sb, B_XREADY + (grp & 1)), lane);
    PACC(te, c1);
  }
  if (tid == 0) bulk_wait_all();
}

__device__ __forceinline__ void conv_warp(const Params& p, uint32_t sb, int cidx, int ch) {
  const int lane = threadIdx.x & 31, g = lane >> 2, c = lane & 3;
  const uint32_t hE0 = sb + OFF_H + ch * HWARP, hO = hE0 + HCOPY;
  const uint32_t hbar = bar_addr(sb, B_HRAW + ch);
  const int dbase = cidx * GROUPS * 8 + ch;
  auto fetch_h = [&](int grp) {
    if (lane == 0) {
      mbar_expect_tx(hbar, 4096);
      asm volatile("cp.async.bulk.shared::cluster.global.mbarrier::complete_tx::bytes [%0], [%1], %2, [%3];"
                   :: "r"(hE0 + (grp & 1) * 2 * HCOPY + 32), "l"(p.a_ssmk + (size_t)(dbase + 8 * grp) * SEQ), "r"(4096), "r"(hbar) : "memory");
    }
  };
  fetch_h(0);
  const uint32_t xlane = (uint32_t)g * CHAN + c * 4;
#pragma unroll 1
  for (int grp = 0; grp < GROUPS; grp++) {
    const uint32_t xc = sb + OFF_X + (grp & 1) * XBUF + ch * CHAN;
    const uint32_t Dd = (uint32_t)__ldg(reinterpret_cast<const unsigned short*>(p.a_D + dbase + 8 * grp)) * 0x10001u;
    PCLK(k0);
    mbar_wait(hbar, grp & 1);
    const uint32_t hE = hE0 + (grp & 1) * 2 * HCOPY;
    if (grp + 1 < GROUPS) fetch_h(grp + 1);
#pragma unroll
    for (int i = 0; i < 8; i++) {
      const uint32_t o = 32 + (i * 32 + lane) * 16;
      const uint4 w = lds16(hE + o);
      const uint32_t nx = lds4(hE + o + 16);
      sts16(hO + o, __byte_perm(w.x, w.y, 0x5432), __byte_perm(w.y, w.z, 0x5432), __byte_perm(w.z, w.w, 0x5432), __byte_perm(w.w, nx, 0x5432));
      if (o == 32) asm volatile("st.shared.u32 [%0], %1;" :: "r"(hO + 28), "r"(w.x << 16) : "memory");
    }
    __syncwarp();
    const uint32_t abase = (g & 1) == 0 ? hE + (7 - g + 2 * c + 1) * 2 : hO + (7 - g + 2 * c) * 2;
    mbar_wait(bar_addr(sb, B_XREADY + (grp & 1)), (grp >> 1) & 1);
    if (grp == 0 && ch >= 4) __nanosleep(CONV_STAGGER_NS);
    PACC(tw, k0);
    PCLK(k1);
    float acc[16][4];
#pragma unroll
    for (int i = 0; i < 16; i++) { acc[i][0] = 0.f; acc[i][1] = 0.f; acc[i][2] = 0.f; acc[i][3] = 0.f; }
    const uint32_t baddr = xc + ((lane >> 3) & 1) * PLANE + (ZROWS + (lane >> 4) * 8 + (lane & 7)) * 16;
#pragma unroll 1
    for (int r = 0; r < 8; r++) {
      uint32_t fa[16][4], fb[8][4];
#pragma unroll
      for (int i = 0; i < 8; i++) ldsm4(fb[i], baddr + i * 256 - r * 16);
#pragma unroll
      for (int jj = 0; jj < 16; jj++) {
        const uint32_t ad = abase + jj * 256 + r * 32;
        fa[jj][0] = lds4(ad); fa[jj][1] = lds4(ad + 16); fa[jj][2] = lds4v(ad + 16); fa[jj][3] = lds4(ad + 32);
      }
#pragma unroll
      for (int jj = 0; jj < 16; jj++)
#pragma unroll
        for (int sx = 0; sx < 16 - jj; sx++)
          mma16816(acc[jj + sx], fa[jj], fb[sx >> 1][2 * (sx & 1)], fb[sx >> 1][2 * (sx & 1) + 1]);
    }
    PACC(tm, k1);
    PCLK(k2);
#pragma unroll
    for (int nt = 0; nt < 16; nt++) {
      const uint32_t lo = transpose8(pack_bf16(acc[nt][0], acc[nt][1]));
      const uint32_t hi = transpose8(pack_bf16(acc[nt][2], acc[nt][3]));
      const uint32_t ad = xc + (ZROWS + 8 * nt) * 16 + lane * 4;
      const uint32_t x1 = lds4(ad + PLANE), x0 = lds4(ad);
      asm volatile("st.shared.u32 [%0], %1;" :: "r"(ad + PLANE), "r"(badd(lo, bmul(x1, Dd))) : "memory");
      asm volatile("st.shared.u32 [%0], %1;" :: "r"(ad), "r"(badd(hi, bmul(x0, Dd))) : "memory");
    }
    if (grp + 1 < GROUPS) warp_arrive(bar_addr(sb, B_ZDONE + (grp & 1)), lane);
    PACC(tr, k2);
  }
  {
    const int d0 = (cidx * GROUPS + GROUPS - 1) * 8;
    const uint32_t* qp = reinterpret_cast<const uint32_t*>(p.a_q + (size_t)(256 * ch + 7 - g) * DA + d0) + c;
    uint32_t qv[32];
#pragma unroll
    for (int i = 0; i < 32; i++) qv[i] = __ldg(qp + i * 8 * (DA / 2));
    named_sync(CW_BAR, 256);
    const uint32_t xb = sb + OFF_X + ((GROUPS - 1) & 1) * XBUF + xlane;
    uint32_t* op = reinterpret_cast<uint32_t*>(p.out + (size_t)(256 * ch + 7 - g) * OUTW + d0) + c;
#pragma unroll
    for (int i = 0; i < 32; i++) op[i * 8 * (OUTW / 2)] = bmul(qv[i], transpose8(lds4(row_addr(xb, 32 * ch + i))));
  }
}

__device__ __forceinline__ void init(uint32_t sb) {
  for (uint32_t i = threadIdx.x; i < END / 16; i += NTHREADS) sts16(sb + i * 16, 0, 0, 0, 0);
  if (threadIdx.x == 0) {
    for (int i = 0; i < 2; i++) { mbar_init(bar_addr(sb, B_XREADY + i), 4); mbar_init(bar_addr(sb, B_ZDONE + i), 8); }
    for (int i = 0; i < NKV; i++) mbar_init(bar_addr(sb, B_KV + i), 1);
    for (int i = 0; i < 3; i++) mbar_init(bar_addr(sb, B_Q + i), 1);
    for (int i = 0; i < 8; i++) mbar_init(bar_addr(sb, B_HRAW + i), 1);
  }
  fence_async_smem();
}
}

__device__ __forceinline__ void ssm_side_work(const Params& p, uint32_t sb, unsigned epoch) {
  const Role ro = get_role();
  const int h = ro.h, j = ro.j;
  const int lane = threadIdx.x & 31, g = lane >> 2, c = lane & 3;
  const int d0 = D_SPARE + 8 * h;
  uint8_t* xs = g_xs + (size_t)(h * 8 + g) * CV_BYTES + c * 4;
  auto xrow = [&](int beta) { return xs + ((beta & 1) ? 0 : CV_PLANE) + (16 + (beta >> 1)) * 16; };
  {
    const uint4* hp = reinterpret_cast<const uint4*>(p.a_ssmk + (size_t)(d0 + j) * SEQ) + lane;
    uint8_t* he = g_xs + (size_t)(h * 8 + j) * CV_BYTES + CV_HE;
#pragma unroll 2
    for (int i = 0; i < 8; i++) {
      const uint4 wv = __ldg(hp + i * 32);
      const uint32_t nx = i * 32 + lane < 255 ? __ldg(reinterpret_cast<const uint32_t*>(hp + i * 32 + 1)) : 0u;
      const uint32_t o = 32 + (i * 32 + lane) * 16;
      *reinterpret_cast<uint4*>(he + o) = wv;
      *reinterpret_cast<uint4*>(he + CV_HCOPY + o) =
          make_uint4(__byte_perm(wv.x, wv.y, 0x5432), __byte_perm(wv.y, wv.z, 0x5432), __byte_perm(wv.z, wv.w, 0x5432), __byte_perm(wv.w, nx, 0x5432));
      if (o == 32) *reinterpret_cast<uint32_t*>(he + CV_HCOPY + 28) = wv.x << 16;
    }
    if (lane == 0) *reinterpret_cast<uint32_t*>(he + CV_D - CV_HE) = (uint32_t)__ldg(reinterpret_cast<const unsigned short*>(p.a_D + d0 + j)) * 0x10001u;
  }
  {
    const uint2 s0 = __ldg(reinterpret_cast<const uint2*>(p.a_shift + (d0 + 2 * c) * 4)), s1 = __ldg(reinterpret_cast<const uint2*>(p.a_shift + (d0 + 2 * c + 1) * 4));
    const uint32_t sh0 = __byte_perm(s0.x, s1.x, 0x5410), sh1 = __byte_perm(s0.x, s1.x, 0x7632);
    const uint32_t sh2 = __byte_perm(s0.y, s1.y, 0x5410), sh3 = __byte_perm(s0.y, s1.y, 0x7632);
    const uint32_t* kp = reinterpret_cast<const uint32_t*>(p.a_k + (size_t)(256 * j + 7 - g) * DA + d0) + c;
    const uint32_t* vp = reinterpret_cast<const uint32_t*>(p.a_v + (size_t)(256 * j + 7 - g) * DA + d0) + c;
    uint32_t kprev = j > 0 ? __ldg(kp - 8 * (DA / 2)) : 0u;
#pragma unroll 1
    for (int i0 = 0; i0 < 32; i0 += 8) {
      uint32_t kk[8], vv[8];
#pragma unroll
      for (int i = 0; i < 8; i++) { kk[i] = __ldg(kp + (i0 + i) * 8 * (DA / 2)); vv[i] = __ldg(vp + (i0 + i) * 8 * (DA / 2)); }
#pragma unroll
      for (int i = 0; i < 8; i++) {
        const uint32_t k2 = __shfl_sync(0xffffffffu, g < 1 ? kprev : kk[i], (lane + 4) & 31);
        const uint32_t k1 = __shfl_sync(0xffffffffu, g < 2 ? kprev : kk[i], (lane + 8) & 31);
        const uint32_t k0 = __shfl_sync(0xffffffffu, g < 3 ? kprev : kk[i], (lane + 12) & 31);
        uint32_t ks = bmul(k0, sh3);
        ks = badd(ks, bmul(k1, sh2)); ks = badd(ks, bmul(k2, sh1)); ks = badd(ks, bmul(kk[i], sh0));
        *reinterpret_cast<uint32_t*>(xrow(32 * j + i0 + i)) = transpose8(bmul(ks, vv[i]));
        kprev = kk[i];
      }
    }
    __syncwarp();
    if (lane == 0) {
      flag_signal(&g_flags.xs_ready[h].v);
      flag_wait(&g_flags.xs_ready[h].v, 8, epoch);
      fence_async_all();
      mbar_arrive(bar_addr(sb, B_XS));
    }
  }
  if (lane == 0) {
    for (int i = 0; i < 2; i++) {
      flag_wait(&g_flags.kv_ready[2 * h + i].v, 16, epoch);
      fence_async_all();
      mbar_arrive(bar_addr(sb, B_KV + i));
      if (PF_CV && i == 0) bulk_prefetch(g_xs + (size_t)(h * 8 + j) * CV_BYTES, CV_BYTES);
    }
    mbar_wait(bar_addr(sb, B_CONV), 0);
    flag_signal(&g_flags.zs_ready[h].v);
    flag_wait(&g_flags.zs_ready[h].v, 8, epoch);
    asm volatile("red.relaxed.gpu.global.add.u64 [%0], 1;" :: "l"(&g_flags.done) : "memory");
  }
  __syncwarp();
  fence_async_all();
  const uint32_t qb = q_region(sb, 1) + 16384, zb = qb + 4096, bar = bar_addr(sb, B_GATE);
  constexpr uint32_t ZCH = 528;
  mbar_wait_slow(bar_addr(sb, B_GFREE), 0);
  if (lane == 0) { mbar_expect_tx(bar, 8192); tma_ld2(qb, &p.aq, bar, d0, 256 * j); }
  __syncwarp();
  if (lane < 16) bulk_ld(zb + (lane >> 1) * ZCH + (lane & 1) * 256, g_xs + (size_t)(h * 8 + (lane >> 1)) * CV_BYTES + (lane & 1) * CV_PLANE + (16 + 16 * j) * 16, 256, bar);
  mbar_wait(bar, 0);
  const uint32_t za = zb + (lane & 7) * ZCH + ((lane >> 3) & 1 ? 0 : 256) + (lane >> 4) * 16;
  const uint32_t qa = qb + (8 * (lane >> 3) + 7 - (lane & 7)) * 16;
#pragma unroll 2
  for (int i = 0; i < 8; i++) {
    uint32_t zz[4], qq[4];
    ldsm4t(zz, za + i * 32);
    ldsm4(qq, qa + i * 512);
    stsm4(qa + i * 512, bmul(qq[0], zz[0]), bmul(qq[1], zz[1]), bmul(qq[2], zz[2]), bmul(qq[3], zz[3]));
  }
  fence_async_smem();
  __syncwarp();
  if (lane == 0) { tma_st2(&p.ao, qb, d0, 256 * j); bulk_commit(); bulk_wait_all(); }
}

__global__ void __cluster_dims__(2, 1, 1) __launch_bounds__(NTHREADS, 1)
concat_heads__ssm_conv_h3__compressed_kv_cla__prompt_kernel(const __grid_constant__ Params p) {
  extern __shared__ uint8_t smem_raw[];
  const uint32_t sb = (smem_u32(smem_raw) + 1023) & ~1023u;
  const int warp = __shfl_sync(0xffffffffu, threadIdx.x >> 5, 0);
  const int wg = warp >> 2;
  const int cta = blockIdx.x;
  const bool attn = cta < NMAIN;
  if (!attn) ssm::init(sb);
  if (attn && threadIdx.x == 0) {
    for (int i = 0; i < 4; i++) { mbar_init(bar_addr(sb, B_P1_FULL + i), 1); mbar_init(bar_addr(sb, B_P1_EMPTY + i), 16); }
    for (int i = 0; i < NSLOT; i++) {
      mbar_init(bar_addr(sb, B_RG_FULL + i), 1); mbar_init(bar_addr(sb, B_RG_EMPTY + i), 16); mbar_init(bar_addr(sb, B_PFREE + i), 1);
    }
    for (int i = 0; i < 2; i++) { mbar_init(bar_addr(sb, B_ST_FULL + i), 4); mbar_init(bar_addr(sb, B_ST_EMPTY + i), 1); }
    mbar_init(bar_addr(sb, B_XS), 1); mbar_init(bar_addr(sb, B_CONV), 8); mbar_init(bar_addr(sb, B_GATE), 1); mbar_init(bar_addr(sb, B_GFREE), 1);
    mbar_init(bar_addr(sb, B_KV), 1); mbar_init(bar_addr(sb, B_KV + 1), 1);
    for (int i = 0; i < 8; i++) mbar_init(bar_addr(sb, B_CTXS + i), 4);
    for (int i = 0; i < 4; i++) { mbar_arrive(bar_addr(sb, B_RG_FULL + i)); if (i < 3) mbar_arrive_n(bar_addr(sb, B_RG_EMPTY + i), 16); }
    for (int i = 0; i < 4; i++) { mbar_init(bar_addr(sb, B_S2_FULL + i), 4); mbar_init(bar_addr(sb, B_S2_EMPTY + i), 1); }
    for (int i = 0; i < 2; i++) { mbar_init(bar_addr(sb, B_QFREE + i), 4); mbar_init(bar_addr(sb, B_CTXF + i), 1); }
    asm volatile("fence.mbarrier_init.release.cluster;" ::: "memory");
  }
  if (attn && threadIdx.x == 32) {
    prefetch_map(&p.ckv); prefetch_map(&p.wuk); prefetch_map(&p.wuv); prefetch_map(&p.x); prefetch_map(&p.wq);
    prefetch_map(&p.kv); prefetch_map(&p.part); prefetch_map(&p.wo); prefetch_map(&p.ctx);
  }
  __syncwarp();
  asm volatile("barrier.cluster.arrive.release.aligned;" ::: "memory");
  if (attn && threadIdx.x == 0) {
    const Role ro = get_role();
    const int h = ro.h, j = ro.j;
    for (int k = 0; k < EARLY_LD; k++) {
      const uint32_t full = bar_addr(sb, B_P1_FULL + k), dst = sb + k * P1_STAGE;
      mbar_expect_tx(full, P1_STAGE);
      tma_ld2(dst, &p.ckv, full, k * 64, 2 * j * 128);
      load_tile4(dst + 16384, &p.wuk, full, k * 64, h * 4, j & 1, false);
    }
  }
  __syncwarp();
  asm volatile("barrier.cluster.wait.acquire.aligned;" ::: "memory");

  const int lane = threadIdx.x & 31;
  if (wg == 0) {
    if (!attn) {
      asm volatile("setmaxnreg.dec.sync.aligned.u32 72;");
      if (threadIdx.x == 0) GT(0);
      if (p.out != nullptr) ssm::io_warpgroup(p, sb, cta - NMAIN);
      if (threadIdx.x == 0) GT(14);
      return;
    }
    asm volatile("setmaxnreg.dec.sync.aligned.u32 40;");
    if (warp == 0) {
      if (lane == 0) producer_main(p, sb);
    } else if (warp < 3) {
      storer_main(p, sb);
    } else {
      const unsigned epoch = load_epoch();
      mbar_wait(bar_addr(sb, B_P1_FULL + 3), 0);
      __nanosleep(SIDE_DELAY_NS);
      ssm_side_work(p, sb, epoch);
    }
  } else {
    if (!attn) {
      asm volatile("setmaxnreg.inc.sync.aligned.u32 216;");
      if (threadIdx.x == 128) { GT(12); PT(10); }
      if (p.out != nullptr) ssm::conv_warp(p, sb, cta - NMAIN, fresh_warp() - 4);
      if (threadIdx.x == 128) { PT(9); GT(13); }
      return;
    }
    asm volatile("setmaxnreg.inc.sync.aligned.u32 232;");
    if (p.out != nullptr) {
      consumer_main(p, sb);
    }
  }
}

typedef CUresult (*EncodeTiledFn)(CUtensorMap*, CUtensorMapDataType, cuuint32_t, void*, const cuuint64_t*, const cuuint64_t*,
                                  const cuuint32_t*, const cuuint32_t*, CUtensorMapInterleave, CUtensorMapSwizzle,
                                  CUtensorMapL2promotion, CUtensorMapFloatOOBfill);

void make_map(EncodeTiledFn enc, CUtensorMap* m, const void* ptr, int rank, const uint64_t* dims, const uint64_t* strides, const uint32_t* box) {
  cuuint64_t d[3], s[2]; cuuint32_t b[3], e[3] = {1, 1, 1};
  for (int i = 0; i < rank; i++) { d[i] = dims[i]; b[i] = box[i]; if (i) s[i - 1] = strides[i - 1]; }
  enc(m, CU_TENSOR_MAP_DATA_TYPE_BFLOAT16, rank, const_cast<void*>(ptr), d, s, b, e, CU_TENSOR_MAP_INTERLEAVE_NONE,
      CU_TENSOR_MAP_SWIZZLE_128B, CU_TENSOR_MAP_L2_PROMOTION_L2_256B, CU_TENSOR_MAP_FLOAT_OOB_FILL_NONE);
}
void map2(EncodeTiledFn enc, CUtensorMap* m, const void* ptr, uint64_t cols, uint64_t rows, uint32_t bc, uint32_t br) {
  const uint64_t dims[2] = {cols, rows}, st[1] = {cols * 2}; const uint32_t box[2] = {bc, br};
  make_map(enc, m, ptr, 2, dims, st, box);
}
void map2_plain(EncodeTiledFn enc, CUtensorMap* m, const void* ptr, uint64_t cols, uint64_t rows, uint32_t bc, uint32_t br) {
  cuuint64_t d[2] = {cols, rows}, st[1] = {cols * 2}; cuuint32_t b[2] = {bc, br}, e[2] = {1, 1};
  enc(m, CU_TENSOR_MAP_DATA_TYPE_BFLOAT16, 2, const_cast<void*>(ptr), d, st, b, e, CU_TENSOR_MAP_INTERLEAVE_NONE,
      CU_TENSOR_MAP_SWIZZLE_NONE, CU_TENSOR_MAP_L2_PROMOTION_L2_128B, CU_TENSOR_MAP_FLOAT_OOB_FILL_NONE);
}
void map3(EncodeTiledFn enc, CUtensorMap* m, const void* ptr, uint64_t rows, uint32_t nblk) {
  const uint64_t dims[3] = {64, rows, 64}, st[2] = {8192, 128}; const uint32_t box[3] = {64, 64, nblk};
  make_map(enc, m, ptr, 3, dims, st, box);
}

}

extern "C" void kernel_launch(void* const* d_in, const int* in_sizes, int n_in, void* d_out, int out_size) {
  (void)in_sizes; (void)n_in; (void)out_size;
  static EncodeTiledFn enc = nullptr;
  static void *kv_ptr = nullptr, *acc_ptr = nullptr;
  if (!enc) {
    void* fn = nullptr; cudaDriverEntryPointQueryResult qr;
    cudaGetDriverEntryPoint("cuTensorMapEncodeTiled", &fn, cudaEnableDefault, &qr);
    enc = (EncodeTiledFn)fn;
    cudaGetSymbolAddress(&kv_ptr, g_kv);
    cudaGetSymbolAddress(&acc_ptr, g_ctx);
    cudaFuncSetAttribute(concat_heads__ssm_conv_h3__compressed_kv_cla__prompt_kernel, cudaFuncAttributeMaxDynamicSharedMemorySize, SMEM_BYTES);
  }
  Params p;
  p.a_q = (const bf16*)d_in[0]; p.a_k = (const bf16*)d_in[1]; p.a_v = (const bf16*)d_in[2];
  map2_plain(enc, &p.aq, d_in[0], DA, SEQ, 8, 256);
  map2_plain(enc, &p.ak, d_in[1], DA, SEQ, 8, 256);
  map2_plain(enc, &p.ak8, d_in[1], DA, SEQ, 8, 8);
  map2_plain(enc, &p.av, d_in[2], DA, SEQ, 8, 256);
  map2_plain(enc, &p.ao, d_out, OUTW, SEQ, 8, 256);
  p.a_shift = (const bf16*)d_in[3]; p.a_ssmk = (const bf16*)d_in[4]; p.a_D = (const bf16*)d_in[5];
  p.out = (bf16*)d_out; p.b_x = (const bf16*)d_in[6]; p.b_wo = (const bf16*)d_in[11];
  map2(enc, &p.x, d_in[6], DM, SEQ, 64, 128);
  map2(enc, &p.ckv, d_in[7], DC, SEQ, 64, 128);
  map3(enc, &p.wq, d_in[8], DM, 2);
  map3(enc, &p.wuk, d_in[9], DC, 2);
  map3(enc, &p.wuv, d_in[10], DC, 2);
  map2(enc, &p.wo, d_in[11], DM, NH * HD, 64, 128);
  {
    const uint64_t dims[3] = {64, 2 * NH * SEQ, 4}, st[2] = {HD * 2, 128}; const uint32_t box[3] = {64, 64, 2};
    make_map(enc, &p.kv, kv_ptr, 3, dims, st, box);
  }
  map2(enc, &p.part, d_out, OUTW, SEQ, 64, 64);
  {
    const uint64_t dims[3] = {64, NMAIN * 128, 4}, st[2] = {HD * 2, 128}; const uint32_t box[3] = {64, 64, 4};
    make_map(enc, &p.ctx, acc_ptr, 3, dims, st, box);
    const uint32_t box1[3] = {64, 64, 1};
    make_map(enc, &p.ctxs, acc_ptr, 3, dims, st, box1);
  }
  concat_heads__ssm_conv_h3__compressed_kv_cla__prompt_kernel<<<NCTA, NTHREADS, SMEM_BYTES>>>(p);
}
```

```cpp
#include <cuda_runtime.h>
#include <cuda_bf16.h>
#include <cuda.h>
#include <stdint.h>

namespace {

typedef __nv_bfloat16 bf16;

constexpr int SEQ  = 2048;
constexpr int DA   = 448;
constexpr int NH   = 16;
constexpr int HD   = 256;
constexpr int DM   = 448;
constexpr int DC   = 1024;
constexpr int OUTW = DA + DM;
constexpr int NMAIN = 128;
constexpr int NCONV = 4;
constexpr int NCTA  = NMAIN + NCONV;
constexpr int NTHREADS = 384;
constexpr int D_SPARE = 320;

__device__ __align__(1024) bf16 g_kv[2ull * SEQ * NH * HD];
__device__ __align__(1024) bf16 g_ctx[(size_t)NMAIN * 128 * HD];
constexpr uint32_t CV_PLANE = 2368, CV_HE = 2 * CV_PLANE, CV_HCOPY = 4160, CV_D = CV_HE + 4144, CV_BYTES = CV_HE + 2 * CV_HCOPY;
__device__ __align__(128) uint8_t g_xs[NMAIN * CV_BYTES];
struct alignas(128) Flag { unsigned v; unsigned pad[31]; };
struct Flags {
  Flag kv_ready[2 * NH];
  Flag ctx_ready[NMAIN * 2];
  Flag out_ready[16 * 2];
  Flag xs_ready[NH];
  Flag zs_ready[NH];
  alignas(128) unsigned long long done;
};
__device__ Flags g_flags;
#define TS(i)
#define TSG(i)
#define GT(i)
#define PT(i)
#define WHICH_TS 0
#define PCLK(var)
#define PACC(acc, t0)
#define PDECL
#define PDUMP()

#define TR_DECL
#define TR(tag)
#define TR_END()

struct alignas(64) Params {
  CUtensorMap ckv;
  CUtensorMap wuk;
  CUtensorMap wuv;
  CUtensorMap x;
  CUtensorMap wq;
  CUtensorMap kv;
  CUtensorMap part;
  CUtensorMap ctx;
  CUtensorMap ctxs;
  CUtensorMap wo;
  CUtensorMap ak, ak8, av, aq, ao;
  const bf16 *a_q, *a_k, *a_v, *a_shift, *a_ssmk, *a_D, *b_x, *b_wo;
  bf16* out;
};

constexpr uint32_t P1_STAGE = 49152;
constexpr uint32_t P1_STG   = 196608;
constexpr uint32_t SLOT     = 32768;
constexpr int      NSLOT    = 5;
constexpr uint32_t QREG     = 163840;
constexpr uint32_t CV_X = 4 * SLOT + 16384, CV_R = 3 * SLOT;
static_assert(CV_BYTES <= 16384 && CV_BYTES % 128 == 0, "SSM operands");
constexpr uint32_t BARS     = 229376;
constexpr uint32_t SMEM_BYTES = BARS + 512 + 1024;
enum : uint32_t {
  B_P1_FULL = 0, B_P1_EMPTY = 4, B_RG_FULL = 8, B_RG_EMPTY = 13, B_ST_FULL = 18, B_ST_EMPTY = 20,
  B_XS = 22, B_PFREE = 23, B_S2_FULL = 28, B_S2_EMPTY = 32, B_QFREE = 36, B_CTXF = 38, B_KV = 40, B_CONV = 42, B_GATE = 43, B_CTXS = 44, B_GFREE = 52, B_COUNT = 53
};

__device__ __forceinline__ uint32_t smem_u32(const void* p) { return (uint32_t)__cvta_generic_to_shared(p); }
__device__ __forceinline__ void mbar_init(uint32_t bar, uint32_t cnt) {
  asm volatile("mbarrier.init.shared::cta.b64 [%0], %1;" :: "r"(bar), "r"(cnt) : "memory");
}
__device__ __forceinline__ void mbar_expect_tx(uint32_t bar, uint32_t bytes) {
  asm volatile("mbarrier.arrive.expect_tx.shared::cta.b64 _, [%0], %1;" :: "r"(bar), "r"(bytes) : "memory");
}
__device__ __forceinline__ void mbar_arrive(uint32_t bar) {
  asm volatile("mbarrier.arrive.shared::cta.b64 _, [%0];" :: "r"(bar) : "memory");
}
__device__ __forceinline__ void mbar_arrive_n(uint32_t bar, uint32_t n) {
  asm volatile("mbarrier.arrive.shared::cta.b64 _, [%0], %1;" :: "r"(bar), "r"(n) : "memory");
}
__device__ __forceinline__ void mbar_arrive_remote(uint32_t bar, uint32_t cta) {
  asm volatile("{\n.reg .b32 ra;\nmapa.shared::cluster.u32 ra, %0, %1;\n"
               "mbarrier.arrive.shared::cluster.b64 _, [ra];\n}" :: "r"(bar), "r"(cta) : "memory");
}
__device__ __forceinline__ void mbar_arrive_remote_n(uint32_t bar, uint32_t cta, uint32_t n) {
  asm volatile("{\n.reg .b32 ra;\nmapa.shared::cluster.u32 ra, %0, %1;\n"
               "mbarrier.arrive.shared::cluster.b64 _, [ra], %2;\n}" :: "r"(bar), "r"(cta), "r"(n) : "memory");
}
__device__ __forceinline__ bool mbar_try(uint32_t bar, uint32_t parity) {
  uint32_t ok;
  asm volatile("{\n.reg .pred p;\nmbarrier.try_wait.parity.shared::cta.b64 p, [%1], %2;\nselp.u32 %0, 1, 0, p;\n}"
               : "=r"(ok) : "r"(bar), "r"(parity) : "memory");
  return ok;
}
constexpr uint32_t SPIN_LIMIT = 1u << 24;
__device__ __forceinline__ void mbar_wait(uint32_t bar, uint32_t parity) {
  if (mbar_try(bar, parity)) return;
  uint32_t n = 0;
  while (!mbar_try(bar, parity)) { if (++n > SPIN_LIMIT) __trap(); }
}
__device__ __forceinline__ void mbar_wait_slow(uint32_t bar, uint32_t parity) {
  uint32_t n = 0;
  while (!mbar_try(bar, parity)) { if (++n > (SPIN_LIMIT >> 4)) __trap(); __nanosleep(500); }
}
__device__ __forceinline__ unsigned load_epoch() {
  unsigned long long e; asm volatile("ld.relaxed.gpu.global.u64 %0, [%1];" : "=l"(e) : "l"(&g_flags.done) : "memory"); return (unsigned)(e / NMAIN);
}
__device__ __forceinline__ void flag_wait(const unsigned* f, unsigned count, unsigned epoch) {
  const unsigned target = (epoch + 1) * count;
  uint32_t n = 0;
  while (true) {
    unsigned v;
    asm volatile("ld.acquire.gpu.global.u32 %0, [%1];" : "=r"(v) : "l"(f) : "memory");
    if ((int)(v - target) >= 0) break;
    if (++n > SPIN_LIMIT) __trap();
    __nanosleep(20);
  }
}
__device__ __forceinline__ void flag_wait_fast(const unsigned* f, unsigned count, unsigned epoch) {
  const unsigned target = (epoch + 1) * count;
  uint32_t n = 0;
  while (true) {
    unsigned v;
    asm volatile("ld.acquire.gpu.global.u32 %0, [%1];" : "=r"(v) : "l"(f) : "memory");
    if ((int)(v - target) >= 0) break;
    if (++n > SPIN_LIMIT) __trap();
  }
}
__device__ __forceinline__ void fence_async_all() { asm volatile("fence.proxy.async;" ::: "memory"); }
__device__ __forceinline__ void flag_signal(unsigned* f) {
  asm volatile("fence.acq_rel.gpu;" ::: "memory");
  asm volatile("red.relaxed.gpu.global.add.u32 [%0], 1;" :: "l"(f) : "memory");
}
__device__ __forceinline__ void flag_signal_after_bulk(unsigned* f) {
  asm volatile("red.relaxed.gpu.global.add.u32 [%0], 1;" :: "l"(f) : "memory");
}
__device__ __forceinline__ void fence_async_smem() { asm volatile("fence.proxy.async.shared::cta;" ::: "memory"); }
__device__ __forceinline__ void tma_ld2(uint32_t dst, const CUtensorMap* m, uint32_t bar, int c0, int c1) {
  asm volatile("cp.async.bulk.tensor.2d.shared::cluster.global.mbarrier::complete_tx::bytes [%0], [%1, {%3, %4}], [%2];"
               :: "r"(dst), "l"(m), "r"(bar), "r"(c0), "r"(c1) : "memory");
}
__device__ __forceinline__ void tma_ld3(uint32_t dst, const CUtensorMap* m, uint32_t bar, int c0, int c1, int c2) {
  asm volatile("cp.async.bulk.tensor.3d.shared::cluster.global.mbarrier::complete_tx::bytes [%0], [%1, {%3, %4, %5}], [%2];"
               :: "r"(dst), "l"(m), "r"(bar), "r"(c0), "r"(c1), "r"(c2) : "memory");
}
__device__ __forceinline__ void tma_ld3_mc(uint32_t dst, const CUtensorMap* m, uint32_t bar, int c0, int c1, int c2) {
  asm volatile("cp.async.bulk.tensor.3d.shared::cluster.global.mbarrier::complete_tx::bytes.multicast::cluster [%0], [%1, {%3, %4, %5}], [%2], %6;"
               :: "r"(dst), "l"(m), "r"(bar), "r"(c0), "r"(c1), "r"(c2), "h"((uint16_t)3) : "memory");
}
__device__ __forceinline__ void bulk_ld(uint32_t dst, const void* src, uint32_t bytes, uint32_t bar) {
  asm volatile("cp.async.bulk.shared::cluster.global.mbarrier::complete_tx::bytes [%0], [%1], %2, [%3];"
               :: "r"(dst), "l"(src), "r"(bytes), "r"(bar) : "memory");
}
__device__ __forceinline__ void tma_st3(const CUtensorMap* m, uint32_t src, int c0, int c1, int c2) {
  asm volatile("cp.async.bulk.tensor.3d.global.shared::cta.bulk_group [%0, {%2, %3, %4}], [%1];"
               :: "l"(m), "r"(src), "r"(c0), "r"(c1), "r"(c2) : "memory");
}
__device__ __forceinline__ void tma_ld2_mc(uint32_t dst, const CUtensorMap* m, uint32_t bar, int c0, int c1) {
  asm volatile("cp.async.bulk.tensor.2d.shared::cluster.global.mbarrier::complete_tx::bytes.multicast::cluster [%0], [%1, {%3, %4}], [%2], %5;"
               :: "r"(dst), "l"(m), "r"(bar), "r"(c0), "r"(c1), "h"((uint16_t)3) : "memory");
}
__device__ __forceinline__ void tma_st2(const CUtensorMap* m, uint32_t src, int c0, int c1) {
  asm volatile("cp.async.bulk.tensor.2d.global.shared::cta.bulk_group [%0, {%2, %3}], [%1];"
               :: "l"(m), "r"(src), "r"(c0), "r"(c1) : "memory");
}
__device__ __forceinline__ void tma_red2(const CUtensorMap* m, uint32_t src, int c0, int c1) {
  asm volatile("cp.reduce.async.bulk.tensor.2d.global.shared::cta.add.tile.bulk_group [%0, {%2, %3}], [%1];"
               :: "l"(m), "r"(src), "r"(c0), "r"(c1) : "memory");
}
__device__ __forceinline__ void tma_pf3(const CUtensorMap* m, int c0, int c1, int c2) {
  asm volatile("cp.async.bulk.prefetch.tensor.3d.L2.global.tile [%0, {%1, %2, %3}];" :: "l"(m), "r"(c0), "r"(c1), "r"(c2) : "memory");
}
__device__ __forceinline__ void bulk_prefetch(const void* src, uint32_t bytes) {
  asm volatile("cp.async.bulk.prefetch.L2.global [%0], %1;" :: "l"(src), "r"(bytes) : "memory");
}
__device__ __forceinline__ void bulk_commit() { asm volatile("cp.async.bulk.commit_group;" ::: "memory"); }
__device__ __forceinline__ void bulk_wait_read() { asm volatile("cp.async.bulk.wait_group.read 0;" ::: "memory"); }
__device__ __forceinline__ void bulk_wait_all() { asm volatile("cp.async.bulk.wait_group 0;" ::: "memory"); }
__device__ __forceinline__ void prefetch_map(const CUtensorMap* m) { asm volatile("prefetch.tensormap [%0];" :: "l"(m) : "memory"); }
__device__ __forceinline__ void wg_fence() { asm volatile("wgmma.fence.sync.aligned;" ::: "memory"); }
__device__ __forceinline__ void wg_commit() { asm volatile("wgmma.commit_group.sync.aligned;" ::: "memory"); }
template <int N> __device__ __forceinline__ void wg_wait() { asm volatile("wgmma.wait_group.sync.aligned %0;" :: "n"(N) : "memory"); }
template <int N> __device__ __forceinline__ void reg_fence(float (&d)[N]) {
#pragma unroll
  for (int i = 0; i < N; i++) asm volatile("" : "+f"(d[i]) :: "memory");
}
template <int N> __device__ __forceinline__ void reg_fence(uint32_t (&d)[N]) {
#pragma unroll
  for (int i = 0; i < N; i++) asm volatile("" : "+r"(d[i]) :: "memory");
}
__device__ __forceinline__ uint32_t fresh_tid() { uint32_t t; asm volatile("mov.u32 %0, %%tid.x;" : "=r"(t)); return t; }
__device__ __forceinline__ uint32_t lane_base16() {
  const uint32_t t = fresh_tid(), lane = t & 31, wq = (t >> 5) & 3;
  return (16 * wq + (lane & 7) + 8 * ((lane >> 3) & 1)) * 128 + (((lane >> 4) ^ (lane & 7)) << 4);
}
__device__ __forceinline__ void named_sync(int id, int n) { asm volatile("bar.sync %0, %1;" :: "r"(id), "r"(n) : "memory"); }
__device__ __forceinline__ void named_arrive(int id, int n) { asm volatile("bar.arrive %0, %1;" :: "r"(id), "r"(n) : "memory"); }
__device__ __forceinline__ uint32_t pack_bf16(float lo, float hi) {
  uint32_t r; asm("cvt.rn.bf16x2.f32 %0, %1, %2;" : "=r"(r) : "f"(hi), "f"(lo)); return r;
}
__device__ __forceinline__ float ex2(float x) { float y; asm("ex2.approx.ftz.f32 %0, %1;" : "=f"(y) : "f"(x)); return y; }
__device__ __forceinline__ void stsm4(uint32_t addr, uint32_t a, uint32_t b, uint32_t c, uint32_t d) {
  asm volatile("stmatrix.sync.aligned.m8n8.x4.shared.b16 [%0], {%1, %2, %3, %4};" :: "r"(addr), "r"(a), "r"(b), "r"(c), "r"(d) : "memory");
}
__device__ __forceinline__ void stsm4t(uint32_t addr, uint32_t a, uint32_t b, uint32_t c, uint32_t d) {
  asm volatile("stmatrix.sync.aligned.m8n8.x4.trans.shared.b16 [%0], {%1, %2, %3, %4};" :: "r"(addr), "r"(a), "r"(b), "r"(c), "r"(d) : "memory");
}
__device__ __forceinline__ uint64_t mk_desc(uint32_t addr, uint32_t lbo, uint32_t sbo) {
  return (uint64_t)(((addr & 0x3FFFF) >> 4) | ((lbo >> 4) << 16)) | ((uint64_t)((sbo >> 4) | (1u << 30)) << 32);
}
__device__ __forceinline__ uint64_t desc_k(uint32_t addr)  { return mk_desc(addr, 16, 1024); }
__device__ __forceinline__ uint64_t desc_mn(uint32_t addr) { return mk_desc(addr, 8192, 1024); }
__device__ __forceinline__ uint64_t desc_add(uint64_t d, uint32_t bytes) { return d + (bytes >> 4); }

__device__ __forceinline__ void wgmma_ss_n256_tb(float (&d)[128], uint64_t da, uint64_t db, int sd) {
  asm volatile("{\n.reg .pred p;\nsetp.ne.b32 p, %130, 0;\n"
    "wgmma.mma_async.sync.aligned.m64n256k16.f32.bf16.bf16 "
    "{%0, %1, %2, %3, %4, %5, %6, %7, %8, %9, %10, %11, %12, %13, %14, %15, "
    "%16, %17, %18, %19, %20, %21, %22, %23, %24, %25, %26, %27, %28, %29, %30, %31, "
    "%32, %33, %34, %35, %36, %37, %38, %39, %40, %41, %42, %43, %44, %45, %46, %47, "
    "%48, %49, %50, %51, %52, %53, %54, %55, %56, %57, %58, %59, %60, %61, %62, %63, "
    "%64, %65, %66, %67, %68, %69, %70, %71, %72, %73, %74, %75, %76, %77, %78, %79, "
    "%80, %81, %82, %83, %84, %85, %86, %87, %88, %89, %90, %91, %92, %93, %94, %95, "
    "%96, %97, %98, %99, %100, %101, %102, %103, %104, %105, %106, %107, %108, %109, %110, %111, "
    "%112, %113, %114, %115, %116, %117, %118, %119, %120, %121, %122, %123, %124, %125, %126, %127}, "
    "%128, %129, p, 1, 1, 0, 1;\n}"
    : "+f"(d[0]), "+f"(d[1]), "+f"(d[2]), "+f"(d[3]), "+f"(d[4]), "+f"(d[5]), "+f"(d[6]), "+f"(d[7]),
      "+f"(d[8]), "+f"(d[9]), "+f"(d[10]), "+f"(d[11]), "+f"(d[12]), "+f"(d[13]), "+f"(d[14]), "+f"(d[15]),
      "+f"(d[16]), "+f"(d[17]), "+f"(d[18]), "+f"(d[19]), "+f"(d[20]), "+f"(d[21]), "+f"(d[22]), "+f"(d[23]),
      "+f"(d[24]), "+f"(d[25]), "+f"(d[26]), "+f"(d[27]), "+f"(d[28]), "+f"(d[29]), "+f"(d[30]), "+f"(d[31]),
      "+f"(d[32]), "+f"(d[33]), "+f"(d[34]), "+f"(d[35]), "+f"(d[36]), "+f"(d[37]), "+f"(d[38]), "+f"(d[39]),
      "+f"(d[40]), "+f"(d[41]), "+f"(d[42]), "+f"(d[43]), "+f"(d[44]), "+f"(d[45]), "+f"(d[46]), "+f"(d[47]),
      "+f"(d[48]), "+f"(d[49]), "+f"(d[50]), "+f"(d[51]), "+f"(d[52]), "+f"(d[53]), "+f"(d[54]), "+f"(d[55]),
      "+f"(d[56]), "+f"(d[57]), "+f"(d[58]), "+f"(d[59]), "+f"(d[60]), "+f"(d[61]), "+f"(d[62]), "+f"(d[63]),
      "+f"(d[64]), "+f"(d[65]), "+f"(d[66]), "+f"(d[67]), "+f"(d[68]), "+f"(d[69]), "+f"(d[70]), "+f"(d[71]),
      "+f"(d[72]), "+f"(d[73]), "+f"(d[74]), "+f"(d[75]), "+f"(d[76]), "+f"(d[77]), "+f"(d[78]), "+f"(d[79]),
      "+f"(d[80]), "+f"(d[81]), "+f"(d[82]), "+f"(d[83]), "+f"(d[84]), "+f"(d[85]), "+f"(d[86]), "+f"(d[87]),
      "+f"(d[88]), "+f"(d[89]), "+f"(d[90]), "+f"(d[91]), "+f"(d[92]), "+f"(d[93]), "+f"(d[94]), "+f"(d[95]),
      "+f"(d[96]), "+f"(d[97]), "+f"(d[98]), "+f"(d[99]), "+f"(d[100]), "+f"(d[101]), "+f"(d[102]), "+f"(d[103]),
      "+f"(d[104]), "+f"(d[105]), "+f"(d[106]), "+f"(d[107]), "+f"(d[108]), "+f"(d[109]), "+f"(d[110]), "+f"(d[111]),
      "+f"(d[112]), "+f"(d[113]), "+f"(d[114]), "+f"(d[115]), "+f"(d[116]), "+f"(d[117]), "+f"(d[118]), "+f"(d[119]),
      "+f"(d[120]), "+f"(d[121]), "+f"(d[122]), "+f"(d[123]), "+f"(d[124]), "+f"(d[125]), "+f"(d[126]), "+f"(d[127])
    : "l"(da), "l"(db), "r"(sd));
}
__device__ __forceinline__ void wgmma_ss_n64(float (&d)[32], uint64_t da, uint64_t db, int sd) {
  asm volatile("{\n.reg .pred p;\nsetp.ne.b32 p, %34, 0;\n"
    "wgmma.mma_async.sync.aligned.m64n64k16.f32.bf16.bf16 "
    "{%0, %1, %2, %3, %4, %5, %6, %7, %8, %9, %10, %11, %12, %13, %14, %15, "
    "%16, %17, %18, %19, %20, %21, %22, %23, %24, %25, %26, %27, %28, %29, %30, %31}, "
    "%32, %33, p, 1, 1, 0, 0;\n}"
    : "+f"(d[0]), "+f"(d[1]), "+f"(d[2]), "+f"(d[3]), "+f"(d[4]), "+f"(d[5]), "+f"(d[6]), "+f"(d[7]),
      "+f"(d[8]), "+f"(d[9]), "+f"(d[10]), "+f"(d[11]), "+f"(d[12]), "+f"(d[13]), "+f"(d[14]), "+f"(d[15]),
      "+f"(d[16]), "+f"(d[17]), "+f"(d[18]), "+f"(d[19]), "+f"(d[20]), "+f"(d[21]), "+f"(d[22]), "+f"(d[23]),
      "+f"(d[24]), "+f"(d[25]), "+f"(d[26]), "+f"(d[27]), "+f"(d[28]), "+f"(d[29]), "+f"(d[30]), "+f"(d[31])
    : "l"(da), "l"(db), "r"(sd));
}
__device__ __forceinline__ void wgmma_rs_n256_tb(float (&d)[128], uint32_t a0, uint32_t a1, uint32_t a2, uint32_t a3, uint64_t db, int sd) {
  asm volatile("{\n.reg .pred p;\nsetp.ne.b32 p, %133, 0;\n"
    "wgmma.mma_async.sync.aligned.m64n256k16.f32.bf16.bf16 "
    "{%0, %1, %2, %3, %4, %5, %6, %7, %8, %9, %10, %11, %12, %13, %14, %15, "
    "%16, %17, %18, %19, %20, %21, %22, %23, %24, %25, %26, %27, %28, %29, %30, %31, "
    "%32, %33, %34, %35, %36, %37, %38, %39, %40, %41, %42, %43, %44, %45, %46, %47, "
    "%48, %49, %50, %51, %52, %53, %54, %55, %56, %57, %58, %59, %60, %61, %62, %63, "
    "%64, %65, %66, %67, %68, %69, %70, %71, %72, %73, %74, %75, %76, %77, %78, %79, "
    "%80, %81, %82, %83, %84, %85, %86, %87, %88, %89, %90, %91, %92, %93, %94, %95, "
    "%96, %97, %98, %99, %100, %101, %102, %103, %104, %105, %106, %107, %108, %109, %110, %111, "
    "%112, %113, %114, %115, %116, %117, %118, %119, %120, %121, %122, %123, %124, %125, %126, %127}, "
    "{%128, %129, %130, %131}, %132, p, 1, 1, 1;\n}"
    : "+f"(d[0]), "+f"(d[1]), "+f"(d[2]), "+f"(d[3]), "+f"(d[4]), "+f"(d[5]), "+f"(d[6]), "+f"(d[7]),
      "+f"(d[8]), "+f"(d[9]), "+f"(d[10]), "+f"(d[11]), "+f"(d[12]), "+f"(d[13]), "+f"(d[14]), "+f"(d[15]),
      "+f"(d[16]), "+f"(d[17]), "+f"(d[18]), "+f"(d[19]), "+f"(d[20]), "+f"(d[21]), "+f"(d[22]), "+f"(d[23]),
      "+f"(d[24]), "+f"(d[25]), "+f"(d[26]), "+f"(d[27]), "+f"(d[28]), "+f"(d[29]), "+f"(d[30]), "+f"(d[31]),
      "+f"(d[32]), "+f"(d[33]), "+f"(d[34]), "+f"(d[35]), "+f"(d[36]), "+f"(d[37]), "+f"(d[38]), "+f"(d[39]),
      "+f"(d[40]), "+f"(d[41]), "+f"(d[42]), "+f"(d[43]), "+f"(d[44]), "+f"(d[45]), "+f"(d[46]), "+f"(d[47]),
      "+f"(d[48]), "+f"(d[49]), "+f"(d[50]), "+f"(d[51]), "+f"(d[52]), "+f"(d[53]), "+f"(d[54]), "+f"(d[55]),
      "+f"(d[56]), "+f"(d[57]), "+f"(d[58]), "+f"(d[59]), "+f"(d[60]), "+f"(d[61]), "+f"(d[62]), "+f"(d[63]),
      "+f"(d[64]), "+f"(d[65]), "+f"(d[66]), "+f"(d[67]), "+f"(d[68]), "+f"(d[69]), "+f"(d[70]), "+f"(d[71]),
      "+f"(d[72]), "+f"(d[73]), "+f"(d[74]), "+f"(d[75]), "+f"(d[76]), "+f"(d[77]), "+f"(d[78]), "+f"(d[79]),
      "+f"(d[80]), "+f"(d[81]), "+f"(d[82]), "+f"(d[83]), "+f"(d[84]), "+f"(d[85]), "+f"(d[86]), "+f"(d[87]),
      "+f"(d[88]), "+f"(d[89]), "+f"(d[90]), "+f"(d[91]), "+f"(d[92]), "+f"(d[93]), "+f"(d[94]), "+f"(d[95]),
      "+f"(d[96]), "+f"(d[97]), "+f"(d[98]), "+f"(d[99]), "+f"(d[100]), "+f"(d[101]), "+f"(d[102]), "+f"(d[103]),
      "+f"(d[104]), "+f"(d[105]), "+f"(d[106]), "+f"(d[107]), "+f"(d[108]), "+f"(d[109]), "+f"(d[110]), "+f"(d[111]),
      "+f"(d[112]), "+f"(d[113]), "+f"(d[114]), "+f"(d[115]), "+f"(d[116]), "+f"(d[117]), "+f"(d[118]), "+f"(d[119]),
      "+f"(d[120]), "+f"(d[121]), "+f"(d[122]), "+f"(d[123]), "+f"(d[124]), "+f"(d[125]), "+f"(d[126]), "+f"(d[127])
    : "r"(a0), "r"(a1), "r"(a2), "r"(a3), "l"(db), "r"(sd));
}
__device__ __forceinline__ void wgmma_rs_n64_tb(float (&d)[32], uint32_t a0, uint32_t a1, uint32_t a2, uint32_t a3, uint64_t db, int sd) {
  asm volatile("{\n.reg .pred p;\nsetp.ne.b32 p, %37, 0;\n"
    "wgmma.mma_async.sync.aligned.m64n64k16.f32.bf16.bf16 "
    "{%0, %1, %2, %3, %4, %5, %6, %7, %8, %9, %10, %11, %12, %13, %14, %15, "
    "%16, %17, %18, %19, %20, %21, %22, %23, %24, %25, %26, %27, %28, %29, %30, %31}, "
    "{%32, %33, %34, %35}, %36, p, 1, 1, 1;\n}"
    : "+f"(d[0]), "+f"(d[1]), "+f"(d[2]), "+f"(d[3]), "+f"(d[4]), "+f"(d[5]), "+f"(d[6]), "+f"(d[7]),
      "+f"(d[8]), "+f"(d[9]), "+f"(d[10]), "+f"(d[11]), "+f"(d[12]), "+f"(d[13]), "+f"(d[14]), "+f"(d[15]),
      "+f"(d[16]), "+f"(d[17]), "+f"(d[18]), "+f"(d[19]), "+f"(d[20]), "+f"(d[21]), "+f"(d[22]), "+f"(d[23]),
      "+f"(d[24]), "+f"(d[25]), "+f"(d[26]), "+f"(d[27]), "+f"(d[28]), "+f"(d[29]), "+f"(d[30]), "+f"(d[31])
    : "r"(a0), "r"(a1), "r"(a2), "r"(a3), "l"(db), "r"(sd));
}

__device__ __forceinline__ uint4 lds16(uint32_t a) {
  uint4 v; asm volatile("ld.shared.v4.u32 {%0, %1, %2, %3}, [%4];" : "=r"(v.x), "=r"(v.y), "=r"(v.z), "=r"(v.w) : "r"(a) : "memory"); return v;
}
__device__ __forceinline__ void sts16(uint32_t a, uint32_t x, uint32_t y, uint32_t z, uint32_t w) {
  asm volatile("st.shared.v4.u32 [%0], {%1, %2, %3, %4};" :: "r"(a), "r"(x), "r"(y), "r"(z), "r"(w) : "memory");
}
__device__ __forceinline__ uint32_t lds4(uint32_t a) { uint32_t v; asm volatile("ld.shared.u32 %0, [%1];" : "=r"(v) : "r"(a) : "memory"); return v; }
__device__ __forceinline__ uint32_t lds4v(uint32_t a) { uint32_t v; asm volatile("ld.volatile.shared.u32 %0, [%1];" : "=r"(v) : "r"(a) : "memory"); return v; }
__device__ __forceinline__ uint32_t bmul(uint32_t a, uint32_t b) { uint32_t r; asm("mul.rn.bf16x2 %0, %1, %2;" : "=r"(r) : "r"(a), "r"(b)); return r; }
__device__ __forceinline__ uint32_t badd(uint32_t a, uint32_t b) { uint32_t r; asm("add.rn.bf16x2 %0, %1, %2;" : "=r"(r) : "r"(a), "r"(b)); return r; }

__device__ __forceinline__ void ldsm4(uint32_t (&r)[4], uint32_t a) {
  asm volatile("ldmatrix.sync.aligned.m8n8.x4.shared.b16 {%0, %1, %2, %3}, [%4];" : "=r"(r[0]), "=r"(r[1]), "=r"(r[2]), "=r"(r[3]) : "r"(a) : "memory");
}
__device__ __forceinline__ void ldsm4t(uint32_t (&r)[4], uint32_t a) {
  asm volatile("ldmatrix.sync.aligned.m8n8.x4.trans.shared.b16 {%0, %1, %2, %3}, [%4];" : "=r"(r[0]), "=r"(r[1]), "=r"(r[2]), "=r"(r[3]) : "r"(a) : "memory");
}
__device__ __forceinline__ uint32_t transpose8(uint32_t a) { uint32_t d; asm volatile("movmatrix.sync.aligned.m8n8.trans.b16 %0, %1;" : "=r"(d) : "r"(a)); return d; }

__device__ __forceinline__ void mma16816(float (&d)[4], const uint32_t (&a)[4], uint32_t b0, uint32_t b1) {
  asm volatile("mma.sync.aligned.m16n8k16.row.col.f32.bf16.bf16.f32 {%0, %1, %2, %3}, {%4, %5, %6, %7}, {%8, %9}, {%0, %1, %2, %3};"
               : "+f"(d[0]), "+f"(d[1]), "+f"(d[2]), "+f"(d[3]) : "r"(a[0]), "r"(a[1]), "r"(a[2]), "r"(a[3]), "r"(b0), "r"(b1));
}

#define P1_SPLIT 0
#define O_ROT 1
#define STG_K1 2
#define STG_K2 10
#define STG_Q1 2
#define STG_Q2 6
#define CTX_K 0
#define PF_QA 99
#define PF_WV 99
#define PF_END 0
#define PF_CV 1
#define PACE_A 850
#define PACE_B 400
#define ARRIVE_KK 12
#define SIDE_DELAY_NS 4000
#define KVH(h) (h)
#define HEAD_MAP 1
#define EARLY_LD 3
constexpr int RED_BAR = 6;
constexpr int CV_BAR = 5;
constexpr int PP_BAR = 3;
template <int V> struct Int { static constexpr int value = V; };
struct Ring {
  uint32_t slot, phase;
  __device__ __forceinline__ void next() { if (++slot == NSLOT) { slot = 0; phase ^= 1; } }
};
__device__ __forceinline__ uint32_t bar_addr(uint32_t sb, uint32_t i) { return sb + BARS + 8 * i; }
__device__ __forceinline__ uint32_t q_region(uint32_t sb, int w) { return sb + QREG + (w ^ 1) * 32768; }

struct Role { int h, j; };
__device__ __forceinline__ Role get_role() {
  int cta; asm volatile("mov.u32 %0, %%ctaid.x;" : "=r"(cta));
  const int c = cta >> 1;
  int h, u;
  if (c < 4) { h = 15; u = c; }
  else if (c < 36) { h = (c - 4) & 7; u = (c - 4) >> 3; }
  else { h = 8 + (c - 36) % 7; u = (c - 36) / 7; }
  return Role{h, 2 * u + (cta & 1)};
}
__device__ __forceinline__ int fresh_warp() { return __shfl_sync(0xffffffffu, fresh_tid() >> 5, 0); }

__device__ __forceinline__ int q_tile(int h, int j, int which) { return ((h < 8) == (which == 0)) ? 15 - j : j; }

__device__ __forceinline__ int o_chunk(int h, int c) { const int x = c + O_ROT * (h & 7); return x % 7; }

__device__ __forceinline__ int num_private(int qt) { return (qt & 1) ? 5 : 1; }
__device__ __forceinline__ void ring_acquire(uint32_t sb, Ring& r, uint32_t bytes) {
  mbar_wait(bar_addr(sb, B_RG_EMPTY + r.slot), r.phase ^ 1);
  mbar_expect_tx(bar_addr(sb, B_RG_FULL + r.slot), bytes);
}
__device__ __forceinline__ void load_tile4(uint32_t dst, const CUtensorMap* m, uint32_t full, int row, int blk0, int rank, bool shared) {
  if (shared) {
    tma_ld3_mc(dst + rank * 16384, m, full, 0, row, blk0 + 2 * rank);
  } else {
    tma_ld3(dst, m, full, 0, row, blk0);
    tma_ld3(dst + 16384, m, full, 0, row, blk0 + 2);
  }
}
__device__ __forceinline__ void producer_main(const Params& p, uint32_t sb) {
  const Role ro = get_role();
  const int h = ro.h, j = ro.j, rank = j & 1;
  auto prefetch_q = [&](int qt) {
    bulk_prefetch(p.b_x + (size_t)(qt * 128 + (h & 7) * 16) * DM, 16 * DM * 2);
    if (j < 7) { tma_pf3(&p.wq, 0, j * 64, h * 4); tma_pf3(&p.wq, 0, j * 64, h * 4 + 2); }
  };
  for (int it = EARLY_LD; it < 71; it++) {
    const int t = it >> 4, k = it & 15, s = it & 3;
    mbar_wait(bar_addr(sb, B_P1_EMPTY + s), ((it >> 2) & 1) ^ 1);
    const uint32_t full = bar_addr(sb, B_P1_FULL + s), dst = sb + s * P1_STAGE;
    mbar_expect_tx(full, P1_STAGE);
    if (t < 4) {
      tma_ld2(dst, &p.ckv, full, k * 64, (2 * j + (t & 1)) * 128);
      load_tile4(dst + 16384, (t >> 1) ? &p.wuv : &p.wuk, full, k * 64, h * 4, rank, true);
    } else {
      tma_ld2(dst, &p.x, full, k * 64, q_tile(h, j, 0) * 128);
      load_tile4(dst + 16384, &p.wq, full, k * 64, h * 4, rank, true);
    }
    if (it == PF_QA) prefetch_q(q_tile(h, j, 0));
    if (it == PF_WV) { for (int i = 0; i < 4; i++) tma_pf3(&p.wuv, 0, (2 * j + (i >> 1)) * 64, h * 4 + 2 * (i & 1)); }
  }
  mbar_wait(bar_addr(sb, B_P1_EMPTY + 3), 0);
  mbar_wait(bar_addr(sb, B_XS), 0);
  mbar_expect_tx(bar_addr(sb, B_RG_FULL + 4), CV_BYTES);
  bulk_ld(sb + CV_X, g_xs + (size_t)(h * 8 + j) * CV_BYTES, CV_BYTES, bar_addr(sb, B_RG_FULL + 4));
  Ring r{0, 1};
  int hs = 5;
  auto acquire = [&](bool shared) {
    mbar_wait(bar_addr(sb, B_RG_EMPTY + r.slot), r.phase ^ 1);
    if (shared && hs < 5) {
      mbar_arrive_remote(bar_addr(sb, B_PFREE + r.slot), rank ^ 1);
      mbar_wait(bar_addr(sb, B_PFREE + r.slot), 0);
      hs++;
    }
    mbar_expect_tx(bar_addr(sb, B_RG_FULL + r.slot), 32768);
  };
  mbar_wait(bar_addr(sb, B_KV), 0);
  for (int which = 0; which < 2; which++) {
    const int qt = q_tile(h, j, which);
    if (which == 1) {
      for (int kc = 0; kc < 7; kc++) {
        ring_acquire(sb, r, 32768);
        load_tile4(sb + r.slot * SLOT, &p.wq, bar_addr(sb, B_RG_FULL + r.slot), kc * 64, h * 4, rank, false);
        r.next();
        if (kc == 0 || (kc & 1)) {
          ring_acquire(sb, r, kc == 0 ? 16384 : 32768);
          const uint32_t full = bar_addr(sb, B_RG_FULL + r.slot), dst = sb + r.slot * SLOT;
          tma_ld2(dst, &p.x, full, kc * 64, qt * 128);
          if (kc > 0) tma_ld2(dst + 16384, &p.x, full, kc * 64 + 64, qt * 128);
          r.next();
        }
      }
      hs = 0;
    }
    const int n = 2 * qt + 2, npriv = num_private(qt), nb = qt & ~1;
    for (int f = 0; f < 2 * n; f++) {
      if (PF_END && f == max(2 * n - PF_END, 0)) {
        if (which == 0) bulk_prefetch(p.b_x + (size_t)((15 - qt) * 128 + (h & 7) * 16) * DM, 16 * DM * 2);
        else bulk_prefetch(p.b_wo + (size_t)(h * HD + j * 32) * DM, 32 * DM * 2);
      }
      const bool isK = (f == 0) || ((f & 1) && f < 2 * n - 1);
      const int i = isK ? (f + 1) >> 1 : (f == 2 * n - 1 ? n - 1 : (f >> 1) - 1);
      int tile = n - 1 - i;
      if (which == 0) { const int b = i >> 1; tile = b >= nb ? i : 2 * (2 * b < nb ? 2 * b : 2 * b - nb + 1) + (i & 1); }
      if (!isK && (tile & 2)) mbar_wait(bar_addr(sb, B_KV + 1), 0);
      if (which == 0 && f < 2) mbar_wait(bar_addr(sb, B_P1_EMPTY + f), 1);
      const bool shared = (which ? f : 2 * n - 1 - f) >= npriv;
      acquire(shared);
      load_tile4(sb + r.slot * SLOT, &p.kv, bar_addr(sb, B_RG_FULL + r.slot), ((isK ? 0 : NH) + KVH(h)) * SEQ + tile * 64, 0, rank, shared);
      r.next();
    }
  }
  for (int i = 0; i < 14; i++) {
    acquire(true);
    tma_ld2_mc(sb + r.slot * SLOT + rank * 16384, &p.wo, bar_addr(sb, B_RG_FULL + r.slot), o_chunk(h, i >> 1) * 64, ((i & 1) ? h ^ 8 : h) * HD + rank * 128);
    r.next();
  }
}

__device__ __forceinline__ void storer_main(const Params& p, uint32_t sb) {
  const Role ro = get_role();
  const int h = ro.h, j = ro.j, w = fresh_warp() - 1;
  const uint32_t full = bar_addr(sb, B_ST_FULL + w), empty = bar_addr(sb, B_ST_EMPTY + w);
  const int lane = threadIdx.x & 31;
  const unsigned epoch = load_epoch();
  for (int job = 0; job < 8; job++) {
    const int t = job >> 1, half = job & 1;
    mbar_wait(full, job & 1);
    const uint32_t src = sb + P1_STG + w * 16384 + (lane >> 3) * 128;
    bf16* dst = g_kv + (size_t)(((t >> 1) * NH + KVH(h)) * SEQ + (2 * j + (t & 1)) * 128 + w * 64 + (lane >> 3)) * HD + half * 128 + (lane & 7) * 8;
    const uint32_t t0 = (uint32_t)clock(), pace = job < 6 ? PACE_A : PACE_B;
#pragma unroll 1
    for (int i0 = 0; i0 < 32; i0 += 4) {
      while ((uint32_t)clock() - t0 < (i0 >> 2) * pace) __nanosleep(40);
#pragma unroll
      for (int i = i0; i < i0 + 4; i++) {
        const int r4 = (i & 15) * 4;
        const uint4 v = lds16(src + (i >> 4) * 8192 + r4 * 128 + (((lane & 7) ^ ((r4 + (lane >> 3)) & 7)) << 4));
        *reinterpret_cast<uint4*>(dst + r4 * HD + (i >> 4) * 64) = v;
      }
    }
    __syncwarp();
    if (lane == 0) {
      mbar_arrive(empty);
      if (job == 5 || job == 7) flag_signal(&g_flags.kv_ready[2 * h + (job == 7)].v);
    }
    __syncwarp();
  }
  const int cta = h * 8 + j, qt = q_tile(h, j, 1);
  const uint32_t qreg = q_region(sb, w);
  {
    mbar_wait(bar_addr(sb, B_CTXS + 4 * w), 0);
    uint4* z = reinterpret_cast<uint4*>(p.out + (size_t)(qt * 128 + w * 64 + (h & 7) * 8 + (lane >> 2)) * OUTW + DA) + (lane & 3);
#pragma unroll
    for (int i = 0; i < 14; i++) z[4 * i] = make_uint4(0, 0, 0, 0);
    __syncwarp();
    if (lane != 0) return;
    for (int b = 0; b < 4; b++) {
      mbar_wait(bar_addr(sb, B_CTXS + 4 * w + b), 0);
      tma_st3(&p.ctxs, qreg + b * 8192, 0, cta * 128 + w * 64, b);
      bulk_commit();
    }
    bulk_wait_read();
    mbar_arrive(empty);
    bulk_wait_all();
    flag_signal(&g_flags.ctx_ready[cta * 2 + w].v);
    flag_signal_after_bulk(&g_flags.out_ready[qt * 2 + w].v);
  }
  {
    const int wx = w ^ 1;
    flag_wait(&g_flags.ctx_ready[(cta ^ 64) * 2 + wx].v, 1, epoch);
    flag_wait(&g_flags.out_ready[qt * 2 + wx].v, 8, epoch);
    fence_async_all();
    mbar_wait(bar_addr(sb, B_QFREE + w), 0);
    mbar_expect_tx(bar_addr(sb, B_CTXF + w), 32768);
    tma_ld3(qreg, &p.ctx, bar_addr(sb, B_CTXF + w), 0, (cta ^ 64) * 128 + wx * 64, 0);
    for (int ch = 0; ch < 7; ch++) {
      const int b = ch & 1;
      mbar_wait(bar_addr(sb, B_S2_FULL + w * 2 + b), (ch >> 1) & 1);
      tma_red2(&p.part, qreg + b * 8192, DA + o_chunk(h, ch) * 64, qt * 128 + wx * 64);
      bulk_commit();
      if (ch == 0 && w == 1) mbar_arrive(bar_addr(sb, B_GFREE));
      bulk_wait_read();
      mbar_arrive(bar_addr(sb, B_S2_EMPTY + w * 2 + b));
    }
    GT(48 + w);
    bulk_wait_all();
    GT(50 + w); GT(52 + w); GT(56);
  }
}

template <int OFF, int NB, int NREG>
__device__ __forceinline__ void store_blocks(uint32_t base, uint32_t lanebase, const uint32_t (&pk)[NREG]) {
#pragma unroll
  for (int J = 0; J < NB * 8; J += 2) {
    const uint32_t a = base + (J >> 3) * 8192 + (lanebase ^ ((J & 7) << 4));
    stsm4(a, pk[OFF + 2 * J], pk[OFF + 2 * J + 1], pk[OFF + 2 * J + 2], pk[OFF + 2 * J + 3]);
  }
}
__device__ __forceinline__ void warp_arrive(uint32_t bar, int lane) { __syncwarp(); if (lane == 0) mbar_arrive(bar); }
__device__ __forceinline__ void release(uint32_t bar, int lane, int rank, bool shared) {
  if (shared) { if (lane < 2) mbar_arrive_remote(bar, rank ^ lane); }
  else if (lane == 0) mbar_arrive_n(bar, 2);
}

template <int W> __device__ __forceinline__ constexpr int cv_tile(int u) { return 2 * u + ((u ^ W) & 1); }
template <int W>
__device__ __forceinline__ void conv_mma(float (&ca)[8][4], uint32_t abase, uint32_t baddr) {
#pragma unroll 1
  for (int rr = 0; rr < 2; rr++) {
    uint32_t fa[16][4], fb[8][4];
#pragma unroll
    for (int i = 0; i < 8; i++) ldsm4(fb[i], baddr + i * 256 - rr * 16);
#pragma unroll
    for (int jj = 0; jj < 16 - W; jj++) {
      const uint32_t ad = abase + jj * 256 + rr * 32;
      fa[jj][0] = lds4(ad); fa[jj][1] = lds4(ad + 16); fa[jj][2] = lds4v(ad + 16); fa[jj][3] = lds4(ad + 32);
    }
#pragma unroll
    for (int jj = 0; jj < 16 - W; jj++)
#pragma unroll
      for (int u = 0; u < 8; u++) {
        const int sx = cv_tile<W>(u) - jj;
        if (sx >= 0) mma16816(ca[u], fa[jj], fb[(sx >> 1) & 7][2 * (sx & 1)], fb[(sx >> 1) & 7][2 * (sx & 1) + 1]);
      }
  }
}

__device__ __forceinline__ void consumer_main(const Params& p, uint32_t sb) {
  const int lane = fresh_tid() & 31, w = (fresh_warp() >> 2) - 1;
  const uint32_t lb = lane_base16();
  int qt, rank;
  { const Role ro = get_role(); qt = q_tile(ro.h, ro.j, 0); rank = ro.j & 1; }
  const uint32_t st_full = bar_addr(sb, B_ST_FULL + w), st_empty = bar_addr(sb, B_ST_EMPTY + w);
  const uint32_t stg = sb + P1_STG + w * 16384;

  auto turn_begin = [&]() { named_sync(PP_BAR + w, 256); };
  auto turn_end = [&]() { named_arrive(PP_BAR + (w ^ 1), 256); };
  if (w == 0) named_arrive(PP_BAR + 1, 256);
  float acc[128];
#pragma unroll
  for (int i = 0; i < 128; i++) acc[i] = 0.f;
  uint32_t pk[64];
#pragma unroll
  for (int i = 0; i < 64; i++) pk[i] = 0;
  PDECL;
  TR_DECL;
  TR(0);
  TSG(0); TS(1);
  const uint32_t qreg = q_region(sb, w);
  for (int t = 0; t < 5; t++) {
    const int nk = t < 4 ? 16 : 7;
#pragma unroll 1
    for (int k = 0; k < nk; k++) {
      const int it = t * 16 + k, s = k & 3;
      mbar_wait(bar_addr(sb, B_P1_FULL + s), (it >> 2) & 1);
      TR(1);
      const uint64_t da = desc_k(sb + s * P1_STAGE + w * 8192), db = desc_mn(sb + s * P1_STAGE + 16384);
      turn_begin();
      wg_fence();
#pragma unroll
      for (int kk = 0; kk < 4; kk++) wgmma_ss_n256_tb(acc, desc_add(da, kk * 32), desc_add(db, kk * 2048), (k | kk) != 0);
      wg_commit();
      turn_end();
      TR(3);
      wg_wait<1>();
      if (k > 0) release(bar_addr(sb, B_P1_EMPTY + ((k - 1) & 3)), lane, rank, true);
      const int k1 = t < 4 ? STG_K1 : STG_Q1, k2 = t < 4 ? STG_K2 : STG_Q2;
      if (t > 0 && (k == k1 || k == k2)) {
        const int job = 2 * (t - 1) + (k != k1);
        if (job > 0) mbar_wait(st_empty, (job - 1) & 1);
        if (k == k1) store_blocks<0, 2>(stg, lb, pk); else store_blocks<32, 2>(stg, lb, pk);
        warp_arrive(st_full, lane);
      }
      TR(5);
    }
    wg_wait<0>();
    TR(6);
    reg_fence(acc);
    release(bar_addr(sb, B_P1_EMPTY + ((nk - 1) & 3)), lane, rank, true);
#pragma unroll
    for (int i = 0; i < 64; i++) pk[i] = pack_bf16(acc[2 * i], acc[2 * i + 1]);
    TS(t < 4 ? 2 + t : 60);
  }
  TS(6);
  {
    const uint32_t ft = fresh_tid(), wq = (ft >> 5) & 3, ln = ft & 31, g = ln >> 2, c = ln & 3;
    const uint32_t cx = sb + CV_X, hE = cx + CV_HE, hO = hE + CV_HCOPY;
    float ca[8][4];
#pragma unroll
    for (int i = 0; i < 8; i++) { ca[i][0] = 0.f; ca[i][1] = 0.f; ca[i][2] = 0.f; ca[i][3] = 0.f; }
    const uint32_t abase = ((g & 1) == 0 ? hE + (7 - g + 2 * c + 1) * 2 : hO + (7 - g + 2 * c) * 2) + wq * 64;
    const uint32_t baddr = cx + ((ln >> 3) & 1) * CV_PLANE + (16 + (ln >> 4) * 8 + (ln & 7)) * 16 - wq * 32;
    mbar_wait(bar_addr(sb, B_RG_FULL + 4), 0);
    TR(7); TS(19); TS(20);
    if (w) conv_mma<1>(ca, abase, baddr); else conv_mma<0>(ca, abase, baddr);
    TR(8); TS(21);
    mbar_wait(bar_addr(sb, B_P1_EMPTY + 2), 1);
    const uint32_t ex = sb + CV_R + w * 16384 + ln * 16;
#pragma unroll
    for (int u = 0; u < 8; u++)
      sts16(ex + (wq * 8 + u) * 512, __float_as_uint(ca[u][0]), __float_as_uint(ca[u][1]), __float_as_uint(ca[u][2]), __float_as_uint(ca[u][3]));
    if (w == 0) { mbar_wait(st_empty, 1); mbar_wait(bar_addr(sb, B_ST_EMPTY + 1), 1); }
    store_blocks<0, 4>(qreg, lb, pk);
    named_sync(1 + w, 128);
    TR(9); TS(22);
    const uint32_t Dd = lds4(cx + CV_D);
    uint32_t z[2][2];
#pragma unroll
    for (int e = 0; e < 2; e++) {
      const uint32_t u = 2 * wq + e, nt = 2 * u + ((e ^ w) & 1);
      float y[4] = {0.f, 0.f, 0.f, 0.f};
#pragma unroll
      for (int v = 0; v < 4; v++) {
        const uint4 t = lds16(ex + (v * 8 + u) * 512);
        y[0] += __uint_as_float(t.x); y[1] += __uint_as_float(t.y); y[2] += __uint_as_float(t.z); y[3] += __uint_as_float(t.w);
      }
      const uint32_t lo = transpose8(pack_bf16(y[0], y[1])), hi = transpose8(pack_bf16(y[2], y[3]));
      const uint32_t ro = (16 + 8 * nt) * 16 + ln * 4;
      z[e][1] = badd(lo, bmul(lds4(cx + CV_PLANE + ro), Dd));
      z[e][0] = badd(hi, bmul(lds4(cx + ro), Dd));
    }
    TS(23);
    fence_async_smem();
    __syncwarp();
    release(bar_addr(sb, B_RG_EMPTY + 3), lane, rank, true);
    release(bar_addr(sb, B_RG_EMPTY + 4), lane, rank, true);
    const Role ro = get_role();
#pragma unroll
    for (int e = 0; e < 2; e++) {
      uint8_t* gz = g_xs + (size_t)(ro.h * 8 + ro.j) * CV_BYTES + (16 + 8 * (4 * wq + 2 * e + ((e ^ w) & 1))) * 16 + ln * 4;
      *reinterpret_cast<uint32_t*>(gz) = z[e][0];
      *reinterpret_cast<uint32_t*>(gz + CV_PLANE) = z[e][1];
    }
    warp_arrive(bar_addr(sb, B_CONV), lane);
#pragma unroll
    for (int i = 0; i < 128; i++) acc[i] = 0.f;
  }
  TS(15);
  TR(10);
  Ring r{0, 1};
  auto take = [&]() { const uint32_t sl = r.slot; mbar_wait(bar_addr(sb, B_RG_FULL + sl), r.phase); r.next(); return sl; };
  constexpr float SC = 0.0625f * 1.4426950408889634f;
#pragma unroll 1
  for (int which = 0; which < 2; which++) {
    if (which == 1) {
      uint32_t xaddr = 0, xs = 0, pw = 0, px = 0;
#pragma unroll 1
      for (int kc = 0; kc < 7; kc++) {
        const uint32_t ws = take();
        if (kc == 0 || (kc & 1)) { xs = take(); xaddr = sb + xs * SLOT + (w ^ 1) * 8192; } else xaddr += 16384;
        TR(11);
        const uint64_t da = desc_k(xaddr), db = desc_mn(sb + ws * SLOT);
        turn_begin();
        wg_fence();
#pragma unroll
        for (int kk = 0; kk < 4; kk++) wgmma_ss_n256_tb(acc, desc_add(da, kk * 32), desc_add(db, kk * 2048), (kc | kk) != 0);
        wg_commit();
        turn_end();
        TR(13);
        wg_wait<1>();
        if (kc > 0) {
          release(bar_addr(sb, B_RG_EMPTY + pw), lane, rank, false);
          if (kc & 1) release(bar_addr(sb, B_RG_EMPTY + px), lane, rank, false);
        }
        pw = ws; px = xs;
        const int cb = kc - CTX_K;
        if (cb >= 1 && cb <= 4) { fence_async_smem(); warp_arrive(bar_addr(sb, B_CTXS + 4 * w + cb - 1), lane); }
        if (cb == 0) store_blocks<0, 1>(qreg, lb, pk);
        else if (cb == 1) store_blocks<16, 1>(qreg + 8192, lb, pk);
        else if (cb == 2) store_blocks<32, 1>(qreg + 16384, lb, pk);
        else if (cb == 3) store_blocks<48, 1>(qreg + 24576, lb, pk);
        TR(15);
      }
      mbar_wait(st_empty, 0);
      wg_wait<0>();
      reg_fence(acc);
      TS(61); TR(16);
      release(bar_addr(sb, B_RG_EMPTY + pw), lane, rank, false);
      release(bar_addr(sb, B_RG_EMPTY + px), lane, rank, false);
#pragma unroll
      for (int i = 0; i < 64; i++) pk[i] = pack_bf16(acc[2 * i], acc[2 * i + 1]);
      store_blocks<0, 4>(qreg, lb, pk);
      fence_async_smem();
      TS(9); TR(19);
      qt = 15 - qt;
    }
    float s[32];
#pragma unroll
    for (int i = 0; i < 32; i++) s[i] = 0.f;
    uint32_t pa[16];
    float m0 = -INFINITY, m1 = -INFINITY, l0 = 0.f, l1 = 0.f;
    const uint64_t dq = desc_k(qreg);
    uint64_t dk = 0, dqq = 0, dv = 0;
    auto prep_qk = [&](uint32_t kaddr) { dk = desc_k(kaddr); dqq = dq + (kaddr >> 31); asm volatile("" : "+l"(dk), "+l"(dqq)); };
    auto prep_pv = [&](uint32_t vaddr) { dv = desc_mn(vaddr); asm volatile("" : "+l"(dv)); };
    auto issue_qk = [&]() {
#pragma unroll
      for (int kk = 0; kk < 16; kk++)
        wgmma_ss_n64(s, desc_add(dqq, (kk >> 2) * 8192 + (kk & 3) * 32), desc_add(dk, (kk >> 2) * 8192 + (kk & 3) * 32), kk != 0);
    };
    auto issue_pv = [&](int accumulate) {
#pragma unroll
      for (int kk = 0; kk < 4; kk++)
        wgmma_rs_n256_tb(acc, pa[4 * kk], pa[4 * kk + 1], pa[4 * kk + 2], pa[4 * kk + 3], desc_add(dv, kk * 2048), accumulate | kk);
    };
    auto mask_diag = [&]() {
      const int d = (int)((lb >> 11) << 4) + (lane >> 2) - 2 * (lane & 3);
#pragma unroll
      for (int jj = 0; jj < 8; jj++) {
        if (8 * jj > d)     s[4 * jj]     = -INFINITY;
        if (8 * jj + 1 > d) s[4 * jj + 1] = -INFINITY;
        if (8 * jj - 8 > d) s[4 * jj + 2] = -INFINITY;
        if (8 * jj - 7 > d) s[4 * jj + 3] = -INFINITY;
      }
    };
    float a0, a1;
    auto softmax = [&]() -> bool {
      float x0 = fmaxf(s[0], s[1]), x1 = fmaxf(s[2], s[3]);
#pragma unroll
      for (int jj = 1; jj < 8; jj++) {
        x0 = fmaxf(x0, fmaxf(s[4 * jj], s[4 * jj + 1]));
        x1 = fmaxf(x1, fmaxf(s[4 * jj + 2], s[4 * jj + 3]));
      }
      x0 = fmaxf(x0, __shfl_xor_sync(0xffffffffu, x0, 1));
      x1 = fmaxf(x1, __shfl_xor_sync(0xffffffffu, x1, 1));
      x0 = fmaxf(x0, __shfl_xor_sync(0xffffffffu, x0, 2));
      x1 = fmaxf(x1, __shfl_xor_sync(0xffffffffu, x1, 2));
      const bool grow = __any_sync(0xffffffffu, fmaxf(x0 - m0, x1 - m1) * SC > 8.f);
      if (grow) {
        x0 = fmaxf(x0, m0); x1 = fmaxf(x1, m1);
        a0 = ex2((m0 - x0) * SC); a1 = ex2((m1 - x1) * SC);
        m0 = x0; m1 = x1;
        l0 *= a0; l1 *= a1;
      }
      const float b0 = -m0 * SC, b1 = -m1 * SC;
      float t0 = 0.f, t1 = 0.f, t2 = 0.f, t3 = 0.f;
#pragma unroll
      for (int jj = 0; jj < 8; jj++) {
        s[4 * jj]     = ex2(fmaf(s[4 * jj], SC, b0));
        s[4 * jj + 1] = ex2(fmaf(s[4 * jj + 1], SC, b0));
        s[4 * jj + 2] = ex2(fmaf(s[4 * jj + 2], SC, b1));
        s[4 * jj + 3] = ex2(fmaf(s[4 * jj + 3], SC, b1));
        t0 += s[4 * jj]; t1 += s[4 * jj + 1]; t2 += s[4 * jj + 2]; t3 += s[4 * jj + 3];
      }
      l0 += t0 + t1; l1 += t2 + t3;
      return grow;
    };
    auto softmax_fast = [&]() -> bool {
      const float b0 = -m0 * SC, b1 = -m1 * SC;
      float t0 = 0.f, t1 = 0.f, t2 = 0.f, t3 = 0.f;
#pragma unroll
      for (int jj = 0; jj < 8; jj++) {
        s[4 * jj]     = ex2(fmaf(s[4 * jj], SC, b0));
        s[4 * jj + 1] = ex2(fmaf(s[4 * jj + 1], SC, b0));
        s[4 * jj + 2] = ex2(fmaf(s[4 * jj + 2], SC, b1));
        s[4 * jj + 3] = ex2(fmaf(s[4 * jj + 3], SC, b1));
        t0 += s[4 * jj]; t1 += s[4 * jj + 1]; t2 += s[4 * jj + 2]; t3 += s[4 * jj + 3];
      }
      t0 += t1; t2 += t3;
      uint32_t redo;
      asm volatile("{\n.reg .pred p, q;\nsetp.le.f32 p, %1, 0f47800000;\nbarrier.cta.red.or.aligned.pred q, %2, 128, !p;\nselp.u32 %0, 1, 0, q;\n}"
                   : "=r"(redo) : "f"(fmaxf(t0, t2) + (t0 - t0) + (t2 - t2)), "r"(RED_BAR + w) : "memory");
      if (!redo) { l0 += t0; l1 += t2; }
      return redo;
    };
    auto rescale = [&]() {
#pragma unroll
      for (int i = 0; i < 32; i++) { acc[4 * i] *= a0; acc[4 * i + 1] *= a0; acc[4 * i + 2] *= a1; acc[4 * i + 3] *= a1; }
    };
    auto to_p = [&]() {
#pragma unroll
      for (int i = 0; i < 16; i++) pa[i] = pack_bf16(s[2 * i], s[2 * i + 1]);
    };

    const bool up = w == which;
    const int n = 2 * qt + 2, nw = n - up, npriv = num_private(qt);
    int fd = which ? 0 : 2 * n - 1;
    const int dir = which ? 1 : -1;
    auto skip = [&]() { r.next(); fd += dir; };
    auto give = [&](uint32_t sl, int d) {
      if (lane < 2) mbar_arrive_remote_n(bar_addr(sb, B_RG_EMPTY + sl), d < npriv ? rank : rank ^ lane, (d & ~2) == 0 ? 2 : 1);
    };
    if (which && up) skip();
    uint32_t ks = take();
    TS(62 + which);
    TR(20);
    prep_qk(sb + ks * SLOT);
    turn_begin();
    wg_fence();
    issue_qk();
    wg_commit();
    turn_end();
    TR(21);
    wg_wait<0>();
    TR(22);
    reg_fence(s);
    give(ks, fd);
    fd += dir;
    if (which && up) skip();
    if (which && nw == 1 && lane == 0) mbar_arrive(bar_addr(sb, B_QFREE + w));
    if (which || nw == 1) mask_diag();
    softmax();
    to_p();
#pragma unroll 1
    for (int jj = 1; jj < nw; jj++) {
      ks = take();
      const uint32_t vs = take();
      TR(30);
      prep_qk(sb + ks * SLOT);
      prep_pv(sb + vs * SLOT);
      turn_begin();
      wg_fence();
      issue_qk();
      wg_commit();
      issue_pv(jj > 1);
      wg_commit();
      turn_end();
      TR(31);
      wg_wait<1>();
      TR(32);
      reg_fence(s);
      const bool diag = !which && jj == nw - 1;
      if (diag) mask_diag();
      bool grow = false;
      if (softmax_fast()) {
#pragma unroll 1
        for (int kb = 0; kb < 4; kb++) {
          const uint64_t da = desc_k(qreg + kb * 8192), db = desc_k(sb + ks * SLOT + kb * 8192);
          wg_fence();
#pragma unroll
          for (int kk = 0; kk < 4; kk++) wgmma_ss_n64(s, desc_add(da, kk * 32), desc_add(db, kk * 32), (kb | kk) != 0);
          wg_commit();
          wg_wait<0>();
          reg_fence(s);
        }
        if (diag) mask_diag();
        grow = softmax();
      }
      give(ks, fd);
      if (which && jj == nw - 1 && lane == 0) mbar_arrive(bar_addr(sb, B_QFREE + w));
      wg_wait<0>();
      reg_fence(acc);
      reg_fence(pa);
      give(vs, fd + dir);
      fd += 2 * dir;
      if (grow) rescale();
      to_p();
    }
    if (!which && up) skip();
    const uint32_t vs = take();
    TR(40);
    prep_pv(sb + vs * SLOT);
    turn_begin();
    wg_fence();
    issue_pv(nw > 1);
    wg_commit();
    turn_end();
    TR(41);
    l0 += __shfl_xor_sync(0xffffffffu, l0, 1); l1 += __shfl_xor_sync(0xffffffffu, l1, 1);
    l0 += __shfl_xor_sync(0xffffffffu, l0, 2); l1 += __shfl_xor_sync(0xffffffffu, l1, 2);
    float i0 = 1.f / l0, i1 = 1.f / l1;
    asm volatile("" : "+f"(i0), "+f"(i1) :: "memory");
    wg_wait<0>();
    TR(42);
    reg_fence(acc);
    reg_fence(pa);
    give(vs, fd);
    if (!which && up) r.next();
    TS(7 + 3 * which);
#pragma unroll
    for (int i = 0; i < 32; i++) {
      pk[2 * i]     = pack_bf16(acc[4 * i] * i0, acc[4 * i + 1] * i0);
      pk[2 * i + 1] = pack_bf16(acc[4 * i + 2] * i1, acc[4 * i + 3] * i1);
    }
    TS(8 + 3 * which); TR(46);
    if (which == 0) TS(31);
  }

  {
    float oa[32], ob[32];
#pragma unroll
    for (int i = 0; i < 32; i++) { oa[i] = 0.f; ob[i] = 0.f; }
    auto stage_o = [&](float (&o)[32], int ch) {
      reg_fence(o);
      uint32_t q[16];
#pragma unroll
      for (int i = 0; i < 16; i++) q[i] = pack_bf16(o[2 * i], o[2 * i + 1]);
      if (ch >= 2) mbar_wait(bar_addr(sb, B_S2_EMPTY + w * 2 + (ch & 1)), ((ch >> 1) - 1) & 1);
      store_blocks<0, 1>(qreg + (ch & 1) * 8192, lb, q);
    };
    auto hand_over = [&](int ch) {
      fence_async_smem();
      warp_arrive(bar_addr(sb, B_S2_FULL + w * 2 + (ch & 1)), lane);
    };
    uint32_t pk2[64];
#pragma unroll
    for (int i = 0; i < 64; i++) pk2[i] = 0;
    uint32_t p2 = 0;
    auto chunk = [&](int ch, float (&o)[32], float (&oprev)[32]) {
      const uint32_t s1 = take();
      TR(50);
      const uint64_t d1 = desc_mn(sb + s1 * SLOT);
      turn_begin();
      wg_fence();
#pragma unroll
      for (int kk = 0; kk < 16; kk++) {
        wgmma_rs_n64_tb(o, pk[4 * kk], pk[4 * kk + 1], pk[4 * kk + 2], pk[4 * kk + 3], desc_add(d1, kk * 2048), kk != 0);
        if (kk == ARRIVE_KK) turn_end();
      }
      wg_commit();
      TR(51);
      if (ch >= 1) {
        wg_wait<1>();
        if (ch <= 4) release(bar_addr(sb, B_RG_EMPTY + p2), lane, rank, true);
        stage_o(oprev, ch - 1);
      } else {
        mbar_wait(bar_addr(sb, B_CTXF + w), 0);
#pragma unroll
        for (int kk = 0; kk < 16; kk++) {
          uint32_t f[4];
          ldsm4(f, qreg + (kk >> 2) * 8192 + (lb ^ ((kk & 3) << 5)));
          pk2[4 * kk] = f[0]; pk2[4 * kk + 1] = f[1]; pk2[4 * kk + 2] = f[2]; pk2[4 * kk + 3] = f[3];
        }
      }
      const uint32_t s2 = take();
      TR(53);
      const uint64_t d2 = desc_mn(sb + s2 * SLOT);
      turn_begin();
      wg_fence();
#pragma unroll
      for (int kk = 0; kk < 16; kk++) {
        wgmma_rs_n64_tb(o, pk2[4 * kk], pk2[4 * kk + 1], pk2[4 * kk + 2], pk2[4 * kk + 3], desc_add(d2, kk * 2048), 1);
        if (kk == ARRIVE_KK && (ch < 6 || w == 1)) turn_end();
      }
      wg_commit();
      TR(54);
      if (ch >= 1) hand_over(ch - 1);
      wg_wait<1>();
      TR(55);
      if (ch <= 4) release(bar_addr(sb, B_RG_EMPTY + s1), lane, rank, true);
      p2 = s2;
    };
#pragma unroll 1
    for (int ch = 0; ch < 6; ch += 2) { chunk(ch, oa, ob); chunk(ch + 1, ob, oa); }
    chunk(6, oa, ob);
    wg_wait<0>();
    TR(58);
    reg_fence(pk);
    reg_fence(pk2);
    stage_o(oa, 6);
    hand_over(6);
  }
  TS(12); TR(59);
  if ((threadIdx.x & 127) == 0) GT(54 + w);

  TS(16); TS(18); TS(17);
  TR(99); TR_END();
  TS(13); TSG(14);
}

#define CONV_STAGGER_NS 1200
namespace ssm {
constexpr int GROUPS = D_SPARE / 8 / NCONV;
constexpr uint32_t ZROWS = 16;
constexpr uint32_t PLANE = 2368;
constexpr uint32_t CHAN = 2 * PLANE + 16;
constexpr uint32_t XBUF = 8 * CHAN;
constexpr uint32_t OFF_X = 0;
constexpr uint32_t HCOPY = 4160;
constexpr uint32_t OFF_H = 2 * XBUF;
constexpr uint32_t HWARP = 3 * HCOPY;
constexpr uint32_t IO_K = 128, IO_V = IO_K + 4096, IO_Q = IO_V + 4096, IOBUF = IO_Q + 4096;
constexpr uint32_t OFF_IO = (OFF_H + 8 * HWARP + 127) / 128 * 128;
constexpr uint32_t END = OFF_IO + 4 * IOBUF;
static_assert(IOBUF % 128 == 0 && OFF_H % 16 == 0, "TMA destination alignment");
static_assert(END <= BARS, "smem");
enum : uint32_t { B_XREADY = 0, B_ZDONE = 2, B_KV = 4, B_Q = 8, B_HRAW = 12, B_QLAST = 20 };
constexpr int CW_BAR = 4;

__device__ __forceinline__ uint32_t x_lane(int lane) { return (lane & 7) * CHAN + (((lane >> 3) & 1) ? 0 : PLANE) + (ZROWS + (lane >> 4)) * 16; }
__device__ __forceinline__ uint32_t t_lane(int lane) { return (uint32_t)(8 * (lane >> 3) + 7 - (lane & 7)) * 16; }
struct Taps { uint32_t s[4]; };
__device__ __forceinline__ Taps load_taps(const Params& p, int d0, int c) {
  const uint2 s0 = __ldg(reinterpret_cast<const uint2*>(p.a_shift + (d0 + 2 * c) * 4)), s1 = __ldg(reinterpret_cast<const uint2*>(p.a_shift + (d0 + 2 * c + 1) * 4));
  return Taps{{__byte_perm(s0.x, s1.x, 0x5410), __byte_perm(s0.x, s1.x, 0x7632), __byte_perm(s0.y, s1.y, 0x5410), __byte_perm(s0.y, s1.y, 0x7632)}};
}
__device__ __forceinline__ uint32_t short_conv(const Taps& t, uint32_t k0, uint32_t k1, uint32_t k2, uint32_t k3, uint32_t v) {
  uint32_t ks = bmul(k0, t.s[3]);
  ks = badd(ks, bmul(k1, t.s[2]));
  ks = badd(ks, bmul(k2, t.s[1]));
  ks = badd(ks, bmul(k3, t.s[0]));
  return bmul(ks, v);
}
__device__ __forceinline__ void gate_chunk(uint32_t xa, uint32_t qa) {
#pragma unroll 4
  for (int i = 0; i < 8; i++) {
    uint32_t zz[4], qq[4];
    ldsm4t(zz, xa + i * 32);
    ldsm4(qq, qa + i * 512);
    stsm4(qa + i * 512, bmul(qq[0], zz[0]), bmul(qq[1], zz[1]), bmul(qq[2], zz[2]), bmul(qq[3], zz[3]));
  }
}

__device__ __forceinline__ void io_warp(const Params& p, uint32_t sb, int cidx, int wq) {
  const int lane = threadIdx.x & 31;
  const uint32_t io = sb + OFF_IO + wq * IOBUF, bkv = bar_addr(sb, B_KV + wq), bq = bar_addr(sb, B_Q + wq);
  auto load_kv = [&](int e) {
    __syncwarp();
    if (lane != 0) return;
    const int d0 = (cidx * GROUPS + (e >> 1)) * 8, row = (2 * wq + (e & 1)) * 256;
    if (e < 2 * GROUPS) {
      mbar_expect_tx(bkv, IO_Q);
      tma_ld2(io, &p.ak8, bkv, d0, row - 8);
      tma_ld2(io + IO_K, &p.ak, bkv, d0, row);
      tma_ld2(io + IO_V, &p.av, bkv, d0, row);
    } else {
      const uint32_t bar = bar_addr(sb, B_QLAST + 2 * wq + 1);
      mbar_expect_tx(bar, 4096);
      tma_ld2(io + IO_K, &p.aq, bar, d0 - 8, row + 256);
    }
  };
  auto load_q = [&](int e) {
    __syncwarp();
    if (lane != 0) return;
    const uint32_t bar = e < 2 * GROUPS - 2 ? bq : bar_addr(sb, B_QLAST + 2 * wq);
    mbar_expect_tx(bar, 4096);
    tma_ld2(io + IO_Q, &p.aq, bar, (cidx * GROUPS + (e >> 1)) * 8, (2 * wq + (e & 1)) * 256);
  };
  load_kv(0);
  const uint32_t xl = sb + OFF_X + x_lane(lane) + wq * 512, tl = io + t_lane(lane);
#pragma unroll 1
  for (int grp = -2; grp + 1 < GROUPS; grp++) {
    const bool more = grp + 2 < GROUPS;
    const Taps taps = load_taps(p, (cidx * GROUPS + (more ? grp + 2 : 0)) * 8, lane & 3);
    PCLK(c0);
    if (grp >= 0) mbar_wait(bar_addr(sb, B_ZDONE + (grp & 1)), (grp >> 1) & 1);
    PACC(tp, c0);
    PCLK(c1);
#pragma unroll 1
    for (int i = 0; i < 2; i++) {
      const uint32_t xa = xl + (grp & 1) * XBUF + i * 256;
      if (grp >= 0) {
        mbar_wait(bq, i);
        gate_chunk(xa, tl + IO_Q);
      }
      if (more) {
        mbar_wait(bkv, i);
#pragma unroll 2
        for (int u = 0; u < 8; u++) {
          const uint32_t ka = tl + IO_K + u * 512;
          uint32_t k0[4], k1[4], k2[4], k3[4], vv[4];
          ldsm4(k0, ka - 48); ldsm4(k1, ka - 32); ldsm4(k2, ka - 16); ldsm4(k3, ka); ldsm4(vv, ka + 4096);
          stsm4t(xa + u * 32, short_conv(taps, k0[0], k1[0], k2[0], k3[0], vv[0]), short_conv(taps, k0[1], k1[1], k2[1], k3[1], vv[1]),
                 short_conv(taps, k0[2], k1[2], k2[2], k3[2], vv[2]), short_conv(taps, k0[3], k1[3], k2[3], k3[3], vv[3]));
        }
        load_kv(2 * (grp + 2) + i + 1);
        if (i == 1) warp_arrive(bar_addr(sb, B_XREADY + (grp & 1)), lane);
      }
      if (grp >= 0) {
        fence_async_smem();
        __syncwarp();
        if (lane == 0) {
          tma_st2(&p.ao, io + IO_Q, (cidx * GROUPS + grp) * 8, (2 * wq + i) * 256);
          bulk_commit();
          bulk_wait_read();
        }
      }
      if (2 * grp + i + 1 >= 0) load_q(2 * grp + i + 1);
    }
    PACC(te, c1);
  }
  if (lane == 0) bulk_wait_all();
}

__device__ __forceinline__ void conv_warp(const Params& p, uint32_t sb, int cidx, int ch) {
  const int lane = threadIdx.x & 31, g = lane >> 2, c = lane & 3;
  const uint32_t hE0 = sb + OFF_H + ch * HWARP, hO = hE0 + HCOPY;
  const uint32_t hbar = bar_addr(sb, B_HRAW + ch);
  const int dbase = cidx * GROUPS * 8 + ch;
  auto fetch_h = [&](int grp) {
    if (lane == 0) {
      mbar_expect_tx(hbar, 4096);
      asm volatile("cp.async.bulk.shared::cluster.global.mbarrier::complete_tx::bytes [%0], [%1], %2, [%3];"
                   :: "r"(hE0 + (grp & 1) * 2 * HCOPY + 32), "l"(p.a_ssmk + (size_t)(dbase + 8 * grp) * SEQ), "r"(4096), "r"(hbar) : "memory");
    }
  };
  fetch_h(0);
#pragma unroll 1
  for (int grp = 0; grp < GROUPS; grp++) {
    const uint32_t xc = sb + OFF_X + (grp & 1) * XBUF + ch * CHAN;
    const uint32_t Dd = (uint32_t)__ldg(reinterpret_cast<const unsigned short*>(p.a_D + dbase + 8 * grp)) * 0x10001u;
    PCLK(k0);
    mbar_wait(hbar, grp & 1);
    const uint32_t hE = hE0 + (grp & 1) * 2 * HCOPY;
    if (grp + 1 < GROUPS) fetch_h(grp + 1);
#pragma unroll
    for (int i = 0; i < 8; i++) {
      const uint32_t o = 32 + (i * 32 + lane) * 16;
      const uint4 w = lds16(hE + o);
      const uint32_t nx = lds4(hE + o + 16);
      sts16(hO + o, __byte_perm(w.x, w.y, 0x5432), __byte_perm(w.y, w.z, 0x5432), __byte_perm(w.z, w.w, 0x5432), __byte_perm(w.w, nx, 0x5432));
      if (o == 32) asm volatile("st.shared.u32 [%0], %1;" :: "r"(hO + 28), "r"(w.x << 16) : "memory");
    }
    __syncwarp();
    const uint32_t abase = (g & 1) == 0 ? hE + (7 - g + 2 * c + 1) * 2 : hO + (7 - g + 2 * c) * 2;
    mbar_wait(bar_addr(sb, B_XREADY + (grp & 1)), (grp >> 1) & 1);
    if (grp == 0 && ch >= 4) __nanosleep(CONV_STAGGER_NS);
    PACC(tw, k0);
    PCLK(k1);
    float acc[16][4];
#pragma unroll
    for (int i = 0; i < 16; i++) { acc[i][0] = 0.f; acc[i][1] = 0.f; acc[i][2] = 0.f; acc[i][3] = 0.f; }
    const uint32_t baddr = xc + ((lane >> 3) & 1) * PLANE + (ZROWS + (lane >> 4) * 8 + (lane & 7)) * 16;
#pragma unroll 1
    for (int r = 0; r < 8; r++) {
      uint32_t fa[16][4], fb[8][4];
#pragma unroll
      for (int i = 0; i < 8; i++) ldsm4(fb[i], baddr + i * 256 - r * 16);
#pragma unroll
      for (int jj = 0; jj < 16; jj++) {
        const uint32_t ad = abase + jj * 256 + r * 32;
        fa[jj][0] = lds4(ad); fa[jj][1] = lds4(ad + 16); fa[jj][2] = lds4v(ad + 16); fa[jj][3] = lds4(ad + 32);
      }
#pragma unroll
      for (int jj = 0; jj < 16; jj++)
#pragma unroll
        for (int sx = 0; sx < 16 - jj; sx++)
          mma16816(acc[jj + sx], fa[jj], fb[sx >> 1][2 * (sx & 1)], fb[sx >> 1][2 * (sx & 1) + 1]);
    }
    PACC(tm, k1);
    PCLK(k2);
#pragma unroll
    for (int i = 0; i < 8; i++) {
      uint32_t x[4];
      ldsm4t(x, baddr + i * 256);
      stsm4t(baddr + i * 256, badd(pack_bf16(acc[2 * i][2], acc[2 * i][3]), bmul(x[0], Dd)), badd(pack_bf16(acc[2 * i][0], acc[2 * i][1]), bmul(x[1], Dd)),
             badd(pack_bf16(acc[2 * i + 1][2], acc[2 * i + 1][3]), bmul(x[2], Dd)), badd(pack_bf16(acc[2 * i + 1][0], acc[2 * i + 1][1]), bmul(x[3], Dd)));
    }
    if (grp + 1 < GROUPS) warp_arrive(bar_addr(sb, B_ZDONE + (grp & 1)), lane);
    PACC(tr, k2);
  }
  {
    mbar_wait(bar_addr(sb, B_QLAST + ch), 0);
    named_sync(CW_BAR, 256);
    const uint32_t qb = sb + OFF_IO + (ch >> 1) * IOBUF + ((ch & 1) ? IO_K : IO_Q);
    gate_chunk(sb + OFF_X + ((GROUPS - 1) & 1) * XBUF + x_lane(lane) + ch * 256, qb + t_lane(lane));
    fence_async_smem();
    __syncwarp();
    if (lane == 0) { tma_st2(&p.ao, qb, (cidx * GROUPS + GROUPS - 1) * 8, ch * 256); bulk_commit(); bulk_wait_all(); }
  }
}

__device__ __forceinline__ void init(uint32_t sb) {
  for (uint32_t i = threadIdx.x; i < 32 * ZROWS; i += NTHREADS) sts16(sb + OFF_X + (i >> 5) * CHAN + ((i >> 4) & 1) * PLANE + (i & 15) * 16, 0, 0, 0, 0);
  if (threadIdx.x < 96) sts16(sb + OFF_H + (threadIdx.x >> 2) * HCOPY + (threadIdx.x & 1) * 16 + ((threadIdx.x & 2) ? 4128 : 0), 0, 0, 0, 0);
  if (threadIdx.x == 0) {
    for (int i = 0; i < 2; i++) { mbar_init(bar_addr(sb, B_XREADY + i), 4); mbar_init(bar_addr(sb, B_ZDONE + i), 8); }
    for (int i = 0; i < 4; i++) { mbar_init(bar_addr(sb, B_KV + i), 1); mbar_init(bar_addr(sb, B_Q + i), 1); }
    for (int i = 0; i < 8; i++) { mbar_init(bar_addr(sb, B_HRAW + i), 1); mbar_init(bar_addr(sb, B_QLAST + i), 1); }
    fence_async_smem();
  }
}
}

__device__ __forceinline__ void ssm_side_work(const Params& p, uint32_t sb, unsigned epoch) {
  const Role ro = get_role();
  const int h = ro.h, j = ro.j;
  const int lane = threadIdx.x & 31, g = lane >> 2, c = lane & 3;
  const int d0 = D_SPARE + 8 * h;
  uint8_t* xs = g_xs + (size_t)(h * 8 + g) * CV_BYTES + c * 4;
  auto xrow = [&](int beta) { return xs + ((beta & 1) ? 0 : CV_PLANE) + (16 + (beta >> 1)) * 16; };
  {
    const uint4* hp = reinterpret_cast<const uint4*>(p.a_ssmk + (size_t)(d0 + j) * SEQ) + lane;
    uint8_t* he = g_xs + (size_t)(h * 8 + j) * CV_BYTES + CV_HE;
#pragma unroll 2
    for (int i = 0; i < 8; i++) {
      const uint4 wv = __ldg(hp + i * 32);
      const uint32_t nx = i * 32 + lane < 255 ? __ldg(reinterpret_cast<const uint32_t*>(hp + i * 32 + 1)) : 0u;
      const uint32_t o = 32 + (i * 32 + lane) * 16;
      *reinterpret_cast<uint4*>(he + o) = wv;
      *reinterpret_cast<uint4*>(he + CV_HCOPY + o) =
          make_uint4(__byte_perm(wv.x, wv.y, 0x5432), __byte_perm(wv.y, wv.z, 0x5432), __byte_perm(wv.z, wv.w, 0x5432), __byte_perm(wv.w, nx, 0x5432));
      if (o == 32) *reinterpret_cast<uint32_t*>(he + CV_HCOPY + 28) = wv.x << 16;
    }
    if (lane == 0) *reinterpret_cast<uint32_t*>(he + CV_D - CV_HE) = (uint32_t)__ldg(reinterpret_cast<const unsigned short*>(p.a_D + d0 + j)) * 0x10001u;
  }
  {
    const uint2 s0 = __ldg(reinterpret_cast<const uint2*>(p.a_shift + (d0 + 2 * c) * 4)), s1 = __ldg(reinterpret_cast<const uint2*>(p.a_shift + (d0 + 2 * c + 1) * 4));
    const uint32_t sh0 = __byte_perm(s0.x, s1.x, 0x5410), sh1 = __byte_perm(s0.x, s1.x, 0x7632);
    const uint32_t sh2 = __byte_perm(s0.y, s1.y, 0x5410), sh3 = __byte_perm(s0.y, s1.y, 0x7632);
    const uint32_t* kp = reinterpret_cast<const uint32_t*>(p.a_k + (size_t)(256 * j + 7 - g) * DA + d0) + c;
    const uint32_t* vp = reinterpret_cast<const uint32_t*>(p.a_v + (size_t)(256 * j + 7 - g) * DA + d0) + c;
    uint32_t kprev = j > 0 ? __ldg(kp - 8 * (DA / 2)) : 0u;
#pragma unroll 1
    for (int i0 = 0; i0 < 32; i0 += 8) {
      uint32_t kk[8], vv[8];
#pragma unroll
      for (int i = 0; i < 8; i++) { kk[i] = __ldg(kp + (i0 + i) * 8 * (DA / 2)); vv[i] = __ldg(vp + (i0 + i) * 8 * (DA / 2)); }
#pragma unroll
      for (int i = 0; i < 8; i++) {
        const uint32_t k2 = __shfl_sync(0xffffffffu, g < 1 ? kprev : kk[i], (lane + 4) & 31);
        const uint32_t k1 = __shfl_sync(0xffffffffu, g < 2 ? kprev : kk[i], (lane + 8) & 31);
        const uint32_t k0 = __shfl_sync(0xffffffffu, g < 3 ? kprev : kk[i], (lane + 12) & 31);
        uint32_t ks = bmul(k0, sh3);
        ks = badd(ks, bmul(k1, sh2)); ks = badd(ks, bmul(k2, sh1)); ks = badd(ks, bmul(kk[i], sh0));
        *reinterpret_cast<uint32_t*>(xrow(32 * j + i0 + i)) = transpose8(bmul(ks, vv[i]));
        kprev = kk[i];
      }
    }
    __syncwarp();
    if (lane == 0) {
      flag_signal(&g_flags.xs_ready[h].v);
      flag_wait(&g_flags.xs_ready[h].v, 8, epoch);
      fence_async_all();
      mbar_arrive(bar_addr(sb, B_XS));
    }
  }
  if (lane == 0) {
    for (int i = 0; i < 2; i++) {
      flag_wait(&g_flags.kv_ready[2 * h + i].v, 16, epoch);
      fence_async_all();
      mbar_arrive(bar_addr(sb, B_KV + i));
      if (PF_CV && i == 0) bulk_prefetch(g_xs + (size_t)(h * 8 + j) * CV_BYTES, CV_BYTES);
    }
    mbar_wait(bar_addr(sb, B_CONV), 0);
    flag_signal(&g_flags.zs_ready[h].v);
    flag_wait(&g_flags.zs_ready[h].v, 8, epoch);
    asm volatile("red.relaxed.gpu.global.add.u64 [%0], 1;" :: "l"(&g_flags.done) : "memory");
  }
  __syncwarp();
  fence_async_all();
  const uint32_t qb = q_region(sb, 1) + 16384, zb = qb + 4096, bar = bar_addr(sb, B_GATE);
  constexpr uint32_t ZCH = 528;
  mbar_wait_slow(bar_addr(sb, B_GFREE), 0);
  if (lane == 0) { mbar_expect_tx(bar, 8192); tma_ld2(qb, &p.aq, bar, d0, 256 * j); }
  __syncwarp();
  if (lane < 16) bulk_ld(zb + (lane >> 1) * ZCH + (lane & 1) * 256, g_xs + (size_t)(h * 8 + (lane >> 1)) * CV_BYTES + (lane & 1) * CV_PLANE + (16 + 16 * j) * 16, 256, bar);
  mbar_wait(bar, 0);
  const uint32_t za = zb + (lane & 7) * ZCH + ((lane >> 3) & 1 ? 0 : 256) + (lane >> 4) * 16;
  const uint32_t qa = qb + (8 * (lane >> 3) + 7 - (lane & 7)) * 16;
#pragma unroll 2
  for (int i = 0; i < 8; i++) {
    uint32_t zz[4], qq[4];
    ldsm4t(zz, za + i * 32);
    ldsm4(qq, qa + i * 512);
    stsm4(qa + i * 512, bmul(qq[0], zz[0]), bmul(qq[1], zz[1]), bmul(qq[2], zz[2]), bmul(qq[3], zz[3]));
  }
  fence_async_smem();
  __syncwarp();
  if (lane == 0) { tma_st2(&p.ao, qb, d0, 256 * j); bulk_commit(); bulk_wait_all(); }
}

__global__ void __cluster_dims__(2, 1, 1) __launch_bounds__(NTHREADS, 1)
concat_heads__ssm_conv_h3__compressed_kv_cla__prompt_kernel(const __grid_constant__ Params p) {
  extern __shared__ uint8_t smem_raw[];
  const uint32_t sb = (smem_u32(smem_raw) + 1023) & ~1023u;
  const int warp = __shfl_sync(0xffffffffu, threadIdx.x >> 5, 0);
  const int wg = warp >> 2;
  const int cta = blockIdx.x;
  const bool attn = cta < NMAIN;
  if (!attn) ssm::init(sb);
  if (attn && threadIdx.x == 0) {
    for (int i = 0; i < 4; i++) { mbar_init(bar_addr(sb, B_P1_FULL + i), 1); mbar_init(bar_addr(sb, B_P1_EMPTY + i), 16); }
    for (int i = 0; i < NSLOT; i++) {
      mbar_init(bar_addr(sb, B_RG_FULL + i), 1); mbar_init(bar_addr(sb, B_RG_EMPTY + i), 16); mbar_init(bar_addr(sb, B_PFREE + i), 1);
    }
    for (int i = 0; i < 2; i++) { mbar_init(bar_addr(sb, B_ST_FULL + i), 4); mbar_init(bar_addr(sb, B_ST_EMPTY + i), 1); }
    mbar_init(bar_addr(sb, B_XS), 1); mbar_init(bar_addr(sb, B_CONV), 8); mbar_init(bar_addr(sb, B_GATE), 1); mbar_init(bar_addr(sb, B_GFREE), 1);
    mbar_init(bar_addr(sb, B_KV), 1); mbar_init(bar_addr(sb, B_KV + 1), 1);
    for (int i = 0; i < 8; i++) mbar_init(bar_addr(sb, B_CTXS + i), 4);
    for (int i = 0; i < 4; i++) { mbar_arrive(bar_addr(sb, B_RG_FULL + i)); if (i < 3) mbar_arrive_n(bar_addr(sb, B_RG_EMPTY + i), 16); }
    for (int i = 0; i < 4; i++) { mbar_init(bar_addr(sb, B_S2_FULL + i), 4); mbar_init(bar_addr(sb, B_S2_EMPTY + i), 1); }
    for (int i = 0; i < 2; i++) { mbar_init(bar_addr(sb, B_QFREE + i), 4); mbar_init(bar_addr(sb, B_CTXF + i), 1); }
    asm volatile("fence.mbarrier_init.release.cluster;" ::: "memory");
  }
  if (attn && threadIdx.x == 32) {
    prefetch_map(&p.ckv); prefetch_map(&p.wuk); prefetch_map(&p.wuv); prefetch_map(&p.x); prefetch_map(&p.wq);
    prefetch_map(&p.kv); prefetch_map(&p.part); prefetch_map(&p.wo); prefetch_map(&p.ctx);
  }
  __syncwarp();
  asm volatile("barrier.cluster.arrive.release.aligned;" ::: "memory");
  if (attn && threadIdx.x == 0) {
    const Role ro = get_role();
    const int h = ro.h, j = ro.j;
    for (int k = 0; k < EARLY_LD; k++) {
      const uint32_t full = bar_addr(sb, B_P1_FULL + k), dst = sb + k * P1_STAGE;
      mbar_expect_tx(full, P1_STAGE);
      tma_ld2(dst, &p.ckv, full, k * 64, 2 * j * 128);
      load_tile4(dst + 16384, &p.wuk, full, k * 64, h * 4, j & 1, false);
    }
  }
  __syncwarp();
  asm volatile("barrier.cluster.wait.acquire.aligned;" ::: "memory");

  const int lane = threadIdx.x & 31;
  if (wg == 0) {
    if (!attn) {
      asm volatile("setmaxnreg.dec.sync.aligned.u32 72;");
      if (threadIdx.x == 0) GT(0);
      if (p.out != nullptr) ssm::io_warp(p, sb, cta - NMAIN, fresh_warp());
      if (threadIdx.x == 0) GT(14);
      return;
    }
    asm volatile("setmaxnreg.dec.sync.aligned.u32 40;");
    if (warp == 0) {
      if (lane == 0) producer_main(p, sb);
    } else if (warp < 3) {
      storer_main(p, sb);
    } else {
      const unsigned epoch = load_epoch();
      mbar_wait(bar_addr(sb, B_P1_FULL + 3), 0);
      __nanosleep(SIDE_DELAY_NS);
      ssm_side_work(p, sb, epoch);
    }
  } else {
    if (!attn) {
      asm volatile("setmaxnreg.inc.sync.aligned.u32 216;");
      if (threadIdx.x == 128) { GT(12); PT(10); }
      if (p.out != nullptr) ssm::conv_warp(p, sb, cta - NMAIN, fresh_warp() - 4);
      if (threadIdx.x == 128) { PT(9); GT(13); }
      return;
    }
    asm volatile("setmaxnreg.inc.sync.aligned.u32 232;");
    if (p.out != nullptr) {
      consumer_main(p, sb);
    }
  }
}

typedef CUresult (*EncodeTiledFn)(CUtensorMap*, CUtensorMapDataType, cuuint32_t, void*, const cuuint64_t*, const cuuint64_t*,
                                  const cuuint32_t*, const cuuint32_t*, CUtensorMapInterleave, CUtensorMapSwizzle,
                                  CUtensorMapL2promotion, CUtensorMapFloatOOBfill);

void make_map(EncodeTiledFn enc, CUtensorMap* m, const void* ptr, int rank, const uint64_t* dims, const uint64_t* strides, const uint32_t* box) {
  cuuint64_t d[3], s[2]; cuuint32_t b[3], e[3] = {1, 1, 1};
  for (int i = 0; i < rank; i++) { d[i] = dims[i]; b[i] = box[i]; if (i) s[i - 1] = strides[i - 1]; }
  enc(m, CU_TENSOR_MAP_DATA_TYPE_BFLOAT16, rank, const_cast<void*>(ptr), d, s, b, e, CU_TENSOR_MAP_INTERLEAVE_NONE,
      CU_TENSOR_MAP_SWIZZLE_128B, CU_TENSOR_MAP_L2_PROMOTION_L2_256B, CU_TENSOR_MAP_FLOAT_OOB_FILL_NONE);
}
void map2(EncodeTiledFn enc, CUtensorMap* m, const void* ptr, uint64_t cols, uint64_t rows, uint32_t bc, uint32_t br) {
  const uint64_t dims[2] = {cols, rows}, st[1] = {cols * 2}; const uint32_t box[2] = {bc, br};
  make_map(enc, m, ptr, 2, dims, st, box);
}
void map2_plain(EncodeTiledFn enc, CUtensorMap* m, const void* ptr, uint64_t cols, uint64_t rows, uint32_t bc, uint32_t br) {
  cuuint64_t d[2] = {cols, rows}, st[1] = {cols * 2}; cuuint32_t b[2] = {bc, br}, e[2] = {1, 1};
  enc(m, CU_TENSOR_MAP_DATA_TYPE_BFLOAT16, 2, const_cast<void*>(ptr), d, st, b, e, CU_TENSOR_MAP_INTERLEAVE_NONE,
      CU_TENSOR_MAP_SWIZZLE_NONE, CU_TENSOR_MAP_L2_PROMOTION_L2_128B, CU_TENSOR_MAP_FLOAT_OOB_FILL_NONE);
}
void map3(EncodeTiledFn enc, CUtensorMap* m, const void* ptr, uint64_t rows, uint32_t nblk) {
  const uint64_t dims[3] = {64, rows, 64}, st[2] = {8192, 128}; const uint32_t box[3] = {64, 64, nblk};
  make_map(enc, m, ptr, 3, dims, st, box);
}

}

extern "C" void kernel_launch(void* const* d_in, const int* in_sizes, int n_in, void* d_out, int out_size) {
  (void)in_sizes; (void)n_in; (void)out_size;
  static EncodeTiledFn enc = nullptr;
  static void *kv_ptr = nullptr, *acc_ptr = nullptr;
  if (!enc) {
    void* fn = nullptr; cudaDriverEntryPointQueryResult qr;
    cudaGetDriverEntryPoint("cuTensorMapEncodeTiled", &fn, cudaEnableDefault, &qr);
    enc = (EncodeTiledFn)fn;
    cudaGetSymbolAddress(&kv_ptr, g_kv);
    cudaGetSymbolAddress(&acc_ptr, g_ctx);
    cudaFuncSetAttribute(concat_heads__ssm_conv_h3__compressed_kv_cla__prompt_kernel, cudaFuncAttributeMaxDynamicSharedMemorySize, SMEM_BYTES);
  }
  Params p;
  p.a_q = (const bf16*)d_in[0]; p.a_k = (const bf16*)d_in[1]; p.a_v = (const bf16*)d_in[2];
  map2_plain(enc, &p.aq, d_in[0], DA, SEQ, 8, 256);
  map2_plain(enc, &p.ak, d_in[1], DA, SEQ, 8, 256);
  map2_plain(enc, &p.ak8, d_in[1], DA, SEQ, 8, 8);
  map2_plain(enc, &p.av, d_in[2], DA, SEQ, 8, 256);
  map2_plain(enc, &p.ao, d_out, OUTW, SEQ, 8, 256);
  p.a_shift = (const bf16*)d_in[3]; p.a_ssmk = (const bf16*)d_in[4]; p.a_D = (const bf16*)d_in[5];
  p.out = (bf16*)d_out; p.b_x = (const bf16*)d_in[6]; p.b_wo = (const bf16*)d_in[11];
  map2(enc, &p.x, d_in[6], DM, SEQ, 64, 128);
  map2(enc, &p.ckv, d_in[7], DC, SEQ, 64, 128);
  map3(enc, &p.wq, d_in[8], DM, 2);
  map3(enc, &p.wuk, d_in[9], DC, 2);
  map3(enc, &p.wuv, d_in[10], DC, 2);
  map2(enc, &p.wo, d_in[11], DM, NH * HD, 64, 128);
  {
    const uint64_t dims[3] = {64, 2 * NH * SEQ, 4}, st[2] = {HD * 2, 128}; const uint32_t box[3] = {64, 64, 2};
    make_map(enc, &p.kv, kv_ptr, 3, dims, st, box);
  }
  map2(enc, &p.part, d_out, OUTW, SEQ, 64, 64);
  {
    const uint64_t dims[3] = {64, NMAIN * 128, 4}, st[2] = {HD * 2, 128}; const uint32_t box[3] = {64, 64, 4};
    make_map(enc, &p.ctx, acc_ptr, 3, dims, st, box);
    const uint32_t box1[3] = {64, 64, 1};
    make_map(enc, &p.ctxs, acc_ptr, 3, dims, st, box1);
  }
  concat_heads__ssm_conv_h3__compressed_kv_cla__prompt_kernel<<<NCTA, NTHREADS, SMEM_BYTES>>>(p);
}
```

```cpp
#include <cuda_runtime.h>
#include <cuda_bf16.h>
#include <cuda.h>
#include <stdint.h>

namespace {

typedef __nv_bfloat16 bf16;

constexpr int SEQ  = 2048;
constexpr int DA   = 448;
constexpr int NH   = 16;
constexpr int HD   = 256;
constexpr int DM   = 448;
constexpr int DC   = 1024;
constexpr int OUTW = DA + DM;
constexpr int NMAIN = 128;
constexpr int NCONV = 4;
constexpr int NCTA  = NMAIN + NCONV;
constexpr int NTHREADS = 384;
constexpr int D_SPARE = 320;

__device__ __align__(1024) bf16 g_kv[2ull * SEQ * NH * HD];
__device__ __align__(1024) bf16 g_ctx[(size_t)NMAIN * 128 * HD];
constexpr uint32_t CV_HE = 272 * 16, CV_HCOPY = 4160, CV_D = CV_HE + 4144, CV_BYTES = CV_HE + 2 * CV_HCOPY;
__device__ __align__(128) uint8_t g_xs[NMAIN * CV_BYTES];
struct alignas(128) Flag { unsigned v; unsigned pad[31]; };
struct Flags {
  Flag kv_ready[2 * NH];
  Flag ctx_ready[NMAIN * 2];
  Flag out_ready[16 * 2];
  Flag xs_ready[NH];
  Flag zs_ready[NH];
  alignas(128) unsigned long long done;
};
__device__ Flags g_flags;
#define TS(i)
#define TSG(i)
#define GT(i)
#define PT(i)
#define WHICH_TS 0
#define PCLK(var)
#define PACC(acc, t0)
#define PDECL
#define PDUMP()

#define TR_DECL
#define TR(tag)
#define TR_END()

struct alignas(64) Params {
  CUtensorMap ckv;
  CUtensorMap wuk;
  CUtensorMap wuv;
  CUtensorMap x;
  CUtensorMap wq;
  CUtensorMap kv;
  CUtensorMap part;
  CUtensorMap ctx;
  CUtensorMap ctxs;
  CUtensorMap wo;
  CUtensorMap ak, ak8, av, aq, ao;
  const bf16 *a_q, *a_k, *a_v, *a_shift, *a_ssmk, *a_D, *b_x, *b_wo;
  bf16* out;
};

constexpr uint32_t P1_STAGE = 49152;
constexpr uint32_t P1_STG   = 196608;
constexpr uint32_t SLOT     = 32768;
constexpr int      NSLOT    = 5;
constexpr uint32_t QREG     = 163840;
constexpr uint32_t CV_X = 4 * SLOT + 16384, CV_R = 3 * SLOT;
static_assert(CV_BYTES <= 16384 && CV_BYTES % 128 == 0, "SSM operands");
constexpr uint32_t BARS     = 229376;
constexpr uint32_t SMEM_BYTES = BARS + 512 + 1024;
enum : uint32_t {
  B_P1_FULL = 0, B_P1_EMPTY = 4, B_RG_FULL = 8, B_RG_EMPTY = 13, B_ST_FULL = 18, B_ST_EMPTY = 20,
  B_XS = 22, B_PFREE = 23, B_S2_FULL = 28, B_S2_EMPTY = 32, B_QFREE = 36, B_CTXF = 38, B_KV = 40, B_CONV = 42, B_GATE = 43, B_CTXS = 44, B_GFREE = 52, B_COUNT = 53
};

__device__ __forceinline__ uint32_t smem_u32(const void* p) { return (uint32_t)__cvta_generic_to_shared(p); }
__device__ __forceinline__ void mbar_init(uint32_t bar, uint32_t cnt) {
  asm volatile("mbarrier.init.shared::cta.b64 [%0], %1;" :: "r"(bar), "r"(cnt) : "memory");
}
__device__ __forceinline__ void mbar_expect_tx(uint32_t bar, uint32_t bytes) {
  asm volatile("mbarrier.arrive.expect_tx.shared::cta.b64 _, [%0], %1;" :: "r"(bar), "r"(bytes) : "memory");
}
__device__ __forceinline__ void mbar_arrive(uint32_t bar) {
  asm volatile("mbarrier.arrive.shared::cta.b64 _, [%0];" :: "r"(bar) : "memory");
}
__device__ __forceinline__ void mbar_arrive_n(uint32_t bar, uint32_t n) {
  asm volatile("mbarrier.arrive.shared::cta.b64 _, [%0], %1;" :: "r"(bar), "r"(n) : "memory");
}
__device__ __forceinline__ void mbar_arrive_remote(uint32_t bar, uint32_t cta) {
  asm volatile("{\n.reg .b32 ra;\nmapa.shared::cluster.u32 ra, %0, %1;\n"
               "mbarrier.arrive.shared::cluster.b64 _, [ra];\n}" :: "r"(bar), "r"(cta) : "memory");
}
__device__ __forceinline__ void mbar_arrive_remote_n(uint32_t bar, uint32_t cta, uint32_t n) {
  asm volatile("{\n.reg .b32 ra;\nmapa.shared::cluster.u32 ra, %0, %1;\n"
               "mbarrier.arrive.shared::cluster.b64 _, [ra], %2;\n}" :: "r"(bar), "r"(cta), "r"(n) : "memory");
}
__device__ __forceinline__ bool mbar_try(uint32_t bar, uint32_t parity) {
  uint32_t ok;
  asm volatile("{\n.reg .pred p;\nmbarrier.try_wait.parity.shared::cta.b64 p, [%1], %2;\nselp.u32 %0, 1, 0, p;\n}"
               : "=r"(ok) : "r"(bar), "r"(parity) : "memory");
  return ok;
}
#define NAP_NS 100
constexpr uint32_t SPIN_LIMIT = 1u << 24;
__device__ __forceinline__ void mbar_wait(uint32_t bar, uint32_t parity) {
  if (mbar_try(bar, parity)) return;
  uint32_t n = 0;
  while (!mbar_try(bar, parity)) { if (++n > SPIN_LIMIT) __trap(); }
}
__device__ __forceinline__ void mbar_wait_nap(uint32_t bar, uint32_t parity) {
  uint32_t n = 0;
  while (!mbar_try(bar, parity)) { if (++n > (SPIN_LIMIT >> 2)) __trap(); __nanosleep(NAP_NS); }
}
__device__ __forceinline__ void mbar_wait_slow(uint32_t bar, uint32_t parity) {
  uint32_t n = 0;
  while (!mbar_try(bar, parity)) { if (++n > (SPIN_LIMIT >> 4)) __trap(); __nanosleep(500); }
}
__device__ __forceinline__ unsigned load_epoch() {
  unsigned long long e; asm volatile("ld.relaxed.gpu.global.u64 %0, [%1];" : "=l"(e) : "l"(&g_flags.done) : "memory"); return (unsigned)(e / NMAIN);
}
__device__ __forceinline__ void flag_wait(const unsigned* f, unsigned count, unsigned epoch) {
  const unsigned target = (epoch + 1) * count;
  uint32_t n = 0;
  while (true) {
    unsigned v;
    asm volatile("ld.acquire.gpu.global.u32 %0, [%1];" : "=r"(v) : "l"(f) : "memory");
    if ((int)(v - target) >= 0) break;
    if (++n > SPIN_LIMIT) __trap();
    __nanosleep(20);
  }
}
__device__ __forceinline__ void flag_wait_fast(const unsigned* f, unsigned count, unsigned epoch) {
  const unsigned target = (epoch + 1) * count;
  uint32_t n = 0;
  while (true) {
    unsigned v;
    asm volatile("ld.acquire.gpu.global.u32 %0, [%1];" : "=r"(v) : "l"(f) : "memory");
    if ((int)(v - target) >= 0) break;
    if (++n > SPIN_LIMIT) __trap();
  }
}
__device__ __forceinline__ void fence_async_all() { asm volatile("fence.proxy.async;" ::: "memory"); }
__device__ __forceinline__ void flag_signal(unsigned* f) {
  asm volatile("fence.acq_rel.gpu;" ::: "memory");
  asm volatile("red.relaxed.gpu.global.add.u32 [%0], 1;" :: "l"(f) : "memory");
}
__device__ __forceinline__ void flag_signal_after_bulk(unsigned* f) {
  asm volatile("red.relaxed.gpu.global.add.u32 [%0], 1;" :: "l"(f) : "memory");
}
__device__ __forceinline__ void fence_async_smem() { asm volatile("fence.proxy.async.shared::cta;" ::: "memory"); }
__device__ __forceinline__ void tma_ld2(uint32_t dst, const CUtensorMap* m, uint32_t bar, int c0, int c1) {
  asm volatile("cp.async.bulk.tensor.2d.shared::cluster.global.mbarrier::complete_tx::bytes [%0], [%1, {%3, %4}], [%2];"
               :: "r"(dst), "l"(m), "r"(bar), "r"(c0), "r"(c1) : "memory");
}
__device__ __forceinline__ void tma_ld3(uint32_t dst, const CUtensorMap* m, uint32_t bar, int c0, int c1, int c2) {
  asm volatile("cp.async.bulk.tensor.3d.shared::cluster.global.mbarrier::complete_tx::bytes [%0], [%1, {%3, %4, %5}], [%2];"
               :: "r"(dst), "l"(m), "r"(bar), "r"(c0), "r"(c1), "r"(c2) : "memory");
}
__device__ __forceinline__ void tma_ld3_mc(uint32_t dst, const CUtensorMap* m, uint32_t bar, int c0, int c1, int c2) {
  asm volatile("cp.async.bulk.tensor.3d.shared::cluster.global.mbarrier::complete_tx::bytes.multicast::cluster [%0], [%1, {%3, %4, %5}], [%2], %6;"
               :: "r"(dst), "l"(m), "r"(bar), "r"(c0), "r"(c1), "r"(c2), "h"((uint16_t)3) : "memory");
}
__device__ __forceinline__ void bulk_ld(uint32_t dst, const void* src, uint32_t bytes, uint32_t bar) {
  asm volatile("cp.async.bulk.shared::cluster.global.mbarrier::complete_tx::bytes [%0], [%1], %2, [%3];"
               :: "r"(dst), "l"(src), "r"(bytes), "r"(bar) : "memory");
}
__device__ __forceinline__ void tma_st3(const CUtensorMap* m, uint32_t src, int c0, int c1, int c2) {
  asm volatile("cp.async.bulk.tensor.3d.global.shared::cta.bulk_group [%0, {%2, %3, %4}], [%1];"
               :: "l"(m), "r"(src), "r"(c0), "r"(c1), "r"(c2) : "memory");
}
__device__ __forceinline__ void tma_ld2_mc(uint32_t dst, const CUtensorMap* m, uint32_t bar, int c0, int c1) {
  asm volatile("cp.async.bulk.tensor.2d.shared::cluster.global.mbarrier::complete_tx::bytes.multicast::cluster [%0], [%1, {%3, %4}], [%2], %5;"
               :: "r"(dst), "l"(m), "r"(bar), "r"(c0), "r"(c1), "h"((uint16_t)3) : "memory");
}
__device__ __forceinline__ void tma_st2(const CUtensorMap* m, uint32_t src, int c0, int c1) {
  asm volatile("cp.async.bulk.tensor.2d.global.shared::cta.bulk_group [%0, {%2, %3}], [%1];"
               :: "l"(m), "r"(src), "r"(c0), "r"(c1) : "memory");
}
__device__ __forceinline__ void tma_red2(const CUtensorMap* m, uint32_t src, int c0, int c1) {
  asm volatile("cp.reduce.async.bulk.tensor.2d.global.shared::cta.add.tile.bulk_group [%0, {%2, %3}], [%1];"
               :: "l"(m), "r"(src), "r"(c0), "r"(c1) : "memory");
}
__device__ __forceinline__ void tma_pf3(const CUtensorMap* m, int c0, int c1, int c2) {
  asm volatile("cp.async.bulk.prefetch.tensor.3d.L2.global.tile [%0, {%1, %2, %3}];" :: "l"(m), "r"(c0), "r"(c1), "r"(c2) : "memory");
}
__device__ __forceinline__ void bulk_prefetch(const void* src, uint32_t bytes) {
  asm volatile("cp.async.bulk.prefetch.L2.global [%0], %1;" :: "l"(src), "r"(bytes) : "memory");
}
__device__ __forceinline__ void bulk_commit() { asm volatile("cp.async.bulk.commit_group;" ::: "memory"); }
__device__ __forceinline__ void bulk_wait_read() { asm volatile("cp.async.bulk.wait_group.read 0;" ::: "memory"); }
__device__ __forceinline__ void bulk_wait_all() { asm volatile("cp.async.bulk.wait_group 0;" ::: "memory"); }
__device__ __forceinline__ void prefetch_map(const CUtensorMap* m) { asm volatile("prefetch.tensormap [%0];" :: "l"(m) : "memory"); }
__device__ __forceinline__ void wg_fence() { asm volatile("wgmma.fence.sync.aligned;" ::: "memory"); }
__device__ __forceinline__ void wg_commit() { asm volatile("wgmma.commit_group.sync.aligned;" ::: "memory"); }
template <int N> __device__ __forceinline__ void wg_wait() { asm volatile("wgmma.wait_group.sync.aligned %0;" :: "n"(N) : "memory"); }
template <int N> __device__ __forceinline__ void reg_fence(float (&d)[N]) {
#pragma unroll
  for (int i = 0; i < N; i++) asm volatile("" : "+f"(d[i]) :: "memory");
}
template <int N> __device__ __forceinline__ void reg_fence(uint32_t (&d)[N]) {
#pragma unroll
  for (int i = 0; i < N; i++) asm volatile("" : "+r"(d[i]) :: "memory");
}
__device__ __forceinline__ uint32_t fresh_tid() { uint32_t t; asm volatile("mov.u32 %0, %%tid.x;" : "=r"(t)); return t; }
__device__ __forceinline__ uint32_t lane_base16() {
  const uint32_t t = fresh_tid(), lane = t & 31, wq = (t >> 5) & 3;
  return (16 * wq + (lane & 7) + 8 * ((lane >> 3) & 1)) * 128 + (((lane >> 4) ^ (lane & 7)) << 4);
}
__device__ __forceinline__ void named_sync(int id, int n) { asm volatile("bar.sync %0, %1;" :: "r"(id), "r"(n) : "memory"); }
__device__ __forceinline__ void named_arrive(int id, int n) { asm volatile("bar.arrive %0, %1;" :: "r"(id), "r"(n) : "memory"); }
__device__ __forceinline__ uint32_t pack_bf16(float lo, float hi) {
  uint32_t r; asm("cvt.rn.bf16x2.f32 %0, %1, %2;" : "=r"(r) : "f"(hi), "f"(lo)); return r;
}
__device__ __forceinline__ float ex2(float x) { float y; asm("ex2.approx.ftz.f32 %0, %1;" : "=f"(y) : "f"(x)); return y; }
__device__ __forceinline__ void stsm4(uint32_t addr, uint32_t a, uint32_t b, uint32_t c, uint32_t d) {
  asm volatile("stmatrix.sync.aligned.m8n8.x4.shared.b16 [%0], {%1, %2, %3, %4};" :: "r"(addr), "r"(a), "r"(b), "r"(c), "r"(d) : "memory");
}
__device__ __forceinline__ void stsm4t(uint32_t addr, uint32_t a, uint32_t b, uint32_t c, uint32_t d) {
  asm volatile("stmatrix.sync.aligned.m8n8.x4.trans.shared.b16 [%0], {%1, %2, %3, %4};" :: "r"(addr), "r"(a), "r"(b), "r"(c), "r"(d) : "memory");
}
__device__ __forceinline__ uint64_t mk_desc(uint32_t addr, uint32_t lbo, uint32_t sbo) {
  return (uint64_t)(((addr & 0x3FFFF) >> 4) | ((lbo >> 4) << 16)) | ((uint64_t)((sbo >> 4) | (1u << 30)) << 32);
}
__device__ __forceinline__ uint64_t desc_k(uint32_t addr)  { return mk_desc(addr, 16, 1024); }
__device__ __forceinline__ uint64_t desc_mn(uint32_t addr) { return mk_desc(addr, 8192, 1024); }
__device__ __forceinline__ uint64_t desc_add(uint64_t d, uint32_t bytes) { return d + (bytes >> 4); }

__device__ __forceinline__ void wgmma_ss_n256_tb(float (&d)[128], uint64_t da, uint64_t db, int sd) {
  asm volatile("{\n.reg .pred p;\nsetp.ne.b32 p, %130, 0;\n"
    "wgmma.mma_async.sync.aligned.m64n256k16.f32.bf16.bf16 "
    "{%0, %1, %2, %3, %4, %5, %6, %7, %8, %9, %10, %11, %12, %13, %14, %15, "
    "%16, %17, %18, %19, %20, %21, %22, %23, %24, %25, %26, %27, %28, %29, %30, %31, "
    "%32, %33, %34, %35, %36, %37, %38, %39, %40, %41, %42, %43, %44, %45, %46, %47, "
    "%48, %49, %50, %51, %52, %53, %54, %55, %56, %57, %58, %59, %60, %61, %62, %63, "
    "%64, %65, %66, %67, %68, %69, %70, %71, %72, %73, %74, %75, %76, %77, %78, %79, "
    "%80, %81, %82, %83, %84, %85, %86, %87, %88, %89, %90, %91, %92, %93, %94, %95, "
    "%96, %97, %98, %99, %100, %101, %102, %103, %104, %105, %106, %107, %108, %109, %110, %111, "
    "%112, %113, %114, %115, %116, %117, %118, %119, %120, %121, %122, %123, %124, %125, %126, %127}, "
    "%128, %129, p, 1, 1, 0, 1;\n}"
    : "+f"(d[0]), "+f"(d[1]), "+f"(d[2]), "+f"(d[3]), "+f"(d[4]), "+f"(d[5]), "+f"(d[6]), "+f"(d[7]),
      "+f"(d[8]), "+f"(d[9]), "+f"(d[10]), "+f"(d[11]), "+f"(d[12]), "+f"(d[13]), "+f"(d[14]), "+f"(d[15]),
      "+f"(d[16]), "+f"(d[17]), "+f"(d[18]), "+f"(d[19]), "+f"(d[20]), "+f"(d[21]), "+f"(d[22]), "+f"(d[23]),
      "+f"(d[24]), "+f"(d[25]), "+f"(d[26]), "+f"(d[27]), "+f"(d[28]), "+f"(d[29]), "+f"(d[30]), "+f"(d[31]),
      "+f"(d[32]), "+f"(d[33]), "+f"(d[34]), "+f"(d[35]), "+f"(d[36]), "+f"(d[37]), "+f"(d[38]), "+f"(d[39]),
      "+f"(d[40]), "+f"(d[41]), "+f"(d[42]), "+f"(d[43]), "+f"(d[44]), "+f"(d[45]), "+f"(d[46]), "+f"(d[47]),
      "+f"(d[48]), "+f"(d[49]), "+f"(d[50]), "+f"(d[51]), "+f"(d[52]), "+f"(d[53]), "+f"(d[54]), "+f"(d[55]),
      "+f"(d[56]), "+f"(d[57]), "+f"(d[58]), "+f"(d[59]), "+f"(d[60]), "+f"(d[61]), "+f"(d[62]), "+f"(d[63]),
      "+f"(d[64]), "+f"(d[65]), "+f"(d[66]), "+f"(d[67]), "+f"(d[68]), "+f"(d[69]), "+f"(d[70]), "+f"(d[71]),
      "+f"(d[72]), "+f"(d[73]), "+f"(d[74]), "+f"(d[75]), "+f"(d[76]), "+f"(d[77]), "+f"(d[78]), "+f"(d[79]),
      "+f"(d[80]), "+f"(d[81]), "+f"(d[82]), "+f"(d[83]), "+f"(d[84]), "+f"(d[85]), "+f"(d[86]), "+f"(d[87]),
      "+f"(d[88]), "+f"(d[89]), "+f"(d[90]), "+f"(d[91]), "+f"(d[92]), "+f"(d[93]), "+f"(d[94]), "+f"(d[95]),
      "+f"(d[96]), "+f"(d[97]), "+f"(d[98]), "+f"(d[99]), "+f"(d[100]), "+f"(d[101]), "+f"(d[102]), "+f"(d[103]),
      "+f"(d[104]), "+f"(d[105]), "+f"(d[106]), "+f"(d[107]), "+f"(d[108]), "+f"(d[109]), "+f"(d[110]), "+f"(d[111]),
      "+f"(d[112]), "+f"(d[113]), "+f"(d[114]), "+f"(d[115]), "+f"(d[116]), "+f"(d[117]), "+f"(d[118]), "+f"(d[119]),
      "+f"(d[120]), "+f"(d[121]), "+f"(d[122]), "+f"(d[123]), "+f"(d[124]), "+f"(d[125]), "+f"(d[126]), "+f"(d[127])
    : "l"(da), "l"(db), "r"(sd));
}
__device__ __forceinline__ void wgmma_ss_n64(float (&d)[32], uint64_t da, uint64_t db, int sd) {
  asm volatile("{\n.reg .pred p;\nsetp.ne.b32 p, %34, 0;\n"
    "wgmma.mma_async.sync.aligned.m64n64k16.f32.bf16.bf16 "
    "{%0, %1, %2, %3, %4, %5, %6, %7, %8, %9, %10, %11, %12, %13, %14, %15, "
    "%16, %17, %18, %19, %20, %21, %22, %23, %24, %25, %26, %27, %28, %29, %30, %31}, "
    "%32, %33, p, 1, 1, 0, 0;\n}"
    : "+f"(d[0]), "+f"(d[1]), "+f"(d[2]), "+f"(d[3]), "+f"(d[4]), "+f"(d[5]), "+f"(d[6]), "+f"(d[7]),
      "+f"(d[8]), "+f"(d[9]), "+f"(d[10]), "+f"(d[11]), "+f"(d[12]), "+f"(d[13]), "+f"(d[14]), "+f"(d[15]),
      "+f"(d[16]), "+f"(d[17]), "+f"(d[18]), "+f"(d[19]), "+f"(d[20]), "+f"(d[21]), "+f"(d[22]), "+f"(d[23]),
      "+f"(d[24]), "+f"(d[25]), "+f"(d[26]), "+f"(d[27]), "+f"(d[28]), "+f"(d[29]), "+f"(d[30]), "+f"(d[31])
    : "l"(da), "l"(db), "r"(sd));
}
__device__ __forceinline__ void wgmma_rs_n256_tb(float (&d)[128], uint32_t a0, uint32_t a1, uint32_t a2, uint32_t a3, uint64_t db, int sd) {
  asm volatile("{\n.reg .pred p;\nsetp.ne.b32 p, %133, 0;\n"
    "wgmma.mma_async.sync.aligned.m64n256k16.f32.bf16.bf16 "
    "{%0, %1, %2, %3, %4, %5, %6, %7, %8, %9, %10, %11, %12, %13, %14, %15, "
    "%16, %17, %18, %19, %20, %21, %22, %23, %24, %25, %26, %27, %28, %29, %30, %31, "
    "%32, %33, %34, %35, %36, %37, %38, %39, %40, %41, %42, %43, %44, %45, %46, %47, "
    "%48, %49, %50, %51, %52, %53, %54, %55, %56, %57, %58, %59, %60, %61, %62, %63, "
    "%64, %65, %66, %67, %68, %69, %70, %71, %72, %73, %74, %75, %76, %77, %78, %79, "
    "%80, %81, %82, %83, %84, %85, %86, %87, %88, %89, %90, %91, %92, %93, %94, %95, "
    "%96, %97, %98, %99, %100, %101, %102, %103, %104, %105, %106, %107, %108, %109, %110, %111, "
    "%112, %113, %114, %115, %116, %117, %118, %119, %120, %121, %122, %123, %124, %125, %126, %127}, "
    "{%128, %129, %130, %131}, %132, p, 1, 1, 1;\n}"
    : "+f"(d[0]), "+f"(d[1]), "+f"(d[2]), "+f"(d[3]), "+f"(d[4]), "+f"(d[5]), "+f"(d[6]), "+f"(d[7]),
      "+f"(d[8]), "+f"(d[9]), "+f"(d[10]), "+f"(d[11]), "+f"(d[12]), "+f"(d[13]), "+f"(d[14]), "+f"(d[15]),
      "+f"(d[16]), "+f"(d[17]), "+f"(d[18]), "+f"(d[19]), "+f"(d[20]), "+f"(d[21]), "+f"(d[22]), "+f"(d[23]),
      "+f"(d[24]), "+f"(d[25]), "+f"(d[26]), "+f"(d[27]), "+f"(d[28]), "+f"(d[29]), "+f"(d[30]), "+f"(d[31]),
      "+f"(d[32]), "+f"(d[33]), "+f"(d[34]), "+f"(d[35]), "+f"(d[36]), "+f"(d[37]), "+f"(d[38]), "+f"(d[39]),
      "+f"(d[40]), "+f"(d[41]), "+f"(d[42]), "+f"(d[43]), "+f"(d[44]), "+f"(d[45]), "+f"(d[46]), "+f"(d[47]),
      "+f"(d[48]), "+f"(d[49]), "+f"(d[50]), "+f"(d[51]), "+f"(d[52]), "+f"(d[53]), "+f"(d[54]), "+f"(d[55]),
      "+f"(d[56]), "+f"(d[57]), "+f"(d[58]), "+f"(d[59]), "+f"(d[60]), "+f"(d[61]), "+f"(d[62]), "+f"(d[63]),
      "+f"(d[64]), "+f"(d[65]), "+f"(d[66]), "+f"(d[67]), "+f"(d[68]), "+f"(d[69]), "+f"(d[70]), "+f"(d[71]),
      "+f"(d[72]), "+f"(d[73]), "+f"(d[74]), "+f"(d[75]), "+f"(d[76]), "+f"(d[77]), "+f"(d[78]), "+f"(d[79]),
      "+f"(d[80]), "+f"(d[81]), "+f"(d[82]), "+f"(d[83]), "+f"(d[84]), "+f"(d[85]), "+f"(d[86]), "+f"(d[87]),
      "+f"(d[88]), "+f"(d[89]), "+f"(d[90]), "+f"(d[91]), "+f"(d[92]), "+f"(d[93]), "+f"(d[94]), "+f"(d[95]),
      "+f"(d[96]), "+f"(d[97]), "+f"(d[98]), "+f"(d[99]), "+f"(d[100]), "+f"(d[101]), "+f"(d[102]), "+f"(d[103]),
      "+f"(d[104]), "+f"(d[105]), "+f"(d[106]), "+f"(d[107]), "+f"(d[108]), "+f"(d[109]), "+f"(d[110]), "+f"(d[111]),
      "+f"(d[112]), "+f"(d[113]), "+f"(d[114]), "+f"(d[115]), "+f"(d[116]), "+f"(d[117]), "+f"(d[118]), "+f"(d[119]),
      "+f"(d[120]), "+f"(d[121]), "+f"(d[122]), "+f"(d[123]), "+f"(d[124]), "+f"(d[125]), "+f"(d[126]), "+f"(d[127])
    : "r"(a0), "r"(a1), "r"(a2), "r"(a3), "l"(db), "r"(sd));
}
__device__ __forceinline__ void wgmma_rs_n64_tb(float (&d)[32], uint32_t a0, uint32_t a1, uint32_t a2, uint32_t a3, uint64_t db, int sd) {
  asm volatile("{\n.reg .pred p;\nsetp.ne.b32 p, %37, 0;\n"
    "wgmma.mma_async.sync.aligned.m64n64k16.f32.bf16.bf16 "
    "{%0, %1, %2, %3, %4, %5, %6, %7, %8, %9, %10, %11, %12, %13, %14, %15, "
    "%16, %17, %18, %19, %20, %21, %22, %23, %24, %25, %26, %27, %28, %29, %30, %31}, "
    "{%32, %33, %34, %35}, %36, p, 1, 1, 1;\n}"
    : "+f"(d[0]), "+f"(d[1]), "+f"(d[2]), "+f"(d[3]), "+f"(d[4]), "+f"(d[5]), "+f"(d[6]), "+f"(d[7]),
      "+f"(d[8]), "+f"(d[9]), "+f"(d[10]), "+f"(d[11]), "+f"(d[12]), "+f"(d[13]), "+f"(d[14]), "+f"(d[15]),
      "+f"(d[16]), "+f"(d[17]), "+f"(d[18]), "+f"(d[19]), "+f"(d[20]), "+f"(d[21]), "+f"(d[22]), "+f"(d[23]),
      "+f"(d[24]), "+f"(d[25]), "+f"(d[26]), "+f"(d[27]), "+f"(d[28]), "+f"(d[29]), "+f"(d[30]), "+f"(d[31])
    : "r"(a0), "r"(a1), "r"(a2), "r"(a3), "l"(db), "r"(sd));
}

__device__ __forceinline__ uint4 lds16(uint32_t a) {
  uint4 v; asm volatile("ld.shared.v4.u32 {%0, %1, %2, %3}, [%4];" : "=r"(v.x), "=r"(v.y), "=r"(v.z), "=r"(v.w) : "r"(a) : "memory"); return v;
}
__device__ __forceinline__ void sts16(uint32_t a, uint32_t x, uint32_t y, uint32_t z, uint32_t w) {
  asm volatile("st.shared.v4.u32 [%0], {%1, %2, %3, %4};" :: "r"(a), "r"(x), "r"(y), "r"(z), "r"(w) : "memory");
}
__device__ __forceinline__ uint32_t lds4(uint32_t a) { uint32_t v; asm volatile("ld.shared.u32 %0, [%1];" : "=r"(v) : "r"(a) : "memory"); return v; }
__device__ __forceinline__ uint32_t lds4v(uint32_t a) { uint32_t v; asm volatile("ld.volatile.shared.u32 %0, [%1];" : "=r"(v) : "r"(a) : "memory"); return v; }
__device__ __forceinline__ uint32_t bmul(uint32_t a, uint32_t b) { uint32_t r; asm("mul.rn.bf16x2 %0, %1, %2;" : "=r"(r) : "r"(a), "r"(b)); return r; }
__device__ __forceinline__ uint32_t bfma(uint32_t a, uint32_t b, uint32_t c) { uint32_t r; asm("fma.rn.bf16x2 %0, %1, %2, %3;" : "=r"(r) : "r"(a), "r"(b), "r"(c)); return r; }
__device__ __forceinline__ uint32_t badd(uint32_t a, uint32_t b) { uint32_t r; asm("add.rn.bf16x2 %0, %1, %2;" : "=r"(r) : "r"(a), "r"(b)); return r; }

__device__ __forceinline__ void ldsm4(uint32_t (&r)[4], uint32_t a) {
  asm volatile("ldmatrix.sync.aligned.m8n8.x4.shared.b16 {%0, %1, %2, %3}, [%4];" : "=r"(r[0]), "=r"(r[1]), "=r"(r[2]), "=r"(r[3]) : "r"(a) : "memory");
}
__device__ __forceinline__ void ldsm4t(uint32_t (&r)[4], uint32_t a) {
  asm volatile("ldmatrix.sync.aligned.m8n8.x4.trans.shared.b16 {%0, %1, %2, %3}, [%4];" : "=r"(r[0]), "=r"(r[1]), "=r"(r[2]), "=r"(r[3]) : "r"(a) : "memory");
}
__device__ __forceinline__ uint32_t transpose8(uint32_t a) { uint32_t d; asm volatile("movmatrix.sync.aligned.m8n8.trans.b16 %0, %1;" : "=r"(d) : "r"(a)); return d; }

__device__ __forceinline__ void mma16816(float (&d)[4], const uint32_t (&a)[4], uint32_t b0, uint32_t b1) {
  asm volatile("mma.sync.aligned.m16n8k16.row.col.f32.bf16.bf16.f32 {%0, %1, %2, %3}, {%4, %5, %6, %7}, {%8, %9}, {%0, %1, %2, %3};"
               : "+f"(d[0]), "+f"(d[1]), "+f"(d[2]), "+f"(d[3]) : "r"(a[0]), "r"(a[1]), "r"(a[2]), "r"(a[3]), "r"(b0), "r"(b1));
}

#define P1_SPLIT 0
#define O_ROT 1
#define STG_K1 2
#define STG_K2 10
#define STG_Q1 2
#define STG_Q2 6
#define CTX_K 0
#define PF_QA 99
#define PF_WV 99
#define PF_END 0
#define PF_CV 1
#define PACE_A 850
#define PACE_B 400
#define ARRIVE_KK 12
#define SIDE_DELAY_NS 4000
#define KVH(h) (h)
#define HEAD_MAP 1
#define EARLY_LD 3
constexpr int RED_BAR = 6;
constexpr int CV_BAR = 5;
constexpr int PP_BAR = 3;
template <int V> struct Int { static constexpr int value = V; };
struct Ring {
  uint32_t slot, phase;
  __device__ __forceinline__ void next() { if (++slot == NSLOT) { slot = 0; phase ^= 1; } }
};
__device__ __forceinline__ uint32_t bar_addr(uint32_t sb, uint32_t i) { return sb + BARS + 8 * i; }
__device__ __forceinline__ uint32_t q_region(uint32_t sb, int w) { return sb + QREG + (w ^ 1) * 32768; }

struct Role { int h, j; };
__device__ __forceinline__ Role get_role() {
  int cta; asm volatile("mov.u32 %0, %%ctaid.x;" : "=r"(cta));
  const int c = cta >> 1;
  int h, u;
  if (c < 4) { h = 15; u = c; }
  else if (c < 36) { h = (c - 4) & 7; u = (c - 4) >> 3; }
  else { h = 8 + (c - 36) % 7; u = (c - 36) / 7; }
  return Role{h, 2 * u + (cta & 1)};
}
__device__ __forceinline__ int fresh_warp() { return __shfl_sync(0xffffffffu, fresh_tid() >> 5, 0); }

__device__ __forceinline__ int q_tile(int h, int j, int which) { return ((h < 8) == (which == 0)) ? 15 - j : j; }

__device__ __forceinline__ int o_chunk(int h, int c) { const int x = c + O_ROT * (h & 7); return x % 7; }

__device__ __forceinline__ int num_private(int qt) { return (qt & 1) ? 5 : 1; }
__device__ __forceinline__ void ring_acquire(uint32_t sb, Ring& r, uint32_t bytes) {
  mbar_wait(bar_addr(sb, B_RG_EMPTY + r.slot), r.phase ^ 1);
  mbar_expect_tx(bar_addr(sb, B_RG_FULL + r.slot), bytes);
}
__device__ __forceinline__ void load_tile4(uint32_t dst, const CUtensorMap* m, uint32_t full, int row, int blk0, int rank, bool shared) {
  if (shared) {
    tma_ld3_mc(dst + rank * 16384, m, full, 0, row, blk0 + 2 * rank);
  } else {
    tma_ld3(dst, m, full, 0, row, blk0);
    tma_ld3(dst + 16384, m, full, 0, row, blk0 + 2);
  }
}
__device__ __forceinline__ void producer_main(const Params& p, uint32_t sb) {
  const Role ro = get_role();
  const int h = ro.h, j = ro.j, rank = j & 1;
  auto prefetch_q = [&](int qt) {
    bulk_prefetch(p.b_x + (size_t)(qt * 128 + (h & 7) * 16) * DM, 16 * DM * 2);
    if (j < 7) { tma_pf3(&p.wq, 0, j * 64, h * 4); tma_pf3(&p.wq, 0, j * 64, h * 4 + 2); }
  };
  for (int it = EARLY_LD; it < 71; it++) {
    const int t = it >> 4, k = it & 15, s = it & 3;
    mbar_wait(bar_addr(sb, B_P1_EMPTY + s), ((it >> 2) & 1) ^ 1);
    const uint32_t full = bar_addr(sb, B_P1_FULL + s), dst = sb + s * P1_STAGE;
    mbar_expect_tx(full, P1_STAGE);
    if (t < 4) {
      tma_ld2(dst, &p.ckv, full, k * 64, (2 * j + (t & 1)) * 128);
      load_tile4(dst + 16384, (t >> 1) ? &p.wuv : &p.wuk, full, k * 64, h * 4, rank, true);
    } else {
      tma_ld2(dst, &p.x, full, k * 64, q_tile(h, j, 0) * 128);
      load_tile4(dst + 16384, &p.wq, full, k * 64, h * 4, rank, true);
    }
    if (it == PF_QA) prefetch_q(q_tile(h, j, 0));
    if (it == PF_WV) { for (int i = 0; i < 4; i++) tma_pf3(&p.wuv, 0, (2 * j + (i >> 1)) * 64, h * 4 + 2 * (i & 1)); }
  }
  mbar_wait(bar_addr(sb, B_P1_EMPTY + 3), 0);
  mbar_wait(bar_addr(sb, B_XS), 0);
  mbar_expect_tx(bar_addr(sb, B_RG_FULL + 4), CV_BYTES);
  bulk_ld(sb + CV_X, g_xs + (size_t)(h * 8 + j) * CV_BYTES, CV_BYTES, bar_addr(sb, B_RG_FULL + 4));
  Ring r{0, 1};
  int hs = 5;
  auto acquire = [&](bool shared) {
    mbar_wait(bar_addr(sb, B_RG_EMPTY + r.slot), r.phase ^ 1);
    if (shared && hs < 5) {
      mbar_arrive_remote(bar_addr(sb, B_PFREE + r.slot), rank ^ 1);
      mbar_wait(bar_addr(sb, B_PFREE + r.slot), 0);
      hs++;
    }
    mbar_expect_tx(bar_addr(sb, B_RG_FULL + r.slot), 32768);
  };
  mbar_wait(bar_addr(sb, B_KV), 0);
  for (int which = 0; which < 2; which++) {
    const int qt = q_tile(h, j, which);
    if (which == 1) {
      for (int kc = 0; kc < 7; kc++) {
        ring_acquire(sb, r, 32768);
        load_tile4(sb + r.slot * SLOT, &p.wq, bar_addr(sb, B_RG_FULL + r.slot), kc * 64, h * 4, rank, false);
        r.next();
        if (kc == 0 || (kc & 1)) {
          ring_acquire(sb, r, kc == 0 ? 16384 : 32768);
          const uint32_t full = bar_addr(sb, B_RG_FULL + r.slot), dst = sb + r.slot * SLOT;
          tma_ld2(dst, &p.x, full, kc * 64, qt * 128);
          if (kc > 0) tma_ld2(dst + 16384, &p.x, full, kc * 64 + 64, qt * 128);
          r.next();
        }
      }
      hs = 0;
    }
    const int n = 2 * qt + 2, npriv = num_private(qt), nb = qt & ~1;
    for (int f = 0; f < 2 * n; f++) {
      if (PF_END && f == max(2 * n - PF_END, 0)) {
        if (which == 0) bulk_prefetch(p.b_x + (size_t)((15 - qt) * 128 + (h & 7) * 16) * DM, 16 * DM * 2);
        else bulk_prefetch(p.b_wo + (size_t)(h * HD + j * 32) * DM, 32 * DM * 2);
      }
      const bool isK = (f == 0) || ((f & 1) && f < 2 * n - 1);
      const int i = isK ? (f + 1) >> 1 : (f == 2 * n - 1 ? n - 1 : (f >> 1) - 1);
      int tile = n - 1 - i;
      if (which == 0) { const int b = i >> 1; tile = b >= nb ? i : 2 * (2 * b < nb ? 2 * b : 2 * b - nb + 1) + (i & 1); }
      if (!isK && (tile & 2)) mbar_wait(bar_addr(sb, B_KV + 1), 0);
      if (which == 0 && f < 2) mbar_wait(bar_addr(sb, B_P1_EMPTY + f), 1);
      const bool shared = (which ? f : 2 * n - 1 - f) >= npriv;
      acquire(shared);
      load_tile4(sb + r.slot * SLOT, &p.kv, bar_addr(sb, B_RG_FULL + r.slot), ((isK ? 0 : NH) + KVH(h)) * SEQ + tile * 64, 0, rank, shared);
      r.next();
    }
  }
  for (int i = 0; i < 14; i++) {
    acquire(true);
    tma_ld2_mc(sb + r.slot * SLOT + rank * 16384, &p.wo, bar_addr(sb, B_RG_FULL + r.slot), o_chunk(h, i >> 1) * 64, ((i & 1) ? h ^ 8 : h) * HD + rank * 128);
    r.next();
  }
}

__device__ __forceinline__ void storer_main(const Params& p, uint32_t sb) {
  const Role ro = get_role();
  const int h = ro.h, j = ro.j, w = fresh_warp() - 1;
  const uint32_t full = bar_addr(sb, B_ST_FULL + w), empty = bar_addr(sb, B_ST_EMPTY + w);
  const int lane = threadIdx.x & 31;
  const unsigned epoch = load_epoch();
  for (int job = 0; job < 8; job++) {
    const int t = job >> 1, half = job & 1;
    mbar_wait(full, job & 1);
    const uint32_t src = sb + P1_STG + w * 16384 + (lane >> 3) * 128;
    bf16* dst = g_kv + (size_t)(((t >> 1) * NH + KVH(h)) * SEQ + (2 * j + (t & 1)) * 128 + w * 64 + (lane >> 3)) * HD + half * 128 + (lane & 7) * 8;
    const uint32_t t0 = (uint32_t)clock(), pace = job < 6 ? PACE_A : PACE_B;
#pragma unroll 1
    for (int i0 = 0; i0 < 32; i0 += 4) {
      while ((uint32_t)clock() - t0 < (i0 >> 2) * pace) __nanosleep(40);
#pragma unroll
      for (int i = i0; i < i0 + 4; i++) {
        const int r4 = (i & 15) * 4;
        const uint4 v = lds16(src + (i >> 4) * 8192 + r4 * 128 + (((lane & 7) ^ ((r4 + (lane >> 3)) & 7)) << 4));
        *reinterpret_cast<uint4*>(dst + r4 * HD + (i >> 4) * 64) = v;
      }
    }
    __syncwarp();
    if (lane == 0) {
      mbar_arrive(empty);
      if (job == 5 || job == 7) flag_signal(&g_flags.kv_ready[2 * h + (job == 7)].v);
    }
    __syncwarp();
  }
  const int cta = h * 8 + j, qt = q_tile(h, j, 1);
  const uint32_t qreg = q_region(sb, w);
  {
    mbar_wait(bar_addr(sb, B_CTXS + 4 * w), 0);
    uint4* z = reinterpret_cast<uint4*>(p.out + (size_t)(qt * 128 + w * 64 + (h & 7) * 8 + (lane >> 2)) * OUTW + DA) + (lane & 3);
#pragma unroll
    for (int i = 0; i < 14; i++) z[4 * i] = make_uint4(0, 0, 0, 0);
    __syncwarp();
    if (lane != 0) return;
    for (int b = 0; b < 4; b++) {
      mbar_wait(bar_addr(sb, B_CTXS + 4 * w + b), 0);
      tma_st3(&p.ctxs, qreg + b * 8192, 0, cta * 128 + w * 64, b);
      bulk_commit();
    }
    bulk_wait_read();
    mbar_arrive(empty);
    bulk_wait_all();
    flag_signal(&g_flags.ctx_ready[cta * 2 + w].v);
    flag_signal_after_bulk(&g_flags.out_ready[qt * 2 + w].v);
  }
  {
    const int wx = w ^ 1;
    flag_wait(&g_flags.ctx_ready[(cta ^ 64) * 2 + wx].v, 1, epoch);
    flag_wait(&g_flags.out_ready[qt * 2 + wx].v, 8, epoch);
    fence_async_all();
    mbar_wait(bar_addr(sb, B_QFREE + w), 0);
    mbar_expect_tx(bar_addr(sb, B_CTXF + w), 32768);
    tma_ld3(qreg, &p.ctx, bar_addr(sb, B_CTXF + w), 0, (cta ^ 64) * 128 + wx * 64, 0);
    for (int ch = 0; ch < 7; ch++) {
      const int b = ch & 1;
      mbar_wait(bar_addr(sb, B_S2_FULL + w * 2 + b), (ch >> 1) & 1);
      tma_red2(&p.part, qreg + b * 8192, DA + o_chunk(h, ch) * 64, qt * 128 + wx * 64);
      bulk_commit();
      if (ch == 0 && w == 1) mbar_arrive(bar_addr(sb, B_GFREE));
      bulk_wait_read();
      mbar_arrive(bar_addr(sb, B_S2_EMPTY + w * 2 + b));
    }
    GT(48 + w);
    bulk_wait_all();
    GT(50 + w); GT(52 + w); GT(56);
  }
}

template <int OFF, int NB, int NREG>
__device__ __forceinline__ void store_blocks(uint32_t base, uint32_t lanebase, const uint32_t (&pk)[NREG]) {
#pragma unroll
  for (int J = 0; J < NB * 8; J += 2) {
    const uint32_t a = base + (J >> 3) * 8192 + (lanebase ^ ((J & 7) << 4));
    stsm4(a, pk[OFF + 2 * J], pk[OFF + 2 * J + 1], pk[OFF + 2 * J + 2], pk[OFF + 2 * J + 3]);
  }
}
__device__ __forceinline__ void warp_arrive(uint32_t bar, int lane) { __syncwarp(); if (lane == 0) mbar_arrive(bar); }
__device__ __forceinline__ void release(uint32_t bar, int lane, int rank, bool shared) {
  if (shared) { if (lane < 2) mbar_arrive_remote(bar, rank ^ lane); }
  else if (lane == 0) mbar_arrive_n(bar, 2);
}

template <int W> __device__ __forceinline__ constexpr int cv_tile(int u) { return 2 * u + ((u ^ W) & 1); }
__device__ __forceinline__ uint32_t cv_x_lane(uint32_t lane) { return (16 + (lane & 15) - (lane >> 4)) * 16; }
__device__ __forceinline__ uint32_t cv_h_lane(uint32_t lane, uint32_t hE, uint32_t hO) {
  const uint32_t g = lane >> 2, c = lane & 3;
  return (g & 1) ? hO + (15 + 2 * c - g) * 2 : hE + (16 + 2 * c - g) * 2;
}
template <int W>
__device__ __forceinline__ void conv_mma(float (&ca)[8][4], uint32_t xa, uint32_t ha) {
#pragma unroll 1
  for (int rr = 0; rr < 2; rr++) {
    uint32_t fx[16][4], fh[16][2];
#pragma unroll
    for (int i = 0; i < 16 - W; i++) { fh[i][0] = lds4(ha + i * 256 + rr * 32); fh[i][1] = lds4(ha + i * 256 + rr * 32 + 16); }
#pragma unroll
    for (int i = 0; i < 16 - W; i++) ldsm4(fx[i], xa + i * 256 - rr * 32);
#pragma unroll
    for (int sx = 0; sx < 16 - W; sx++)
#pragma unroll
      for (int u = 0; u < 8; u++) {
        const int jj = cv_tile<W>(u) - sx;
        if (jj >= 0) mma16816(ca[u], fx[sx], fh[jj & 15][0], fh[jj & 15][1]);
      }
  }
}

__device__ __forceinline__ void consumer_main(const Params& p, uint32_t sb) {
  const int lane = fresh_tid() & 31, w = (fresh_warp() >> 2) - 1;
  const uint32_t lb = lane_base16();
  int qt, rank;
  { const Role ro = get_role(); qt = q_tile(ro.h, ro.j, 0); rank = ro.j & 1; }
  const uint32_t st_full = bar_addr(sb, B_ST_FULL + w), st_empty = bar_addr(sb, B_ST_EMPTY + w);
  const uint32_t stg = sb + P1_STG + w * 16384;

  auto turn_begin = [&]() { named_sync(PP_BAR + w, 256); };
  auto turn_end = [&]() { named_arrive(PP_BAR + (w ^ 1), 256); };
  if (w == 0) named_arrive(PP_BAR + 1, 256);
  float acc[128];
#pragma unroll
  for (int i = 0; i < 128; i++) acc[i] = 0.f;
  uint32_t pk[64];
#pragma unroll
  for (int i = 0; i < 64; i++) pk[i] = 0;
  PDECL;
  TR_DECL;
  TR(0);
  TSG(0); TS(1);
  const uint32_t qreg = q_region(sb, w);
  for (int t = 0; t < 5; t++) {
    const int nk = t < 4 ? 16 : 7;
#pragma unroll 1
    for (int k = 0; k < nk; k++) {
      const int it = t * 16 + k, s = k & 3;
      mbar_wait(bar_addr(sb, B_P1_FULL + s), (it >> 2) & 1);
      TR(1);
      const uint64_t da = desc_k(sb + s * P1_STAGE + w * 8192), db = desc_mn(sb + s * P1_STAGE + 16384);
      turn_begin();
      wg_fence();
#pragma unroll
      for (int kk = 0; kk < 4; kk++) wgmma_ss_n256_tb(acc, desc_add(da, kk * 32), desc_add(db, kk * 2048), (k | kk) != 0);
      wg_commit();
      turn_end();
      TR(3);
      wg_wait<1>();
      if (k > 0) release(bar_addr(sb, B_P1_EMPTY + ((k - 1) & 3)), lane, rank, true);
      const int k1 = t < 4 ? STG_K1 : STG_Q1, k2 = t < 4 ? STG_K2 : STG_Q2;
      if (t > 0 && (k == k1 || k == k2)) {
        const int job = 2 * (t - 1) + (k != k1);
        if (job > 0) mbar_wait(st_empty, (job - 1) & 1);
        if (k == k1) store_blocks<0, 2>(stg, lb, pk); else store_blocks<32, 2>(stg, lb, pk);
        warp_arrive(st_full, lane);
      }
      TR(5);
    }
    wg_wait<0>();
    TR(6);
    reg_fence(acc);
    release(bar_addr(sb, B_P1_EMPTY + ((nk - 1) & 3)), lane, rank, true);
#pragma unroll
    for (int i = 0; i < 64; i++) pk[i] = pack_bf16(acc[2 * i], acc[2 * i + 1]);
    TS(t < 4 ? 2 + t : 60);
  }
  TS(6);
  {
    const uint32_t wq = lb >> 11, ln = lane, cx = sb + CV_X;
    float ca[8][4];
#pragma unroll
    for (int i = 0; i < 8; i++) { ca[i][0] = 0.f; ca[i][1] = 0.f; ca[i][2] = 0.f; ca[i][3] = 0.f; }
    const uint32_t xa = cx + cv_x_lane(ln) - wq * 64, ha = cv_h_lane(ln, cx + CV_HE, cx + CV_HE + CV_HCOPY) + wq * 64;
    mbar_wait(bar_addr(sb, B_RG_FULL + 4), 0);
    TR(7); TS(19); TS(20);
    if (w) conv_mma<1>(ca, xa, ha); else conv_mma<0>(ca, xa, ha);
    TR(8); TS(21);
    mbar_wait(bar_addr(sb, B_P1_EMPTY + 2), 1);
    const uint32_t ex = sb + CV_R + w * 16384 + ln * 16;
#pragma unroll
    for (int u = 0; u < 8; u++)
      sts16(ex + (wq * 8 + u) * 512, __float_as_uint(ca[u][0]), __float_as_uint(ca[u][1]), __float_as_uint(ca[u][2]), __float_as_uint(ca[u][3]));
    if (w == 0) { mbar_wait(st_empty, 1); mbar_wait(bar_addr(sb, B_ST_EMPTY + 1), 1); }
    store_blocks<0, 4>(qreg, lb, pk);
    named_sync(1 + w, 128);
    TR(9); TS(22);
    const uint32_t Dd = lds4(cx + CV_D);
    uint32_t z[2][2];
#pragma unroll
    for (int e = 0; e < 2; e++) {
      const uint32_t u = 2 * wq + e, nt = 2 * u + ((e ^ w) & 1);
      float y[4] = {0.f, 0.f, 0.f, 0.f};
#pragma unroll
      for (int v = 0; v < 4; v++) {
        const uint4 t = lds16(ex + (v * 8 + u) * 512);
        y[0] += __uint_as_float(t.x); y[1] += __uint_as_float(t.y); y[2] += __uint_as_float(t.z); y[3] += __uint_as_float(t.w);
      }
      const uint32_t ro = (16 + 16 * nt) * 16 + ln * 4;
      z[e][0] = badd(pack_bf16(y[0], y[1]), bmul(lds4(cx + ro), Dd));
      z[e][1] = badd(pack_bf16(y[2], y[3]), bmul(lds4(cx + ro + 128), Dd));
    }
    TS(23);
    fence_async_smem();
    __syncwarp();
    release(bar_addr(sb, B_RG_EMPTY + 3), lane, rank, true);
    release(bar_addr(sb, B_RG_EMPTY + 4), lane, rank, true);
    const Role ro = get_role();
#pragma unroll
    for (int e = 0; e < 2; e++) {
      uint8_t* gz = g_xs + (size_t)(ro.h * 8 + ro.j) * CV_BYTES + (16 + 16 * (4 * wq + 2 * e + ((e ^ w) & 1))) * 16 + ln * 4;
      *reinterpret_cast<uint32_t*>(gz) = z[e][0];
      *reinterpret_cast<uint32_t*>(gz + 128) = z[e][1];
    }
    warp_arrive(bar_addr(sb, B_CONV), lane);
#pragma unroll
    for (int i = 0; i < 128; i++) acc[i] = 0.f;
  }
  TS(15);
  TR(10);
  Ring r{0, 1};
  auto take = [&]() { const uint32_t sl = r.slot; mbar_wait(bar_addr(sb, B_RG_FULL + sl), r.phase); r.next(); return sl; };
  constexpr float SC = 0.0625f * 1.4426950408889634f;
#pragma unroll 1
  for (int which = 0; which < 2; which++) {
    if (which == 1) {
      uint32_t xaddr = 0, xs = 0, pw = 0, px = 0;
#pragma unroll 1
      for (int kc = 0; kc < 7; kc++) {
        const uint32_t ws = take();
        if (kc == 0 || (kc & 1)) { xs = take(); xaddr = sb + xs * SLOT + (w ^ 1) * 8192; } else xaddr += 16384;
        TR(11);
        const uint64_t da = desc_k(xaddr), db = desc_mn(sb + ws * SLOT);
        turn_begin();
        wg_fence();
#pragma unroll
        for (int kk = 0; kk < 4; kk++) wgmma_ss_n256_tb(acc, desc_add(da, kk * 32), desc_add(db, kk * 2048), (kc | kk) != 0);
        wg_commit();
        turn_end();
        TR(13);
        wg_wait<1>();
        if (kc > 0) {
          release(bar_addr(sb, B_RG_EMPTY + pw), lane, rank, false);
          if (kc & 1) release(bar_addr(sb, B_RG_EMPTY + px), lane, rank, false);
        }
        pw = ws; px = xs;
        const int cb = kc - CTX_K;
        if (cb >= 1 && cb <= 4) { fence_async_smem(); warp_arrive(bar_addr(sb, B_CTXS + 4 * w + cb - 1), lane); }
        if (cb == 0) store_blocks<0, 1>(qreg, lb, pk);
        else if (cb == 1) store_blocks<16, 1>(qreg + 8192, lb, pk);
        else if (cb == 2) store_blocks<32, 1>(qreg + 16384, lb, pk);
        else if (cb == 3) store_blocks<48, 1>(qreg + 24576, lb, pk);
        TR(15);
      }
      mbar_wait(st_empty, 0);
      wg_wait<0>();
      reg_fence(acc);
      TS(61); TR(16);
      release(bar_addr(sb, B_RG_EMPTY + pw), lane, rank, false);
      release(bar_addr(sb, B_RG_EMPTY + px), lane, rank, false);
#pragma unroll
      for (int i = 0; i < 64; i++) pk[i] = pack_bf16(acc[2 * i], acc[2 * i + 1]);
      store_blocks<0, 4>(qreg, lb, pk);
      fence_async_smem();
      TS(9); TR(19);
      qt = 15 - qt;
    }
    float s[32];
#pragma unroll
    for (int i = 0; i < 32; i++) s[i] = 0.f;
    uint32_t pa[16];
    float m0 = -INFINITY, m1 = -INFINITY, l0 = 0.f, l1 = 0.f;
    const uint64_t dq = desc_k(qreg);
    uint64_t dk = 0, dqq = 0, dv = 0;
    auto prep_qk = [&](uint32_t kaddr) { dk = desc_k(kaddr); dqq = dq + (kaddr >> 31); asm volatile("" : "+l"(dk), "+l"(dqq)); };
    auto prep_pv = [&](uint32_t vaddr) { dv = desc_mn(vaddr); asm volatile("" : "+l"(dv)); };
    auto issue_qk = [&]() {
#pragma unroll
      for (int kk = 0; kk < 16; kk++)
        wgmma_ss_n64(s, desc_add(dqq, (kk >> 2) * 8192 + (kk & 3) * 32), desc_add(dk, (kk >> 2) * 8192 + (kk & 3) * 32), kk != 0);
    };
    auto issue_pv = [&](int accumulate) {
#pragma unroll
      for (int kk = 0; kk < 4; kk++)
        wgmma_rs_n256_tb(acc, pa[4 * kk], pa[4 * kk + 1], pa[4 * kk + 2], pa[4 * kk + 3], desc_add(dv, kk * 2048), accumulate | kk);
    };
    auto mask_diag = [&]() {
      const int d = (int)((lb >> 11) << 4) + (lane >> 2) - 2 * (lane & 3);
#pragma unroll
      for (int jj = 0; jj < 8; jj++) {
        if (8 * jj > d)     s[4 * jj]     = -INFINITY;
        if (8 * jj + 1 > d) s[4 * jj + 1] = -INFINITY;
        if (8 * jj - 8 > d) s[4 * jj + 2] = -INFINITY;
        if (8 * jj - 7 > d) s[4 * jj + 3] = -INFINITY;
      }
    };
    float a0, a1;
    auto softmax = [&]() -> bool {
      float x0 = fmaxf(s[0], s[1]), x1 = fmaxf(s[2], s[3]);
#pragma unroll
      for (int jj = 1; jj < 8; jj++) {
        x0 = fmaxf(x0, fmaxf(s[4 * jj], s[4 * jj + 1]));
        x1 = fmaxf(x1, fmaxf(s[4 * jj + 2], s[4 * jj + 3]));
      }
      x0 = fmaxf(x0, __shfl_xor_sync(0xffffffffu, x0, 1));
      x1 = fmaxf(x1, __shfl_xor_sync(0xffffffffu, x1, 1));
      x0 = fmaxf(x0, __shfl_xor_sync(0xffffffffu, x0, 2));
      x1 = fmaxf(x1, __shfl_xor_sync(0xffffffffu, x1, 2));
      const bool grow = __any_sync(0xffffffffu, fmaxf(x0 - m0, x1 - m1) * SC > 8.f);
      if (grow) {
        x0 = fmaxf(x0, m0); x1 = fmaxf(x1, m1);
        a0 = ex2((m0 - x0) * SC); a1 = ex2((m1 - x1) * SC);
        m0 = x0; m1 = x1;
        l0 *= a0; l1 *= a1;
      }
      const float b0 = -m0 * SC, b1 = -m1 * SC;
      float t0 = 0.f, t1 = 0.f, t2 = 0.f, t3 = 0.f;
#pragma unroll
      for (int jj = 0; jj < 8; jj++) {
        s[4 * jj]     = ex2(fmaf(s[4 * jj], SC, b0));
        s[4 * jj + 1] = ex2(fmaf(s[4 * jj + 1], SC, b0));
        s[4 * jj + 2] = ex2(fmaf(s[4 * jj + 2], SC, b1));
        s[4 * jj + 3] = ex2(fmaf(s[4 * jj + 3], SC, b1));
        t0 += s[4 * jj]; t1 += s[4 * jj + 1]; t2 += s[4 * jj + 2]; t3 += s[4 * jj + 3];
      }
      l0 += t0 + t1; l1 += t2 + t3;
      return grow;
    };
    auto softmax_fast = [&]() -> bool {
      const float b0 = -m0 * SC, b1 = -m1 * SC;
      float t0 = 0.f, t1 = 0.f, t2 = 0.f, t3 = 0.f;
#pragma unroll
      for (int jj = 0; jj < 8; jj++) {
        s[4 * jj]     = ex2(fmaf(s[4 * jj], SC, b0));
        s[4 * jj + 1] = ex2(fmaf(s[4 * jj + 1], SC, b0));
        s[4 * jj + 2] = ex2(fmaf(s[4 * jj + 2], SC, b1));
        s[4 * jj + 3] = ex2(fmaf(s[4 * jj + 3], SC, b1));
        t0 += s[4 * jj]; t1 += s[4 * jj + 1]; t2 += s[4 * jj + 2]; t3 += s[4 * jj + 3];
      }
      t0 += t1; t2 += t3;
      uint32_t redo;
      asm volatile("{\n.reg .pred p, q;\nsetp.le.f32 p, %1, 0f47800000;\nbarrier.cta.red.or.aligned.pred q, %2, 128, !p;\nselp.u32 %0, 1, 0, q;\n}"
                   : "=r"(redo) : "f"(fmaxf(t0, t2) + (t0 - t0) + (t2 - t2)), "r"(RED_BAR + w) : "memory");
      if (!redo) { l0 += t0; l1 += t2; }
      return redo;
    };
    auto rescale = [&]() {
#pragma unroll
      for (int i = 0; i < 32; i++) { acc[4 * i] *= a0; acc[4 * i + 1] *= a0; acc[4 * i + 2] *= a1; acc[4 * i + 3] *= a1; }
    };
    auto to_p = [&]() {
#pragma unroll
      for (int i = 0; i < 16; i++) pa[i] = pack_bf16(s[2 * i], s[2 * i + 1]);
    };

    const bool up = w == which;
    const int n = 2 * qt + 2, nw = n - up, npriv = num_private(qt);
    int fd = which ? 0 : 2 * n - 1;
    const int dir = which ? 1 : -1;
    auto skip = [&]() { r.next(); fd += dir; };
    auto give = [&](uint32_t sl, int d) {
      if (lane < 2) mbar_arrive_remote_n(bar_addr(sb, B_RG_EMPTY + sl), d < npriv ? rank : rank ^ lane, (d & ~2) == 0 ? 2 : 1);
    };
    if (which && up) skip();
    uint32_t ks = take();
    TS(62 + which);
    TR(20);
    prep_qk(sb + ks * SLOT);
    turn_begin();
    wg_fence();
    issue_qk();
    wg_commit();
    turn_end();
    TR(21);
    wg_wait<0>();
    TR(22);
    reg_fence(s);
    give(ks, fd);
    fd += dir;
    if (which && up) skip();
    if (which && nw == 1 && lane == 0) mbar_arrive(bar_addr(sb, B_QFREE + w));
    if (which || nw == 1) mask_diag();
    softmax();
    to_p();
#pragma unroll 1
    for (int jj = 1; jj < nw; jj++) {
      ks = take();
      const uint32_t vs = take();
      TR(30);
      prep_qk(sb + ks * SLOT);
      prep_pv(sb + vs * SLOT);
      turn_begin();
      wg_fence();
      issue_qk();
      wg_commit();
      issue_pv(jj > 1);
      wg_commit();
      turn_end();
      TR(31);
      wg_wait<1>();
      TR(32);
      reg_fence(s);
      const bool diag = !which && jj == nw - 1;
      if (diag) mask_diag();
      bool grow = false;
      if (softmax_fast()) {
#pragma unroll 1
        for (int kb = 0; kb < 4; kb++) {
          const uint64_t da = desc_k(qreg + kb * 8192), db = desc_k(sb + ks * SLOT + kb * 8192);
          wg_fence();
#pragma unroll
          for (int kk = 0; kk < 4; kk++) wgmma_ss_n64(s, desc_add(da, kk * 32), desc_add(db, kk * 32), (kb | kk) != 0);
          wg_commit();
          wg_wait<0>();
          reg_fence(s);
        }
        if (diag) mask_diag();
        grow = softmax();
      }
      give(ks, fd);
      if (which && jj == nw - 1 && lane == 0) mbar_arrive(bar_addr(sb, B_QFREE + w));
      wg_wait<0>();
      reg_fence(acc);
      reg_fence(pa);
      give(vs, fd + dir);
      fd += 2 * dir;
      if (grow) rescale();
      to_p();
    }
    if (!which && up) skip();
    const uint32_t vs = take();
    TR(40);
    prep_pv(sb + vs * SLOT);
    turn_begin();
    wg_fence();
    issue_pv(nw > 1);
    wg_commit();
    turn_end();
    TR(41);
    l0 += __shfl_xor_sync(0xffffffffu, l0, 1); l1 += __shfl_xor_sync(0xffffffffu, l1, 1);
    l0 += __shfl_xor_sync(0xffffffffu, l0, 2); l1 += __shfl_xor_sync(0xffffffffu, l1, 2);
    float i0 = 1.f / l0, i1 = 1.f / l1;
    asm volatile("" : "+f"(i0), "+f"(i1) :: "memory");
    wg_wait<0>();
    TR(42);
    reg_fence(acc);
    reg_fence(pa);
    give(vs, fd);
    if (!which && up) r.next();
    TS(7 + 3 * which);
#pragma unroll
    for (int i = 0; i < 32; i++) {
      pk[2 * i]     = pack_bf16(acc[4 * i] * i0, acc[4 * i + 1] * i0);
      pk[2 * i + 1] = pack_bf16(acc[4 * i + 2] * i1, acc[4 * i + 3] * i1);
    }
    TS(8 + 3 * which); TR(46);
    if (which == 0) TS(31);
  }

  {
    float oa[32], ob[32];
#pragma unroll
    for (int i = 0; i < 32; i++) { oa[i] = 0.f; ob[i] = 0.f; }
    auto stage_o = [&](float (&o)[32], int ch) {
      reg_fence(o);
      uint32_t q[16];
#pragma unroll
      for (int i = 0; i < 16; i++) q[i] = pack_bf16(o[2 * i], o[2 * i + 1]);
      if (ch >= 2) mbar_wait(bar_addr(sb, B_S2_EMPTY + w * 2 + (ch & 1)), ((ch >> 1) - 1) & 1);
      store_blocks<0, 1>(qreg + (ch & 1) * 8192, lb, q);
    };
    auto hand_over = [&](int ch) {
      fence_async_smem();
      warp_arrive(bar_addr(sb, B_S2_FULL + w * 2 + (ch & 1)), lane);
    };
    uint32_t pk2[64];
#pragma unroll
    for (int i = 0; i < 64; i++) pk2[i] = 0;
    uint32_t p2 = 0;
    auto chunk = [&](int ch, float (&o)[32], float (&oprev)[32]) {
      const uint32_t s1 = take();
      TR(50);
      const uint64_t d1 = desc_mn(sb + s1 * SLOT);
      turn_begin();
      wg_fence();
#pragma unroll
      for (int kk = 0; kk < 16; kk++) {
        wgmma_rs_n64_tb(o, pk[4 * kk], pk[4 * kk + 1], pk[4 * kk + 2], pk[4 * kk + 3], desc_add(d1, kk * 2048), kk != 0);
        if (kk == ARRIVE_KK) turn_end();
      }
      wg_commit();
      TR(51);
      if (ch >= 1) {
        wg_wait<1>();
        if (ch <= 4) release(bar_addr(sb, B_RG_EMPTY + p2), lane, rank, true);
        stage_o(oprev, ch - 1);
      } else {
        mbar_wait(bar_addr(sb, B_CTXF + w), 0);
#pragma unroll
        for (int kk = 0; kk < 16; kk++) {
          uint32_t f[4];
          ldsm4(f, qreg + (kk >> 2) * 8192 + (lb ^ ((kk & 3) << 5)));
          pk2[4 * kk] = f[0]; pk2[4 * kk + 1] = f[1]; pk2[4 * kk + 2] = f[2]; pk2[4 * kk + 3] = f[3];
        }
      }
      const uint32_t s2 = take();
      TR(53);
      const uint64_t d2 = desc_mn(sb + s2 * SLOT);
      turn_begin();
      wg_fence();
#pragma unroll
      for (int kk = 0; kk < 16; kk++) {
        wgmma_rs_n64_tb(o, pk2[4 * kk], pk2[4 * kk + 1], pk2[4 * kk + 2], pk2[4 * kk + 3], desc_add(d2, kk * 2048), 1);
        if (kk == ARRIVE_KK && (ch < 6 || w == 1)) turn_end();
      }
      wg_commit();
      TR(54);
      if (ch >= 1) hand_over(ch - 1);
      wg_wait<1>();
      TR(55);
      if (ch <= 4) release(bar_addr(sb, B_RG_EMPTY + s1), lane, rank, true);
      p2 = s2;
    };
#pragma unroll 1
    for (int ch = 0; ch < 6; ch += 2) { chunk(ch, oa, ob); chunk(ch + 1, ob, oa); }
    chunk(6, oa, ob);
    wg_wait<0>();
    TR(58);
    reg_fence(pk);
    reg_fence(pk2);
    stage_o(oa, 6);
    hand_over(6);
  }
  TS(12); TR(59);
  if ((threadIdx.x & 127) == 0) GT(54 + w);

  TS(16); TS(18); TS(17);
  TR(99); TR_END();
  TS(13); TSG(14);
}

#define CONV_STAGGER_NS 1200
namespace ssm {
constexpr int GROUPS = D_SPARE / 8 / NCONV;
constexpr uint32_t ZROWS = 16;
constexpr uint32_t CHAN = (ZROWS + 256 + 1) * 16;
constexpr uint32_t XBUF = 8 * CHAN;
constexpr uint32_t OFF_X = 0;
constexpr uint32_t HCOPY = 4160;
constexpr uint32_t OFF_H = 2 * XBUF;
constexpr uint32_t HWARP = 3 * HCOPY;
constexpr uint32_t IO_K = 128, IO_V = IO_K + 4096, IO_Q = IO_V + 4096, IOBUF = IO_Q + 4096;
constexpr uint32_t OFF_IO = (OFF_H + 8 * HWARP + 127) / 128 * 128;
constexpr uint32_t END = OFF_IO + 4 * IOBUF;
static_assert(IOBUF % 128 == 0 && OFF_H % 16 == 0, "TMA destination alignment");
static_assert(END <= BARS, "smem");
enum : uint32_t { B_XREADY = 0, B_ZDONE = 2, B_KV = 4, B_Q = 8, B_HRAW = 12, B_QLAST = 20 };
constexpr int CW_BAR = 4;

__device__ __forceinline__ int group_d0(int cidx, int grp) { return (grp * NCONV + cidx) * 8; }
__device__ __forceinline__ uint32_t x_lane(int lane) { return (lane & 7) * CHAN + (ZROWS + (lane >> 3)) * 16; }
__device__ __forceinline__ uint32_t t_lane(int lane) { return (uint32_t)(8 * (lane >> 3) + 7 - (lane & 7)) * 16; }
struct Taps { uint32_t s[4]; };
__device__ __forceinline__ Taps load_taps(const Params& p, int d0, int c) {
  const uint2 s0 = __ldg(reinterpret_cast<const uint2*>(p.a_shift + (d0 + 2 * c) * 4)), s1 = __ldg(reinterpret_cast<const uint2*>(p.a_shift + (d0 + 2 * c + 1) * 4));
  return Taps{{__byte_perm(s0.x, s1.x, 0x5410), __byte_perm(s0.x, s1.x, 0x7632), __byte_perm(s0.y, s1.y, 0x5410), __byte_perm(s0.y, s1.y, 0x7632)}};
}
__device__ __forceinline__ uint32_t short_conv(const Taps& t, uint32_t k0, uint32_t k1, uint32_t k2, uint32_t k3, uint32_t v) {
  return bmul(bfma(k3, t.s[0], bfma(k2, t.s[1], bfma(k1, t.s[2], bmul(k0, t.s[3])))), v);
}
__device__ __forceinline__ void gate_chunk(uint32_t xa, uint32_t qa) {
#pragma unroll 4
  for (int i = 0; i < 8; i++) {
    uint32_t zz[4], qq[4];
    ldsm4t(zz, xa + i * 64);
    ldsm4(qq, qa + i * 512);
    stsm4(qa + i * 512, bmul(qq[0], zz[0]), bmul(qq[1], zz[1]), bmul(qq[2], zz[2]), bmul(qq[3], zz[3]));
  }
}

__device__ __forceinline__ void io_warp(const Params& p, uint32_t sb, int cidx, int wq) {
  const int lane = threadIdx.x & 31;
  const uint32_t io = sb + OFF_IO + wq * IOBUF, bkv = bar_addr(sb, B_KV + wq), bq = bar_addr(sb, B_Q + wq);
  auto load_kv = [&](int e) {
    __syncwarp();
    if (lane != 0) return;
    const int d0 = group_d0(cidx, e >> 1), row = (2 * wq + (e & 1)) * 256;
    if (e < 2 * GROUPS) {
      mbar_expect_tx(bkv, IO_Q);
      tma_ld2(io, &p.ak8, bkv, d0, row - 8);
      tma_ld2(io + IO_K, &p.ak, bkv, d0, row);
      tma_ld2(io + IO_V, &p.av, bkv, d0, row);
    } else {
      const uint32_t bar = bar_addr(sb, B_QLAST + 2 * wq + 1);
      mbar_expect_tx(bar, 4096);
      tma_ld2(io + IO_K, &p.aq, bar, group_d0(cidx, GROUPS - 1), row + 256);
    }
  };
  auto load_q = [&](int e) {
    __syncwarp();
    if (lane != 0) return;
    const uint32_t bar = e < 2 * GROUPS - 2 ? bq : bar_addr(sb, B_QLAST + 2 * wq);
    mbar_expect_tx(bar, 4096);
    tma_ld2(io + IO_Q, &p.aq, bar, group_d0(cidx, e >> 1), (2 * wq + (e & 1)) * 256);
  };
  TR_DECL;
  TR(0);
  load_kv(0);
  const uint32_t xl = sb + OFF_X + x_lane(lane) + wq * 1024, tl = io + t_lane(lane);
#pragma unroll 1
  for (int grp = -2; grp + 1 < GROUPS; grp++) {
    const bool more = grp + 2 < GROUPS;
    const Taps taps = load_taps(p, group_d0(cidx, more ? grp + 2 : 0), lane & 3);
    PCLK(c0);
    if (grp >= 0) mbar_wait_nap(bar_addr(sb, B_ZDONE + (grp & 1)), (grp >> 1) & 1);
    PACC(tp, c0);
    PCLK(c1);
    TR(80);
#pragma unroll 1
    for (int i = 0; i < 2; i++) {
      const uint32_t xa = xl + (grp & 1) * XBUF + i * 512;
      if (grp >= 0) {
        mbar_wait_nap(bq, i);
        TR(81);
        gate_chunk(xa, tl + IO_Q);
      }
      if (more) {
        TR(82);
        mbar_wait_nap(bkv, i);
        TR(83);
#pragma unroll 2
        for (int u = 0; u < 8; u++) {
          const uint32_t ka = tl + IO_K + u * 512;
          uint32_t k0[4], k1[4], k2[4], k3[4], vv[4];
          ldsm4(k0, ka - 48); ldsm4(k1, ka - 32); ldsm4(k2, ka - 16); ldsm4(k3, ka); ldsm4(vv, ka + 4096);
          stsm4t(xa + u * 64, short_conv(taps, k0[0], k1[0], k2[0], k3[0], vv[0]), short_conv(taps, k0[1], k1[1], k2[1], k3[1], vv[1]),
                 short_conv(taps, k0[2], k1[2], k2[2], k3[2], vv[2]), short_conv(taps, k0[3], k1[3], k2[3], k3[3], vv[3]));
        }
        load_kv(2 * (grp + 2) + i + 1);
        TR(84);
        if (i == 1) warp_arrive(bar_addr(sb, B_XREADY + (grp & 1)), lane);
      }
      if (grp >= 0) {
        fence_async_smem();
        __syncwarp();
        if (lane == 0) {
          tma_st2(&p.ao, io + IO_Q, group_d0(cidx, grp), (2 * wq + i) * 256);
          bulk_commit();
          bulk_wait_read();
        }
      }
      if (2 * grp + i + 1 >= 0) load_q(2 * grp + i + 1);
      TR(85);
    }
    PACC(te, c1);
  }
  if (lane == 0) bulk_wait_all();
  TR(99); TR_END();
}

__device__ __forceinline__ void conv_warp(const Params& p, uint32_t sb, int cidx, int ch) {
  const int lane = threadIdx.x & 31;
  const uint32_t hE0 = sb + OFF_H + ch * HWARP, hO = hE0 + HCOPY;
  const uint32_t hbar = bar_addr(sb, B_HRAW + ch);
  auto fetch_h = [&](int grp) {
    if (lane == 0) {
      mbar_expect_tx(hbar, 4096);
      asm volatile("cp.async.bulk.shared::cluster.global.mbarrier::complete_tx::bytes [%0], [%1], %2, [%3];"
                   :: "r"(hE0 + (grp & 1) * 2 * HCOPY + 32), "l"(p.a_ssmk + (size_t)(group_d0(cidx, grp) + ch) * SEQ), "r"(4096), "r"(hbar) : "memory");
    }
  };
  TR_DECL;
  TR(0);
  fetch_h(0);
#pragma unroll 1
  for (int grp = 0; grp < GROUPS; grp++) {
    const uint32_t xc = sb + OFF_X + (grp & 1) * XBUF + ch * CHAN;
    const uint32_t Dd = (uint32_t)__ldg(reinterpret_cast<const unsigned short*>(p.a_D + group_d0(cidx, grp) + ch)) * 0x10001u;
    PCLK(k0);
    mbar_wait(hbar, grp & 1);
    const uint32_t hE = hE0 + (grp & 1) * 2 * HCOPY;
    if (grp + 1 < GROUPS) fetch_h(grp + 1);
#pragma unroll
    for (int i = 0; i < 8; i++) {
      const uint32_t o = 32 + (i * 32 + lane) * 16;
      const uint4 w = lds16(hE + o);
      const uint32_t nx = lds4(hE + o + 16);
      sts16(hO + o, __byte_perm(w.x, w.y, 0x5432), __byte_perm(w.y, w.z, 0x5432), __byte_perm(w.z, w.w, 0x5432), __byte_perm(w.w, nx, 0x5432));
      if (o == 32) asm volatile("st.shared.u32 [%0], %1;" :: "r"(hO + 28), "r"(w.x << 16) : "memory");
    }
    __syncwarp();
    const uint32_t ha = cv_h_lane(lane, hE, hO), xa = xc + cv_x_lane(lane);
    TR(71);
    mbar_wait(bar_addr(sb, B_XREADY + (grp & 1)), (grp >> 1) & 1);
    TR(72);
    if (grp == 0 && ch >= 4) __nanosleep(CONV_STAGGER_NS);
    PACC(tw, k0);
    PCLK(k1);
    float acc[16][4];
#pragma unroll
    for (int i = 0; i < 16; i++) { acc[i][0] = 0.f; acc[i][1] = 0.f; acc[i][2] = 0.f; acc[i][3] = 0.f; }
#pragma unroll 1
    for (int r = 0; r < 8; r++) {
      uint32_t fx[16][4], fh[16][2];
#pragma unroll
      for (int i = 0; i < 16; i++) { fh[i][0] = lds4(ha + i * 256 + r * 32); fh[i][1] = lds4(ha + i * 256 + r * 32 + 16); }
#pragma unroll
      for (int i = 0; i < 16; i++) ldsm4(fx[i], xa + i * 256 - r * 32);
#pragma unroll
      for (int sx = 0; sx < 16; sx++)
#pragma unroll
        for (int jj = 0; jj < 16 - sx; jj++) mma16816(acc[jj + sx], fx[sx], fh[jj][0], fh[jj][1]);
    }
    PACC(tm, k1);
    PCLK(k2);
    TR(73);
#pragma unroll
    for (int i = 0; i < 8; i++) {
      uint32_t x[4];
      const uint32_t ad = xc + (ZROWS + lane) * 16 + i * 512;
      ldsm4(x, ad);
      stsm4(ad, badd(pack_bf16(acc[2 * i][0], acc[2 * i][1]), bmul(x[0], Dd)), badd(pack_bf16(acc[2 * i][2], acc[2 * i][3]), bmul(x[1], Dd)),
            badd(pack_bf16(acc[2 * i + 1][0], acc[2 * i + 1][1]), bmul(x[2], Dd)), badd(pack_bf16(acc[2 * i + 1][2], acc[2 * i + 1][3]), bmul(x[3], Dd)));
    }
    if (grp + 1 < GROUPS) warp_arrive(bar_addr(sb, B_ZDONE + (grp & 1)), lane);
    PACC(tr, k2);
    TR(74);
  }
  {
    mbar_wait(bar_addr(sb, B_QLAST + ch), 0);
    named_sync(CW_BAR, 256);
    TR(75);
    const uint32_t qb = sb + OFF_IO + (ch >> 1) * IOBUF + ((ch & 1) ? IO_K : IO_Q);
    gate_chunk(sb + OFF_X + ((GROUPS - 1) & 1) * XBUF + x_lane(lane) + ch * 512, qb + t_lane(lane));
    fence_async_smem();
    __syncwarp();
    if (lane == 0) { tma_st2(&p.ao, qb, group_d0(cidx, GROUPS - 1), ch * 256); bulk_commit(); bulk_wait_all(); }
    TR(99); TR_END();
  }
}

__device__ __forceinline__ void init(uint32_t sb) {
  if (threadIdx.x < 16 * ZROWS) sts16(sb + OFF_X + (threadIdx.x >> 4) * CHAN + (threadIdx.x & 15) * 16, 0, 0, 0, 0);
  if (threadIdx.x < 96) sts16(sb + OFF_H + (threadIdx.x >> 2) * HCOPY + (threadIdx.x & 1) * 16 + ((threadIdx.x & 2) ? 4128 : 0), 0, 0, 0, 0);
  if (threadIdx.x == 0) {
    for (int i = 0; i < 2; i++) { mbar_init(bar_addr(sb, B_XREADY + i), 4); mbar_init(bar_addr(sb, B_ZDONE + i), 8); }
    for (int i = 0; i < 4; i++) { mbar_init(bar_addr(sb, B_KV + i), 1); mbar_init(bar_addr(sb, B_Q + i), 1); }
    for (int i = 0; i < 8; i++) { mbar_init(bar_addr(sb, B_HRAW + i), 1); mbar_init(bar_addr(sb, B_QLAST + i), 1); }
    fence_async_smem();
  }
}
}

__device__ __forceinline__ void ssm_side_work(const Params& p, uint32_t sb, unsigned epoch) {
  const Role ro = get_role();
  const int h = ro.h, j = ro.j;
  const int lane = threadIdx.x & 31, g = lane >> 2, c = lane & 3;
  const int d0 = D_SPARE + 8 * h;
  uint8_t* xs = g_xs + (size_t)(h * 8 + g) * CV_BYTES + c * 4;
  auto xrow = [&](int beta) { return xs + (16 + beta) * 16; };
  {
    const uint4* hp = reinterpret_cast<const uint4*>(p.a_ssmk + (size_t)(d0 + j) * SEQ) + lane;
    uint8_t* he = g_xs + (size_t)(h * 8 + j) * CV_BYTES + CV_HE;
#pragma unroll 2
    for (int i = 0; i < 8; i++) {
      const uint4 wv = __ldg(hp + i * 32);
      const uint32_t nx = i * 32 + lane < 255 ? __ldg(reinterpret_cast<const uint32_t*>(hp + i * 32 + 1)) : 0u;
      const uint32_t o = 32 + (i * 32 + lane) * 16;
      *reinterpret_cast<uint4*>(he + o) = wv;
      *reinterpret_cast<uint4*>(he + CV_HCOPY + o) =
          make_uint4(__byte_perm(wv.x, wv.y, 0x5432), __byte_perm(wv.y, wv.z, 0x5432), __byte_perm(wv.z, wv.w, 0x5432), __byte_perm(wv.w, nx, 0x5432));
      if (o == 32) *reinterpret_cast<uint32_t*>(he + CV_HCOPY + 28) = wv.x << 16;
    }
    if (lane == 0) *reinterpret_cast<uint32_t*>(he + CV_D - CV_HE) = (uint32_t)__ldg(reinterpret_cast<const unsigned short*>(p.a_D + d0 + j)) * 0x10001u;
  }
  {
    const ssm::Taps taps = ssm::load_taps(p, d0, c);
    const uint32_t* kp = reinterpret_cast<const uint32_t*>(p.a_k + (size_t)(256 * j + 7 - g) * DA + d0) + c;
    const uint32_t* vp = reinterpret_cast<const uint32_t*>(p.a_v + (size_t)(256 * j + 7 - g) * DA + d0) + c;
    uint32_t kprev = j > 0 ? __ldg(kp - 8 * (DA / 2)) : 0u;
#pragma unroll 1
    for (int i0 = 0; i0 < 32; i0 += 8) {
      uint32_t kk[8], vv[8];
#pragma unroll
      for (int i = 0; i < 8; i++) { kk[i] = __ldg(kp + (i0 + i) * 8 * (DA / 2)); vv[i] = __ldg(vp + (i0 + i) * 8 * (DA / 2)); }
#pragma unroll
      for (int i = 0; i < 8; i++) {
        const uint32_t k2 = __shfl_sync(0xffffffffu, g < 1 ? kprev : kk[i], (lane + 4) & 31);
        const uint32_t k1 = __shfl_sync(0xffffffffu, g < 2 ? kprev : kk[i], (lane + 8) & 31);
        const uint32_t k0 = __shfl_sync(0xffffffffu, g < 3 ? kprev : kk[i], (lane + 12) & 31);
        *reinterpret_cast<uint32_t*>(xrow(32 * j + i0 + i)) = transpose8(ssm::short_conv(taps, k0, k1, k2, kk[i], vv[i]));
        kprev = kk[i];
      }
    }
    __syncwarp();
    if (lane == 0) {
      flag_signal(&g_flags.xs_ready[h].v);
      flag_wait(&g_flags.xs_ready[h].v, 8, epoch);
      fence_async_all();
      mbar_arrive(bar_addr(sb, B_XS));
    }
  }
  if (lane == 0) {
    for (int i = 0; i < 2; i++) {
      flag_wait(&g_flags.kv_ready[2 * h + i].v, 16, epoch);
      fence_async_all();
      mbar_arrive(bar_addr(sb, B_KV + i));
      if (PF_CV && i == 0) bulk_prefetch(g_xs + (size_t)(h * 8 + j) * CV_BYTES, CV_BYTES);
    }
    mbar_wait(bar_addr(sb, B_CONV), 0);
    flag_signal(&g_flags.zs_ready[h].v);
    flag_wait(&g_flags.zs_ready[h].v, 8, epoch);
    asm volatile("red.relaxed.gpu.global.add.u64 [%0], 1;" :: "l"(&g_flags.done) : "memory");
  }
  __syncwarp();
  fence_async_all();
  const uint32_t qb = q_region(sb, 1) + 16384, zb = qb + 4096, bar = bar_addr(sb, B_GATE);
  constexpr uint32_t ZCH = 528;
  mbar_wait_slow(bar_addr(sb, B_GFREE), 0);
  if (lane == 0) { mbar_expect_tx(bar, 8192); tma_ld2(qb, &p.aq, bar, d0, 256 * j); }
  __syncwarp();
  if (lane < 8) bulk_ld(zb + lane * ZCH, g_xs + (size_t)(h * 8 + lane) * CV_BYTES + (16 + 32 * j) * 16, 512, bar);
  mbar_wait(bar, 0);
  ssm::gate_chunk(zb + (lane & 7) * ZCH + (lane >> 3) * 16, qb + ssm::t_lane(lane));
  fence_async_smem();
  __syncwarp();
  if (lane == 0) { tma_st2(&p.ao, qb, d0, 256 * j); bulk_commit(); bulk_wait_all(); }
}

__global__ void __cluster_dims__(2, 1, 1) __launch_bounds__(NTHREADS, 1)
concat_heads__ssm_conv_h3__compressed_kv_cla__prompt_kernel(const __grid_constant__ Params p) {
  extern __shared__ uint8_t smem_raw[];
  const uint32_t sb = (smem_u32(smem_raw) + 1023) & ~1023u;
  const int warp = __shfl_sync(0xffffffffu, threadIdx.x >> 5, 0);
  const int wg = warp >> 2;
  const int cta = blockIdx.x;
  const bool attn = cta < NMAIN;
  if (!attn) ssm::init(sb);
  if (attn && threadIdx.x == 0) {
    for (int i = 0; i < 4; i++) { mbar_init(bar_addr(sb, B_P1_FULL + i), 1); mbar_init(bar_addr(sb, B_P1_EMPTY + i), 16); }
    for (int i = 0; i < NSLOT; i++) {
      mbar_init(bar_addr(sb, B_RG_FULL + i), 1); mbar_init(bar_addr(sb, B_RG_EMPTY + i), 16); mbar_init(bar_addr(sb, B_PFREE + i), 1);
    }
    for (int i = 0; i < 2; i++) { mbar_init(bar_addr(sb, B_ST_FULL + i), 4); mbar_init(bar_addr(sb, B_ST_EMPTY + i), 1); }
    mbar_init(bar_addr(sb, B_XS), 1); mbar_init(bar_addr(sb, B_CONV), 8); mbar_init(bar_addr(sb, B_GATE), 1); mbar_init(bar_addr(sb, B_GFREE), 1);
    mbar_init(bar_addr(sb, B_KV), 1); mbar_init(bar_addr(sb, B_KV + 1), 1);
    for (int i = 0; i < 8; i++) mbar_init(bar_addr(sb, B_CTXS + i), 4);
    for (int i = 0; i < 4; i++) { mbar_arrive(bar_addr(sb, B_RG_FULL + i)); if (i < 3) mbar_arrive_n(bar_addr(sb, B_RG_EMPTY + i), 16); }
    for (int i = 0; i < 4; i++) { mbar_init(bar_addr(sb, B_S2_FULL + i), 4); mbar_init(bar_addr(sb, B_S2_EMPTY + i), 1); }
    for (int i = 0; i < 2; i++) { mbar_init(bar_addr(sb, B_QFREE + i), 4); mbar_init(bar_addr(sb, B_CTXF + i), 1); }
    asm volatile("fence.mbarrier_init.release.cluster;" ::: "memory");
  }
  if (attn && threadIdx.x == 32) {
    prefetch_map(&p.ckv); prefetch_map(&p.wuk); prefetch_map(&p.wuv); prefetch_map(&p.x); prefetch_map(&p.wq);
    prefetch_map(&p.kv); prefetch_map(&p.part); prefetch_map(&p.wo); prefetch_map(&p.ctx);
  }
  __syncwarp();
  asm volatile("barrier.cluster.arrive.release.aligned;" ::: "memory");
  if (attn && threadIdx.x == 0) {
    const Role ro = get_role();
    const int h = ro.h, j = ro.j;
    for (int k = 0; k < EARLY_LD; k++) {
      const uint32_t full = bar_addr(sb, B_P1_FULL + k), dst = sb + k * P1_STAGE;
      mbar_expect_tx(full, P1_STAGE);
      tma_ld2(dst, &p.ckv, full, k * 64, 2 * j * 128);
      load_tile4(dst + 16384, &p.wuk, full, k * 64, h * 4, j & 1, false);
    }
  }
  __syncwarp();
  asm volatile("barrier.cluster.wait.acquire.aligned;" ::: "memory");

  const int lane = threadIdx.x & 31;
  if (wg == 0) {
    if (!attn) {
      asm volatile("setmaxnreg.dec.sync.aligned.u32 72;");
      if (threadIdx.x == 0) GT(0);
      if (p.out != nullptr) ssm::io_warp(p, sb, cta - NMAIN, fresh_warp());
      if (threadIdx.x == 0) GT(14);
      return;
    }
    asm volatile("setmaxnreg.dec.sync.aligned.u32 40;");
    if (warp == 0) {
      if (lane == 0) producer_main(p, sb);
    } else if (warp < 3) {
      storer_main(p, sb);
    } else {
      const unsigned epoch = load_epoch();
      mbar_wait(bar_addr(sb, B_P1_FULL + 3), 0);
      __nanosleep(SIDE_DELAY_NS);
      ssm_side_work(p, sb, epoch);
    }
  } else {
    if (!attn) {
      asm volatile("setmaxnreg.inc.sync.aligned.u32 216;");
      if (threadIdx.x == 128) { GT(12); PT(10); }
      if (p.out != nullptr) ssm::conv_warp(p, sb, cta - NMAIN, fresh_warp() - 4);
      if (threadIdx.x == 128) { PT(9); GT(13); }
      return;
    }
    asm volatile("setmaxnreg.inc.sync.aligned.u32 232;");
    if (p.out != nullptr) {
      consumer_main(p, sb);
    }
  }
}

typedef CUresult (*EncodeTiledFn)(CUtensorMap*, CUtensorMapDataType, cuuint32_t, void*, const cuuint64_t*, const cuuint64_t*,
                                  const cuuint32_t*, const cuuint32_t*, CUtensorMapInterleave, CUtensorMapSwizzle,
                                  CUtensorMapL2promotion, CUtensorMapFloatOOBfill);

void make_map(EncodeTiledFn enc, CUtensorMap* m, const void* ptr, int rank, const uint64_t* dims, const uint64_t* strides, const uint32_t* box) {
  cuuint64_t d[3], s[2]; cuuint32_t b[3], e[3] = {1, 1, 1};
  for (int i = 0; i < rank; i++) { d[i] = dims[i]; b[i] = box[i]; if (i) s[i - 1] = strides[i - 1]; }
  enc(m, CU_TENSOR_MAP_DATA_TYPE_BFLOAT16, rank, const_cast<void*>(ptr), d, s, b, e, CU_TENSOR_MAP_INTERLEAVE_NONE,
      CU_TENSOR_MAP_SWIZZLE_128B, CU_TENSOR_MAP_L2_PROMOTION_L2_256B, CU_TENSOR_MAP_FLOAT_OOB_FILL_NONE);
}
void map2(EncodeTiledFn enc, CUtensorMap* m, const void* ptr, uint64_t cols, uint64_t rows, uint32_t bc, uint32_t br) {
  const uint64_t dims[2] = {cols, rows}, st[1] = {cols * 2}; const uint32_t box[2] = {bc, br};
  make_map(enc, m, ptr, 2, dims, st, box);
}
void map2_plain(EncodeTiledFn enc, CUtensorMap* m, const void* ptr, uint64_t cols, uint64_t rows, uint32_t bc, uint32_t br) {
  cuuint64_t d[2] = {cols, rows}, st[1] = {cols * 2}; cuuint32_t b[2] = {bc, br}, e[2] = {1, 1};
  enc(m, CU_TENSOR_MAP_DATA_TYPE_BFLOAT16, 2, const_cast<void*>(ptr), d, st, b, e, CU_TENSOR_MAP_INTERLEAVE_NONE,
      CU_TENSOR_MAP_SWIZZLE_NONE, CU_TENSOR_MAP_L2_PROMOTION_L2_128B, CU_TENSOR_MAP_FLOAT_OOB_FILL_NONE);
}
void map3(EncodeTiledFn enc, CUtensorMap* m, const void* ptr, uint64_t rows, uint32_t nblk) {
  const uint64_t dims[3] = {64, rows, 64}, st[2] = {8192, 128}; const uint32_t box[3] = {64, 64, nblk};
  make_map(enc, m, ptr, 3, dims, st, box);
}

}

extern "C" void kernel_launch(void* const* d_in, const int* in_sizes, int n_in, void* d_out, int out_size) {
  (void)in_sizes; (void)n_in; (void)out_size;
  static EncodeTiledFn enc = nullptr;
  static void *kv_ptr = nullptr, *acc_ptr = nullptr;
  if (!enc) {
    void* fn = nullptr; cudaDriverEntryPointQueryResult qr;
    cudaGetDriverEntryPoint("cuTensorMapEncodeTiled", &fn, cudaEnableDefault, &qr);
    enc = (EncodeTiledFn)fn;
    cudaGetSymbolAddress(&kv_ptr, g_kv);
    cudaGetSymbolAddress(&acc_ptr, g_ctx);
    cudaFuncSetAttribute(concat_heads__ssm_conv_h3__compressed_kv_cla__prompt_kernel, cudaFuncAttributeMaxDynamicSharedMemorySize, SMEM_BYTES);
  }
  Params p;
  p.a_q = (const bf16*)d_in[0]; p.a_k = (const bf16*)d_in[1]; p.a_v = (const bf16*)d_in[2];
  map2_plain(enc, &p.aq, d_in[0], DA, SEQ, 8, 256);
  map2_plain(enc, &p.ak, d_in[1], DA, SEQ, 8, 256);
  map2_plain(enc, &p.ak8, d_in[1], DA, SEQ, 8, 8);
  map2_plain(enc, &p.av, d_in[2], DA, SEQ, 8, 256);
  map2_plain(enc, &p.ao, d_out, OUTW, SEQ, 8, 256);
  p.a_shift = (const bf16*)d_in[3]; p.a_ssmk = (const bf16*)d_in[4]; p.a_D = (const bf16*)d_in[5];
  p.out = (bf16*)d_out; p.b_x = (const bf16*)d_in[6]; p.b_wo = (const bf16*)d_in[11];
  map2(enc, &p.x, d_in[6], DM, SEQ, 64, 128);
  map2(enc, &p.ckv, d_in[7], DC, SEQ, 64, 128);
  map3(enc, &p.wq, d_in[8], DM, 2);
  map3(enc, &p.wuk, d_in[9], DC, 2);
  map3(enc, &p.wuv, d_in[10], DC, 2);
  map2(enc, &p.wo, d_in[11], DM, NH * HD, 64, 128);
  {
    const uint64_t dims[3] = {64, 2 * NH * SEQ, 4}, st[2] = {HD * 2, 128}; const uint32_t box[3] = {64, 64, 2};
    make_map(enc, &p.kv, kv_ptr, 3, dims, st, box);
  }
  map2(enc, &p.part, d_out, OUTW, SEQ, 64, 64);
  {
    const uint64_t dims[3] = {64, NMAIN * 128, 4}, st[2] = {HD * 2, 128}; const uint32_t box[3] = {64, 64, 4};
    make_map(enc, &p.ctx, acc_ptr, 3, dims, st, box);
    const uint32_t box1[3] = {64, 64, 1};
    make_map(enc, &p.ctxs, acc_ptr, 3, dims, st, box1);
  }
  concat_heads__ssm_conv_h3__compressed_kv_cla__prompt_kernel<<<NCTA, NTHREADS, SMEM_BYTES>>>(p);
}
```

```cpp
#include <cuda_runtime.h>
#include <cuda_bf16.h>
#include <cuda.h>
#include <stdint.h>

namespace {

typedef __nv_bfloat16 bf16;

constexpr int SEQ  = 2048;
constexpr int DA   = 448;
constexpr int NH   = 16;
constexpr int HD   = 256;
constexpr int DM   = 448;
constexpr int DC   = 1024;
constexpr int OUTW = DA + DM;
constexpr int NMAIN = 128;
constexpr int NCONV = 4;
constexpr int NCTA  = NMAIN + NCONV;
constexpr int NTHREADS = 384;
constexpr int D_SPARE = 320;

__device__ __align__(1024) bf16 g_kv[2ull * SEQ * NH * HD];
__device__ __align__(1024) bf16 g_ctx[(size_t)NMAIN * 128 * HD];
constexpr uint32_t CV_HE = 272 * 16, CV_HCOPY = 4160, CV_D = CV_HE + 4144, CV_BYTES = CV_HE + 2 * CV_HCOPY;
__device__ __align__(128) uint8_t g_xs[NMAIN * CV_BYTES];
struct alignas(128) Flag { unsigned v; unsigned pad[31]; };
struct Flags {
  Flag kv_ready[2 * NH];
  Flag ctx_ready[NMAIN * 2];
  Flag out_ready[16 * 2];
  Flag xs_ready[NH];
  Flag zs_ready[NH];
  alignas(128) unsigned long long done;
};
__device__ Flags g_flags;
#define TS(i)
#define TSG(i)
#define GT(i)
#define PT(i)
#define WHICH_TS 0
#define PCLK(var)
#define PACC(acc, t0)
#define PDECL
#define PDUMP()

#define TR_DECL
#define TR(tag)
#define TR_END()

struct alignas(64) Params {
  CUtensorMap ckv;
  CUtensorMap wuk;
  CUtensorMap wuv;
  CUtensorMap x;
  CUtensorMap wq;
  CUtensorMap wqp;
  CUtensorMap kv;
  CUtensorMap kvs;
  CUtensorMap part;
  CUtensorMap ctx;
  CUtensorMap ctxs;
  CUtensorMap wo;
  CUtensorMap ak, ak8, av, aq, ao;
  const bf16 *a_q, *a_k, *a_v, *a_shift, *a_ssmk, *a_D, *b_x, *b_wo;
  bf16* out;
};

constexpr uint32_t P1_STAGE = 49152;
constexpr uint32_t P1_STG   = 196608;
constexpr uint32_t SLOT     = 32768;
constexpr int      NSLOT    = 5;
constexpr uint32_t QREG     = 163840;
constexpr uint32_t CV_X = 4 * SLOT + 16384, CV_R = 3 * SLOT;
static_assert(CV_BYTES <= 16384 && CV_BYTES % 128 == 0, "SSM operands");
constexpr uint32_t BARS     = 229376;
constexpr uint32_t SMEM_BYTES = BARS + 512 + 1024;
enum : uint32_t {
  B_P1_FULL = 0, B_P1_EMPTY = 4, B_RG_FULL = 8, B_RG_EMPTY = 13, B_ST_FULL = 18, B_ST_EMPTY = 20,
  B_XS = 22, B_PFREE = 23, B_S2_FULL = 28, B_S2_EMPTY = 32, B_QFREE = 36, B_CTXF = 38, B_KV = 40, B_CONV = 42, B_GATE = 43, B_CTXS = 44, B_GFREE = 52, B_COUNT = 53
};

__device__ __forceinline__ uint32_t smem_u32(const void* p) { return (uint32_t)__cvta_generic_to_shared(p); }
__device__ __forceinline__ void mbar_init(uint32_t bar, uint32_t cnt) {
  asm volatile("mbarrier.init.shared::cta.b64 [%0], %1;" :: "r"(bar), "r"(cnt) : "memory");
}
__device__ __forceinline__ void mbar_expect_tx(uint32_t bar, uint32_t bytes) {
  asm volatile("mbarrier.arrive.expect_tx.shared::cta.b64 _, [%0], %1;" :: "r"(bar), "r"(bytes) : "memory");
}
__device__ __forceinline__ void mbar_arrive(uint32_t bar) {
  asm volatile("mbarrier.arrive.shared::cta.b64 _, [%0];" :: "r"(bar) : "memory");
}
__device__ __forceinline__ void mbar_arrive_n(uint32_t bar, uint32_t n) {
  asm volatile("mbarrier.arrive.shared::cta.b64 _, [%0], %1;" :: "r"(bar), "r"(n) : "memory");
}
__device__ __forceinline__ void mbar_arrive_remote(uint32_t bar, uint32_t cta) {
  asm volatile("{\n.reg .b32 ra;\nmapa.shared::cluster.u32 ra, %0, %1;\n"
               "mbarrier.arrive.shared::cluster.b64 _, [ra];\n}" :: "r"(bar), "r"(cta) : "memory");
}
__device__ __forceinline__ void mbar_arrive_remote_n(uint32_t bar, uint32_t cta, uint32_t n) {
  asm volatile("{\n.reg .b32 ra;\nmapa.shared::cluster.u32 ra, %0, %1;\n"
               "mbarrier.arrive.shared::cluster.b64 _, [ra], %2;\n}" :: "r"(bar), "r"(cta), "r"(n) : "memory");
}
__device__ __forceinline__ bool mbar_try(uint32_t bar, uint32_t parity) {
  uint32_t ok;
  asm volatile("{\n.reg .pred p;\nmbarrier.try_wait.parity.shared::cta.b64 p, [%1], %2;\nselp.u32 %0, 1, 0, p;\n}"
               : "=r"(ok) : "r"(bar), "r"(parity) : "memory");
  return ok;
}
#define NAP_NS 100
constexpr uint32_t SPIN_LIMIT = 1u << 24;
__device__ __forceinline__ void mbar_wait(uint32_t bar, uint32_t parity) {
  if (mbar_try(bar, parity)) return;
  uint32_t n = 0;
  while (!mbar_try(bar, parity)) { if (++n > SPIN_LIMIT) __trap(); }
}
__device__ __forceinline__ void mbar_wait_nap(uint32_t bar, uint32_t parity) {
  uint32_t n = 0;
  while (!mbar_try(bar, parity)) { if (++n > (SPIN_LIMIT >> 2)) __trap(); __nanosleep(NAP_NS); }
}
__device__ __forceinline__ void mbar_wait_slow(uint32_t bar, uint32_t parity) {
  uint32_t n = 0;
  while (!mbar_try(bar, parity)) { if (++n > (SPIN_LIMIT >> 4)) __trap(); __nanosleep(500); }
}
__device__ __forceinline__ unsigned load_epoch() {
  unsigned long long e; asm volatile("ld.relaxed.gpu.global.u64 %0, [%1];" : "=l"(e) : "l"(&g_flags.done) : "memory"); return (unsigned)(e / NMAIN);
}
__device__ __forceinline__ void flag_wait(const unsigned* f, unsigned count, unsigned epoch) {
  const unsigned target = (epoch + 1) * count;
  uint32_t n = 0;
  while (true) {
    unsigned v;
    asm volatile("ld.acquire.gpu.global.u32 %0, [%1];" : "=r"(v) : "l"(f) : "memory");
    if ((int)(v - target) >= 0) break;
    if (++n > SPIN_LIMIT) __trap();
    __nanosleep(20);
  }
}
__device__ __forceinline__ void flag_wait_fast(const unsigned* f, unsigned count, unsigned epoch) {
  const unsigned target = (epoch + 1) * count;
  uint32_t n = 0;
  while (true) {
    unsigned v;
    asm volatile("ld.acquire.gpu.global.u32 %0, [%1];" : "=r"(v) : "l"(f) : "memory");
    if ((int)(v - target) >= 0) break;
    if (++n > SPIN_LIMIT) __trap();
  }
}
__device__ __forceinline__ void fence_async_all() { asm volatile("fence.proxy.async;" ::: "memory"); }
__device__ __forceinline__ void flag_signal(unsigned* f) {
  asm volatile("fence.acq_rel.gpu;" ::: "memory");
  asm volatile("red.relaxed.gpu.global.add.u32 [%0], 1;" :: "l"(f) : "memory");
}
__device__ __forceinline__ void flag_signal_after_bulk(unsigned* f) {
  asm volatile("red.relaxed.gpu.global.add.u32 [%0], 1;" :: "l"(f) : "memory");
}
__device__ __forceinline__ void fence_async_smem() { asm volatile("fence.proxy.async.shared::cta;" ::: "memory"); }
__device__ __forceinline__ void tma_ld2(uint32_t dst, const CUtensorMap* m, uint32_t bar, int c0, int c1) {
  asm volatile("cp.async.bulk.tensor.2d.shared::cluster.global.mbarrier::complete_tx::bytes [%0], [%1, {%3, %4}], [%2];"
               :: "r"(dst), "l"(m), "r"(bar), "r"(c0), "r"(c1) : "memory");
}
__device__ __forceinline__ void tma_ld3(uint32_t dst, const CUtensorMap* m, uint32_t bar, int c0, int c1, int c2) {
  asm volatile("cp.async.bulk.tensor.3d.shared::cluster.global.mbarrier::complete_tx::bytes [%0], [%1, {%3, %4, %5}], [%2];"
               :: "r"(dst), "l"(m), "r"(bar), "r"(c0), "r"(c1), "r"(c2) : "memory");
}
__device__ __forceinline__ void tma_ld3_mc(uint32_t dst, const CUtensorMap* m, uint32_t bar, int c0, int c1, int c2) {
  asm volatile("cp.async.bulk.tensor.3d.shared::cluster.global.mbarrier::complete_tx::bytes.multicast::cluster [%0], [%1, {%3, %4, %5}], [%2], %6;"
               :: "r"(dst), "l"(m), "r"(bar), "r"(c0), "r"(c1), "r"(c2), "h"((uint16_t)3) : "memory");
}
__device__ __forceinline__ void bulk_ld(uint32_t dst, const void* src, uint32_t bytes, uint32_t bar) {
  asm volatile("cp.async.bulk.shared::cluster.global.mbarrier::complete_tx::bytes [%0], [%1], %2, [%3];"
               :: "r"(dst), "l"(src), "r"(bytes), "r"(bar) : "memory");
}
__device__ __forceinline__ void tma_st3(const CUtensorMap* m, uint32_t src, int c0, int c1, int c2) {
  asm volatile("cp.async.bulk.tensor.3d.global.shared::cta.bulk_group [%0, {%2, %3, %4}], [%1];"
               :: "l"(m), "r"(src), "r"(c0), "r"(c1), "r"(c2) : "memory");
}
__device__ __forceinline__ void tma_ld2_mc(uint32_t dst, const CUtensorMap* m, uint32_t bar, int c0, int c1) {
  asm volatile("cp.async.bulk.tensor.2d.shared::cluster.global.mbarrier::complete_tx::bytes.multicast::cluster [%0], [%1, {%3, %4}], [%2], %5;"
               :: "r"(dst), "l"(m), "r"(bar), "r"(c0), "r"(c1), "h"((uint16_t)3) : "memory");
}
__device__ __forceinline__ void tma_st2(const CUtensorMap* m, uint32_t src, int c0, int c1) {
  asm volatile("cp.async.bulk.tensor.2d.global.shared::cta.bulk_group [%0, {%2, %3}], [%1];"
               :: "l"(m), "r"(src), "r"(c0), "r"(c1) : "memory");
}
__device__ __forceinline__ void tma_red2(const CUtensorMap* m, uint32_t src, int c0, int c1) {
  asm volatile("cp.reduce.async.bulk.tensor.2d.global.shared::cta.add.tile.bulk_group [%0, {%2, %3}], [%1];"
               :: "l"(m), "r"(src), "r"(c0), "r"(c1) : "memory");
}
__device__ __forceinline__ void tma_pf3(const CUtensorMap* m, int c0, int c1, int c2) {
  asm volatile("cp.async.bulk.prefetch.tensor.3d.L2.global.tile [%0, {%1, %2, %3}];" :: "l"(m), "r"(c0), "r"(c1), "r"(c2) : "memory");
}
__device__ __forceinline__ void tma_pf2(const CUtensorMap* m, int c0, int c1) {
  asm volatile("cp.async.bulk.prefetch.tensor.2d.L2.global.tile [%0, {%1, %2}];" :: "l"(m), "r"(c0), "r"(c1) : "memory");
}
__device__ __forceinline__ void bulk_prefetch(const void* src, uint32_t bytes) {
  asm volatile("cp.async.bulk.prefetch.L2.global [%0], %1;" :: "l"(src), "r"(bytes) : "memory");
}
__device__ __forceinline__ void bulk_commit() { asm volatile("cp.async.bulk.commit_group;" ::: "memory"); }
__device__ __forceinline__ void bulk_wait_read() { asm volatile("cp.async.bulk.wait_group.read 0;" ::: "memory"); }
__device__ __forceinline__ void bulk_wait_all() { asm volatile("cp.async.bulk.wait_group 0;" ::: "memory"); }
__device__ __forceinline__ void prefetch_map(const CUtensorMap* m) { asm volatile("prefetch.tensormap [%0];" :: "l"(m) : "memory"); }
__device__ __forceinline__ void wg_fence() { asm volatile("wgmma.fence.sync.aligned;" ::: "memory"); }
__device__ __forceinline__ void wg_commit() { asm volatile("wgmma.commit_group.sync.aligned;" ::: "memory"); }
template <int N> __device__ __forceinline__ void wg_wait() { asm volatile("wgmma.wait_group.sync.aligned %0;" :: "n"(N) : "memory"); }
template <int N> __device__ __forceinline__ void reg_fence(float (&d)[N]) {
#pragma unroll
  for (int i = 0; i < N; i++) asm volatile("" : "+f"(d[i]) :: "memory");
}
template <int N> __device__ __forceinline__ void reg_fence(uint32_t (&d)[N]) {
#pragma unroll
  for (int i = 0; i < N; i++) asm volatile("" : "+r"(d[i]) :: "memory");
}
__device__ __forceinline__ uint32_t fresh_tid() { uint32_t t; asm volatile("mov.u32 %0, %%tid.x;" : "=r"(t)); return t; }
__device__ __forceinline__ uint32_t lane_base16() {
  const uint32_t t = fresh_tid(), lane = t & 31, wq = (t >> 5) & 3;
  return (16 * wq + (lane & 7) + 8 * ((lane >> 3) & 1)) * 128 + (((lane >> 4) ^ (lane & 7)) << 4);
}
__device__ __forceinline__ void named_sync(int id, int n) { asm volatile("bar.sync %0, %1;" :: "r"(id), "r"(n) : "memory"); }
__device__ __forceinline__ void named_arrive(int id, int n) { asm volatile("bar.arrive %0, %1;" :: "r"(id), "r"(n) : "memory"); }
__device__ __forceinline__ uint32_t pack_bf16(float lo, float hi) {
  uint32_t r; asm("cvt.rn.bf16x2.f32 %0, %1, %2;" : "=r"(r) : "f"(hi), "f"(lo)); return r;
}
__device__ __forceinline__ float ex2(float x) { float y; asm("ex2.approx.ftz.f32 %0, %1;" : "=f"(y) : "f"(x)); return y; }
__device__ __forceinline__ void stsm4(uint32_t addr, uint32_t a, uint32_t b, uint32_t c, uint32_t d) {
  asm volatile("stmatrix.sync.aligned.m8n8.x4.shared.b16 [%0], {%1, %2, %3, %4};" :: "r"(addr), "r"(a), "r"(b), "r"(c), "r"(d) : "memory");
}
__device__ __forceinline__ void stsm4t(uint32_t addr, uint32_t a, uint32_t b, uint32_t c, uint32_t d) {
  asm volatile("stmatrix.sync.aligned.m8n8.x4.trans.shared.b16 [%0], {%1, %2, %3, %4};" :: "r"(addr), "r"(a), "r"(b), "r"(c), "r"(d) : "memory");
}
__device__ __forceinline__ uint64_t mk_desc(uint32_t addr, uint32_t lbo, uint32_t sbo) {
  return (uint64_t)(((addr & 0x3FFFF) >> 4) | ((lbo >> 4) << 16)) | ((uint64_t)((sbo >> 4) | (1u << 30)) << 32);
}
__device__ __forceinline__ uint64_t desc_k(uint32_t addr)  { return mk_desc(addr, 16, 1024); }
__device__ __forceinline__ uint64_t desc_mn(uint32_t addr) { return mk_desc(addr, 8192, 1024); }
__device__ __forceinline__ uint64_t desc_add(uint64_t d, uint32_t bytes) { return d + (bytes >> 4); }

__device__ __forceinline__ void wgmma_ss_n256_tb(float (&d)[128], uint64_t da, uint64_t db, int sd) {
  asm volatile("{\n.reg .pred p;\nsetp.ne.b32 p, %130, 0;\n"
    "wgmma.mma_async.sync.aligned.m64n256k16.f32.bf16.bf16 "
    "{%0, %1, %2, %3, %4, %5, %6, %7, %8, %9, %10, %11, %12, %13, %14, %15, "
    "%16, %17, %18, %19, %20, %21, %22, %23, %24, %25, %26, %27, %28, %29, %30, %31, "
    "%32, %33, %34, %35, %36, %37, %38, %39, %40, %41, %42, %43, %44, %45, %46, %47, "
    "%48, %49, %50, %51, %52, %53, %54, %55, %56, %57, %58, %59, %60, %61, %62, %63, "
    "%64, %65, %66, %67, %68, %69, %70, %71, %72, %73, %74, %75, %76, %77, %78, %79, "
    "%80, %81, %82, %83, %84, %85, %86, %87, %88, %89, %90, %91, %92, %93, %94, %95, "
    "%96, %97, %98, %99, %100, %101, %102, %103, %104, %105, %106, %107, %108, %109, %110, %111, "
    "%112, %113, %114, %115, %116, %117, %118, %119, %120, %121, %122, %123, %124, %125, %126, %127}, "
    "%128, %129, p, 1, 1, 0, 1;\n}"
    : "+f"(d[0]), "+f"(d[1]), "+f"(d[2]), "+f"(d[3]), "+f"(d[4]), "+f"(d[5]), "+f"(d[6]), "+f"(d[7]),
      "+f"(d[8]), "+f"(d[9]), "+f"(d[10]), "+f"(d[11]), "+f"(d[12]), "+f"(d[13]), "+f"(d[14]), "+f"(d[15]),
      "+f"(d[16]), "+f"(d[17]), "+f"(d[18]), "+f"(d[19]), "+f"(d[20]), "+f"(d[21]), "+f"(d[22]), "+f"(d[23]),
      "+f"(d[24]), "+f"(d[25]), "+f"(d[26]), "+f"(d[27]), "+f"(d[28]), "+f"(d[29]), "+f"(d[30]), "+f"(d[31]),
      "+f"(d[32]), "+f"(d[33]), "+f"(d[34]), "+f"(d[35]), "+f"(d[36]), "+f"(d[37]), "+f"(d[38]), "+f"(d[39]),
      "+f"(d[40]), "+f"(d[41]), "+f"(d[42]), "+f"(d[43]), "+f"(d[44]), "+f"(d[45]), "+f"(d[46]), "+f"(d[47]),
      "+f"(d[48]), "+f"(d[49]), "+f"(d[50]), "+f"(d[51]), "+f"(d[52]), "+f"(d[53]), "+f"(d[54]), "+f"(d[55]),
      "+f"(d[56]), "+f"(d[57]), "+f"(d[58]), "+f"(d[59]), "+f"(d[60]), "+f"(d[61]), "+f"(d[62]), "+f"(d[63]),
      "+f"(d[64]), "+f"(d[65]), "+f"(d[66]), "+f"(d[67]), "+f"(d[68]), "+f"(d[69]), "+f"(d[70]), "+f"(d[71]),
      "+f"(d[72]), "+f"(d[73]), "+f"(d[74]), "+f"(d[75]), "+f"(d[76]), "+f"(d[77]), "+f"(d[78]), "+f"(d[79]),
      "+f"(d[80]), "+f"(d[81]), "+f"(d[82]), "+f"(d[83]), "+f"(d[84]), "+f"(d[85]), "+f"(d[86]), "+f"(d[87]),
      "+f"(d[88]), "+f"(d[89]), "+f"(d[90]), "+f"(d[91]), "+f"(d[92]), "+f"(d[93]), "+f"(d[94]), "+f"(d[95]),
      "+f"(d[96]), "+f"(d[97]), "+f"(d[98]), "+f"(d[99]), "+f"(d[100]), "+f"(d[101]), "+f"(d[102]), "+f"(d[103]),
      "+f"(d[104]), "+f"(d[105]), "+f"(d[106]), "+f"(d[107]), "+f"(d[108]), "+f"(d[109]), "+f"(d[110]), "+f"(d[111]),
      "+f"(d[112]), "+f"(d[113]), "+f"(d[114]), "+f"(d[115]), "+f"(d[116]), "+f"(d[117]), "+f"(d[118]), "+f"(d[119]),
      "+f"(d[120]), "+f"(d[121]), "+f"(d[122]), "+f"(d[123]), "+f"(d[124]), "+f"(d[125]), "+f"(d[126]), "+f"(d[127])
    : "l"(da), "l"(db), "r"(sd));
}
__device__ __forceinline__ void wgmma_ss_n64(float (&d)[32], uint64_t da, uint64_t db, int sd) {
  asm volatile("{\n.reg .pred p;\nsetp.ne.b32 p, %34, 0;\n"
    "wgmma.mma_async.sync.aligned.m64n64k16.f32.bf16.bf16 "
    "{%0, %1, %2, %3, %4, %5, %6, %7, %8, %9, %10, %11, %12, %13, %14, %15, "
    "%16, %17, %18, %19, %20, %21, %22, %23, %24, %25, %26, %27, %28, %29, %30, %31}, "
    "%32, %33, p, 1, 1, 0, 0;\n}"
    : "+f"(d[0]), "+f"(d[1]), "+f"(d[2]), "+f"(d[3]), "+f"(d[4]), "+f"(d[5]), "+f"(d[6]), "+f"(d[7]),
      "+f"(d[8]), "+f"(d[9]), "+f"(d[10]), "+f"(d[11]), "+f"(d[12]), "+f"(d[13]), "+f"(d[14]), "+f"(d[15]),
      "+f"(d[16]), "+f"(d[17]), "+f"(d[18]), "+f"(d[19]), "+f"(d[20]), "+f"(d[21]), "+f"(d[22]), "+f"(d[23]),
      "+f"(d[24]), "+f"(d[25]), "+f"(d[26]), "+f"(d[27]), "+f"(d[28]), "+f"(d[29]), "+f"(d[30]), "+f"(d[31])
    : "l"(da), "l"(db), "r"(sd));
}
__device__ __forceinline__ void wgmma_rs_n256_tb(float (&d)[128], uint32_t a0, uint32_t a1, uint32_t a2, uint32_t a3, uint64_t db, int sd) {
  asm volatile("{\n.reg .pred p;\nsetp.ne.b32 p, %133, 0;\n"
    "wgmma.mma_async.sync.aligned.m64n256k16.f32.bf16.bf16 "
    "{%0, %1, %2, %3, %4, %5, %6, %7, %8, %9, %10, %11, %12, %13, %14, %15, "
    "%16, %17, %18, %19, %20, %21, %22, %23, %24, %25, %26, %27, %28, %29, %30, %31, "
    "%32, %33, %34, %35, %36, %37, %38, %39, %40, %41, %42, %43, %44, %45, %46, %47, "
    "%48, %49, %50, %51, %52, %53, %54, %55, %56, %57, %58, %59, %60, %61, %62, %63, "
    "%64, %65, %66, %67, %68, %69, %70, %71, %72, %73, %74, %75, %76, %77, %78, %79, "
    "%80, %81, %82, %83, %84, %85, %86, %87, %88, %89, %90, %91, %92, %93, %94, %95, "
    "%96, %97, %98, %99, %100, %101, %102, %103, %104, %105, %106, %107, %108, %109, %110, %111, "
    "%112, %113, %114, %115, %116, %117, %118, %119, %120, %121, %122, %123, %124, %125, %126, %127}, "
    "{%128, %129, %130, %131}, %132, p, 1, 1, 1;\n}"
    : "+f"(d[0]), "+f"(d[1]), "+f"(d[2]), "+f"(d[3]), "+f"(d[4]), "+f"(d[5]), "+f"(d[6]), "+f"(d[7]),
      "+f"(d[8]), "+f"(d[9]), "+f"(d[10]), "+f"(d[11]), "+f"(d[12]), "+f"(d[13]), "+f"(d[14]), "+f"(d[15]),
      "+f"(d[16]), "+f"(d[17]), "+f"(d[18]), "+f"(d[19]), "+f"(d[20]), "+f"(d[21]), "+f"(d[22]), "+f"(d[23]),
      "+f"(d[24]), "+f"(d[25]), "+f"(d[26]), "+f"(d[27]), "+f"(d[28]), "+f"(d[29]), "+f"(d[30]), "+f"(d[31]),
      "+f"(d[32]), "+f"(d[33]), "+f"(d[34]), "+f"(d[35]), "+f"(d[36]), "+f"(d[37]), "+f"(d[38]), "+f"(d[39]),
      "+f"(d[40]), "+f"(d[41]), "+f"(d[42]), "+f"(d[43]), "+f"(d[44]), "+f"(d[45]), "+f"(d[46]), "+f"(d[47]),
      "+f"(d[48]), "+f"(d[49]), "+f"(d[50]), "+f"(d[51]), "+f"(d[52]), "+f"(d[53]), "+f"(d[54]), "+f"(d[55]),
      "+f"(d[56]), "+f"(d[57]), "+f"(d[58]), "+f"(d[59]), "+f"(d[60]), "+f"(d[61]), "+f"(d[62]), "+f"(d[63]),
      "+f"(d[64]), "+f"(d[65]), "+f"(d[66]), "+f"(d[67]), "+f"(d[68]), "+f"(d[69]), "+f"(d[70]), "+f"(d[71]),
      "+f"(d[72]), "+f"(d[73]), "+f"(d[74]), "+f"(d[75]), "+f"(d[76]), "+f"(d[77]), "+f"(d[78]), "+f"(d[79]),
      "+f"(d[80]), "+f"(d[81]), "+f"(d[82]), "+f"(d[83]), "+f"(d[84]), "+f"(d[85]), "+f"(d[86]), "+f"(d[87]),
      "+f"(d[88]), "+f"(d[89]), "+f"(d[90]), "+f"(d[91]), "+f"(d[92]), "+f"(d[93]), "+f"(d[94]), "+f"(d[95]),
      "+f"(d[96]), "+f"(d[97]), "+f"(d[98]), "+f"(d[99]), "+f"(d[100]), "+f"(d[101]), "+f"(d[102]), "+f"(d[103]),
      "+f"(d[104]), "+f"(d[105]), "+f"(d[106]), "+f"(d[107]), "+f"(d[108]), "+f"(d[109]), "+f"(d[110]), "+f"(d[111]),
      "+f"(d[112]), "+f"(d[113]), "+f"(d[114]), "+f"(d[115]), "+f"(d[116]), "+f"(d[117]), "+f"(d[118]), "+f"(d[119]),
      "+f"(d[120]), "+f"(d[121]), "+f"(d[122]), "+f"(d[123]), "+f"(d[124]), "+f"(d[125]), "+f"(d[126]), "+f"(d[127])
    : "r"(a0), "r"(a1), "r"(a2), "r"(a3), "l"(db), "r"(sd));
}
__device__ __forceinline__ void wgmma_rs_n64_tb(float (&d)[32], uint32_t a0, uint32_t a1, uint32_t a2, uint32_t a3, uint64_t db, int sd) {
  asm volatile("{\n.reg .pred p;\nsetp.ne.b32 p, %37, 0;\n"
    "wgmma.mma_async.sync.aligned.m64n64k16.f32.bf16.bf16 "
    "{%0, %1, %2, %3, %4, %5, %6, %7, %8, %9, %10, %11, %12, %13, %14, %15, "
    "%16, %17, %18, %19, %20, %21, %22, %23, %24, %25, %26, %27, %28, %29, %30, %31}, "
    "{%32, %33, %34, %35}, %36, p, 1, 1, 1;\n}"
    : "+f"(d[0]), "+f"(d[1]), "+f"(d[2]), "+f"(d[3]), "+f"(d[4]), "+f"(d[5]), "+f"(d[6]), "+f"(d[7]),
      "+f"(d[8]), "+f"(d[9]), "+f"(d[10]), "+f"(d[11]), "+f"(d[12]), "+f"(d[13]), "+f"(d[14]), "+f"(d[15]),
      "+f"(d[16]), "+f"(d[17]), "+f"(d[18]), "+f"(d[19]), "+f"(d[20]), "+f"(d[21]), "+f"(d[22]), "+f"(d[23]),
      "+f"(d[24]), "+f"(d[25]), "+f"(d[26]), "+f"(d[27]), "+f"(d[28]), "+f"(d[29]), "+f"(d[30]), "+f"(d[31])
    : "r"(a0), "r"(a1), "r"(a2), "r"(a3), "l"(db), "r"(sd));
}
__device__ __forceinline__ void wgmma_rs_n64(float (&d)[32], uint32_t a0, uint32_t a1, uint32_t a2, uint32_t a3, uint64_t db, int sd) {
  asm volatile("{\n.reg .pred p;\nsetp.ne.b32 p, %37, 0;\n"
    "wgmma.mma_async.sync.aligned.m64n64k16.f32.bf16.bf16 "
    "{%0, %1, %2, %3, %4, %5, %6, %7, %8, %9, %10, %11, %12, %13, %14, %15, "
    "%16, %17, %18, %19, %20, %21, %22, %23, %24, %25, %26, %27, %28, %29, %30, %31}, "
    "{%32, %33, %34, %35}, %36, p, 1, 1, 0;\n}"
    : "+f"(d[0]), "+f"(d[1]), "+f"(d[2]), "+f"(d[3]), "+f"(d[4]), "+f"(d[5]), "+f"(d[6]), "+f"(d[7]),
      "+f"(d[8]), "+f"(d[9]), "+f"(d[10]), "+f"(d[11]), "+f"(d[12]), "+f"(d[13]), "+f"(d[14]), "+f"(d[15]),
      "+f"(d[16]), "+f"(d[17]), "+f"(d[18]), "+f"(d[19]), "+f"(d[20]), "+f"(d[21]), "+f"(d[22]), "+f"(d[23]),
      "+f"(d[24]), "+f"(d[25]), "+f"(d[26]), "+f"(d[27]), "+f"(d[28]), "+f"(d[29]), "+f"(d[30]), "+f"(d[31])
    : "r"(a0), "r"(a1), "r"(a2), "r"(a3), "l"(db), "r"(sd));
}

__device__ __forceinline__ uint4 lds16(uint32_t a) {
  uint4 v; asm volatile("ld.shared.v4.u32 {%0, %1, %2, %3}, [%4];" : "=r"(v.x), "=r"(v.y), "=r"(v.z), "=r"(v.w) : "r"(a) : "memory"); return v;
}
__device__ __forceinline__ void sts16(uint32_t a, uint32_t x, uint32_t y, uint32_t z, uint32_t w) {
  asm volatile("st.shared.v4.u32 [%0], {%1, %2, %3, %4};" :: "r"(a), "r"(x), "r"(y), "r"(z), "r"(w) : "memory");
}
__device__ __forceinline__ uint32_t lds4(uint32_t a) { uint32_t v; asm volatile("ld.shared.u32 %0, [%1];" : "=r"(v) : "r"(a) : "memory"); return v; }
__device__ __forceinline__ uint32_t lds4v(uint32_t a) { uint32_t v; asm volatile("ld.volatile.shared.u32 %0, [%1];" : "=r"(v) : "r"(a) : "memory"); return v; }
__device__ __forceinline__ uint32_t bmul(uint32_t a, uint32_t b) { uint32_t r; asm("mul.rn.bf16x2 %0, %1, %2;" : "=r"(r) : "r"(a), "r"(b)); return r; }
__device__ __forceinline__ uint32_t bfma(uint32_t a, uint32_t b, uint32_t c) { uint32_t r; asm("fma.rn.bf16x2 %0, %1, %2, %3;" : "=r"(r) : "r"(a), "r"(b), "r"(c)); return r; }
__device__ __forceinline__ uint32_t badd(uint32_t a, uint32_t b) { uint32_t r; asm("add.rn.bf16x2 %0, %1, %2;" : "=r"(r) : "r"(a), "r"(b)); return r; }

__device__ __forceinline__ void ldsm4(uint32_t (&r)[4], uint32_t a) {
  asm volatile("ldmatrix.sync.aligned.m8n8.x4.shared.b16 {%0, %1, %2, %3}, [%4];" : "=r"(r[0]), "=r"(r[1]), "=r"(r[2]), "=r"(r[3]) : "r"(a) : "memory");
}
__device__ __forceinline__ void ldsm4t(uint32_t (&r)[4], uint32_t a) {
  asm volatile("ldmatrix.sync.aligned.m8n8.x4.trans.shared.b16 {%0, %1, %2, %3}, [%4];" : "=r"(r[0]), "=r"(r[1]), "=r"(r[2]), "=r"(r[3]) : "r"(a) : "memory");
}
__device__ __forceinline__ uint32_t transpose8(uint32_t a) { uint32_t d; asm volatile("movmatrix.sync.aligned.m8n8.trans.b16 %0, %1;" : "=r"(d) : "r"(a)); return d; }

__device__ __forceinline__ void mma16816(float (&d)[4], const uint32_t (&a)[4], uint32_t b0, uint32_t b1) {
  asm volatile("mma.sync.aligned.m16n8k16.row.col.f32.bf16.bf16.f32 {%0, %1, %2, %3}, {%4, %5, %6, %7}, {%8, %9}, {%0, %1, %2, %3};"
               : "+f"(d[0]), "+f"(d[1]), "+f"(d[2]), "+f"(d[3]) : "r"(a[0]), "r"(a[1]), "r"(a[2]), "r"(a[3]), "r"(b0), "r"(b1));
}

#define P1_SPLIT 0
#define O_ROT 1
#define STG_K1 2
#define STG_K2 10
#define STG_Q1 (KV_TMA ? 1 : 2)
#define STG_Q2 (KV_TMA ? 5 : 6)
#define CTX_K 0
#define PF_QA 48
#define PF_WV 99
#define PF_END 0
#define PF_CV 1
#define PACE_A 850
#define PACE_B 400
#define Q_PRE 1
#define KV_TMA 32
#define TPACE_A 3200
#define TPACE_B 800
#define ARRIVE_KK 12
#define SIDE_DELAY_NS 4000
#define KVH(h) (h)
#define HEAD_MAP 1
#define EARLY_LD 3
constexpr int RED_BAR = 6;
constexpr int CV_BAR = 5;
constexpr int PP_BAR = 3;
template <int V> struct Int { static constexpr int value = V; };
struct Ring {
  uint32_t slot, phase;
  __device__ __forceinline__ void next() { if (++slot == NSLOT) { slot = 0; phase ^= 1; } }
};
__device__ __forceinline__ uint32_t bar_addr(uint32_t sb, uint32_t i) { return sb + BARS + 8 * i; }
__device__ __forceinline__ uint32_t q_region(uint32_t sb, int w) { return sb + QREG + (w ^ 1) * 32768; }

struct Role { int h, j; };
__device__ __forceinline__ Role get_role() {
  int cta; asm volatile("mov.u32 %0, %%ctaid.x;" : "=r"(cta));
  const int c = cta >> 1;
  int h, u;
  if (c < 4) { h = 15; u = c; }
  else if (c < 36) { h = (c - 4) & 7; u = (c - 4) >> 3; }
  else { h = 8 + (c - 36) % 7; u = (c - 36) / 7; }
  return Role{h, 2 * u + (cta & 1)};
}
__device__ __forceinline__ int fresh_warp() { return __shfl_sync(0xffffffffu, fresh_tid() >> 5, 0); }

__device__ __forceinline__ int q_tile(int h, int j, int which) { return ((h < 8) == (which == 0)) ? 15 - j : j; }

__device__ __forceinline__ int o_chunk(int h, int c) { const int x = c + O_ROT * (h & 7); return x % 7; }

__device__ __forceinline__ int num_private(int qt) { return (qt & 1) ? 5 : 1; }
__device__ __forceinline__ void ring_acquire(uint32_t sb, Ring& r, uint32_t bytes) {
  mbar_wait(bar_addr(sb, B_RG_EMPTY + r.slot), r.phase ^ 1);
  mbar_expect_tx(bar_addr(sb, B_RG_FULL + r.slot), bytes);
}
__device__ __forceinline__ void load_tile4(uint32_t dst, const CUtensorMap* m, uint32_t full, int row, int blk0, int rank, bool shared) {
  if (shared) {
    tma_ld3_mc(dst + rank * 16384, m, full, 0, row, blk0 + 2 * rank);
  } else {
    tma_ld3(dst, m, full, 0, row, blk0);
    tma_ld3(dst + 16384, m, full, 0, row, blk0 + 2);
  }
}
__device__ __forceinline__ void producer_main(const Params& p, uint32_t sb) {
  const Role ro = get_role();
  const int h = ro.h, j = ro.j, rank = j & 1;
  for (int it = EARLY_LD; it < 71; it++) {
    const int t = it >> 4, k = it & 15, s = it & 3;
    mbar_wait(bar_addr(sb, B_P1_EMPTY + s), ((it >> 2) & 1) ^ 1);
    const uint32_t full = bar_addr(sb, B_P1_FULL + s), dst = sb + s * P1_STAGE;
    mbar_expect_tx(full, P1_STAGE);
    if (t < 4) {
      tma_ld2(dst, &p.ckv, full, k * 64, (2 * j + (t & 1)) * 128);
      load_tile4(dst + 16384, (t >> 1) ? &p.wuv : &p.wuk, full, k * 64, h * 4, rank, true);
    } else {
      tma_ld2(dst, &p.x, full, k * 64, q_tile(h, j, 0) * 128);
      load_tile4(dst + 16384, &p.wq, full, k * 64, h * 4, rank, true);
    }
    if (it >= PF_QA && it < PF_QA + 14) {
      const int i = it - PF_QA;
      bulk_prefetch(p.b_x + (size_t)(q_tile(h, j, 0) * 128 + (h & 7) * 16) * DM + i * 512, 1024);
      tma_pf2(&p.wqp, h * HD, (i * 8 + j) * 4);
    }
  }
  mbar_wait(bar_addr(sb, B_P1_EMPTY + 3), 0);
  mbar_wait(bar_addr(sb, B_XS), 0);
  mbar_expect_tx(bar_addr(sb, B_RG_FULL + 4), CV_BYTES);
  bulk_ld(sb + CV_X, g_xs + (size_t)(h * 8 + j) * CV_BYTES, CV_BYTES, bar_addr(sb, B_RG_FULL + 4));
  Ring r{0, 1};
  int hs = 5;
  auto acquire = [&](bool shared) {
    mbar_wait(bar_addr(sb, B_RG_EMPTY + r.slot), r.phase ^ 1);
    if (shared && hs < 5) {
      mbar_arrive_remote(bar_addr(sb, B_PFREE + r.slot), rank ^ 1);
      mbar_wait(bar_addr(sb, B_PFREE + r.slot), 0);
      hs++;
    }
    mbar_expect_tx(bar_addr(sb, B_RG_FULL + r.slot), 32768);
  };
  mbar_wait(bar_addr(sb, B_KV), 0);
  for (int which = 0; which < 2; which++) {
    const int qt = q_tile(h, j, which);
    if (which == 1) {
      for (int kc = 0; kc < 7; kc++) {
        ring_acquire(sb, r, 32768);
        load_tile4(sb + r.slot * SLOT, &p.wq, bar_addr(sb, B_RG_FULL + r.slot), kc * 64, h * 4, rank, false);
        r.next();
        if (kc == 0 || (kc & 1)) {
          ring_acquire(sb, r, kc == 0 ? 16384 : 32768);
          const uint32_t full = bar_addr(sb, B_RG_FULL + r.slot), dst = sb + r.slot * SLOT;
          tma_ld2(dst, &p.x, full, kc * 64, qt * 128);
          if (kc > 0) tma_ld2(dst + 16384, &p.x, full, kc * 64 + 64, qt * 128);
          r.next();
        }
      }
      hs = 0;
    }
    const int n = 2 * qt + 2, npriv = num_private(qt), nb = qt & ~1;
    for (int f = 0; f < 2 * n; f++) {
      if (PF_END && f == max(2 * n - PF_END, 0)) {
        if (which == 0) bulk_prefetch(p.b_x + (size_t)((15 - qt) * 128 + (h & 7) * 16) * DM, 16 * DM * 2);
        else bulk_prefetch(p.b_wo + (size_t)(h * HD + j * 32) * DM, 32 * DM * 2);
      }
      const bool isK = (f == 0) || ((f & 1) && f < 2 * n - 1);
      const int i = isK ? (f + 1) >> 1 : (f == 2 * n - 1 ? n - 1 : (f >> 1) - 1);
      int tile = n - 1 - i;
      if (which == 0) { const int b = i >> 1; tile = b >= nb ? i : 2 * (2 * b < nb ? 2 * b : 2 * b - nb + 1) + (i & 1); }
      if (!isK && (tile & 2)) mbar_wait(bar_addr(sb, B_KV + 1), 0);
      if (which == 0 && f < 2) mbar_wait(bar_addr(sb, B_P1_EMPTY + f), 1);
      const bool shared = (which ? f : 2 * n - 1 - f) >= npriv;
      acquire(shared);
      load_tile4(sb + r.slot * SLOT, &p.kv, bar_addr(sb, B_RG_FULL + r.slot), ((isK ? 0 : NH) + KVH(h)) * SEQ + tile * 64, 0, rank, shared);
      r.next();
    }
  }
  for (int i = 0; i < 14; i++) {
    acquire(true);
    tma_ld2_mc(sb + r.slot * SLOT + rank * 16384, &p.wo, bar_addr(sb, B_RG_FULL + r.slot), o_chunk(h, i >> 1) * 64, ((i & 1) ? h ^ 8 : h) * HD + rank * 128);
    r.next();
  }
}

__device__ __forceinline__ void storer_main(const Params& p, uint32_t sb) {
  const Role ro = get_role();
  const int h = ro.h, j = ro.j, w = fresh_warp() - 1;
  const uint32_t full = bar_addr(sb, B_ST_FULL + w), empty = bar_addr(sb, B_ST_EMPTY + w);
  const int lane = threadIdx.x & 31;
  const unsigned epoch = load_epoch();
  if (lane == 0) {
    for (int job = 0; job < 8; job++) {
      const int t = job >> 1, row = ((t >> 1) * NH + KVH(h)) * SEQ + (2 * j + (t & 1)) * 128 + w * 64;
      mbar_wait_nap(full, job & 1);
      for (int i = 0; i < 128 / KV_TMA; i++) {
        if (i) __nanosleep((job < 6 ? TPACE_A : TPACE_B) * KV_TMA / 128);
        tma_st3(&p.kvs, sb + P1_STG + w * 16384 + i * KV_TMA * 128, 0, row + (i * KV_TMA & 63), (job & 1) * 2 + (i * KV_TMA >> 6));
      }
      bulk_commit();
      bulk_wait_read();
      mbar_arrive(empty);
      if (job == 5 || job == 7) { bulk_wait_all(); flag_signal(&g_flags.kv_ready[2 * h + (job == 7)].v); }
    }
  }
  __syncwarp();
  const int cta = h * 8 + j, qt = q_tile(h, j, 1);
  const uint32_t qreg = q_region(sb, w);
  {
    mbar_wait(bar_addr(sb, B_CTXS + 4 * w), 0);
    uint4* z = reinterpret_cast<uint4*>(p.out + (size_t)(qt * 128 + w * 64 + (h & 7) * 8 + (lane >> 2)) * OUTW + DA) + (lane & 3);
#pragma unroll
    for (int i = 0; i < 14; i++) z[4 * i] = make_uint4(0, 0, 0, 0);
    __syncwarp();
    if (lane != 0) return;
    for (int b = 0; b < 4; b++) {
      mbar_wait(bar_addr(sb, B_CTXS + 4 * w + b), 0);
      tma_st3(&p.ctxs, qreg + b * 8192, 0, cta * 128 + w * 64, b);
      bulk_commit();
    }
    bulk_wait_read();
    mbar_arrive(empty);
    bulk_wait_all();
    flag_signal(&g_flags.ctx_ready[cta * 2 + w].v);
    flag_signal_after_bulk(&g_flags.out_ready[qt * 2 + w].v);
  }
  {
    const int wx = w ^ 1;
    flag_wait(&g_flags.ctx_ready[(cta ^ 64) * 2 + wx].v, 1, epoch);
    flag_wait(&g_flags.out_ready[qt * 2 + wx].v, 8, epoch);
    fence_async_all();
    mbar_wait(bar_addr(sb, B_QFREE + w), 0);
    mbar_expect_tx(bar_addr(sb, B_CTXF + w), 32768);
    tma_ld3(qreg, &p.ctx, bar_addr(sb, B_CTXF + w), 0, (cta ^ 64) * 128 + wx * 64, 0);
    for (int ch = 0; ch < 7; ch++) {
      const int b = ch & 1;
      mbar_wait(bar_addr(sb, B_S2_FULL + w * 2 + b), (ch >> 1) & 1);
      tma_red2(&p.part, qreg + b * 8192, DA + o_chunk(h, ch) * 64, qt * 128 + wx * 64);
      bulk_commit();
      if (ch == 0 && w == 1) mbar_arrive(bar_addr(sb, B_GFREE));
      bulk_wait_read();
      mbar_arrive(bar_addr(sb, B_S2_EMPTY + w * 2 + b));
    }
    GT(48 + w);
    bulk_wait_all();
    GT(50 + w); GT(52 + w); GT(56);
  }
}

template <int OFF, int NB, int NREG>
__device__ __forceinline__ void store_blocks(uint32_t base, uint32_t lanebase, const uint32_t (&pk)[NREG]) {
#pragma unroll
  for (int J = 0; J < NB * 8; J += 2) {
    const uint32_t a = base + (J >> 3) * 8192 + (lanebase ^ ((J & 7) << 4));
    stsm4(a, pk[OFF + 2 * J], pk[OFF + 2 * J + 1], pk[OFF + 2 * J + 2], pk[OFF + 2 * J + 3]);
  }
}
__device__ __forceinline__ void warp_arrive(uint32_t bar, int lane) { __syncwarp(); if (lane == 0) mbar_arrive(bar); }
__device__ __forceinline__ void release(uint32_t bar, int lane, int rank, bool shared) {
  if (shared) { if (lane < 2) mbar_arrive_remote(bar, rank ^ lane); }
  else if (lane == 0) mbar_arrive_n(bar, 2);
}

template <int W> __device__ __forceinline__ constexpr int cv_tile(int u) { return 2 * u + ((u ^ W) & 1); }
__device__ __forceinline__ uint32_t cv_x_lane(uint32_t lane) { return (16 + (lane & 15) - (lane >> 4)) * 16; }
__device__ __forceinline__ uint32_t cv_h_lane(uint32_t lane, uint32_t hE, uint32_t hO) {
  const uint32_t g = lane >> 2, c = lane & 3;
  return (g & 1) ? hO + (15 + 2 * c - g) * 2 : hE + (16 + 2 * c - g) * 2;
}
template <int W>
__device__ __forceinline__ void conv_mma(float (&ca)[8][4], uint32_t xa, uint32_t ha) {
  constexpr int N = 16 - W;
  uint32_t fx[N][4], fh[N][2];
  auto ld_h = [&](int i, int rr) { fh[i][0] = lds4(ha + i * 256 + rr * 32); fh[i][1] = lds4(ha + i * 256 + rr * 32 + 16); };
  ldsm4(fx[0], xa);
#pragma unroll
  for (int u = 0; u < 8; u++) ld_h(cv_tile<W>(u), 0);
  ldsm4(fx[1], xa + 256);
#pragma unroll
  for (int u = 0; u < 8; u++) if (cv_tile<W ^ 1>(u) < N) ld_h(cv_tile<W ^ 1>(u), 0);
#pragma unroll
  for (int i = 2; i < N; i++) ldsm4(fx[i], xa + i * 256);
#pragma unroll
  for (int sx = 0; sx < N; sx++) {
#pragma unroll
    for (int u = 0; u < 8; u++) {
      const int jj = cv_tile<W>(u) - sx;
      if (jj >= 0) mma16816(ca[u], fx[sx], fh[jj < 0 ? 0 : jj][0], fh[jj < 0 ? 0 : jj][1]);
    }
    ldsm4(fx[sx], xa + sx * 256 - 32);
    ld_h(N - 1 - sx, 1);
  }
#pragma unroll
  for (int jj = N - 1; jj >= 0; jj--)
#pragma unroll
    for (int u = 0; u < 8; u++) {
      const int sx = cv_tile<W>(u) - jj;
      if (sx >= 0) mma16816(ca[u], fx[sx < 0 ? 0 : sx], fh[jj][0], fh[jj][1]);
    }
}

__device__ __forceinline__ void consumer_main(const Params& p, uint32_t sb) {
  const int lane = fresh_tid() & 31, w = (fresh_warp() >> 2) - 1;
  const uint32_t lb = lane_base16();
  int qt, rank;
  { const Role ro = get_role(); qt = q_tile(ro.h, ro.j, 0); rank = ro.j & 1; }
  const uint32_t st_full = bar_addr(sb, B_ST_FULL + w), st_empty = bar_addr(sb, B_ST_EMPTY + w);
  const uint32_t stg = sb + P1_STG + w * 16384;

  auto turn_begin = [&]() { named_sync(PP_BAR + w, 256); };
  auto turn_end = [&]() { named_arrive(PP_BAR + (w ^ 1), 256); };
  if (w == 0) named_arrive(PP_BAR + 1, 256);
  float acc[128];
#pragma unroll
  for (int i = 0; i < 128; i++) acc[i] = 0.f;
  uint32_t pk[64];
#pragma unroll
  for (int i = 0; i < 64; i++) pk[i] = 0;
  PDECL;
  TR_DECL;
  TR(0);
  TSG(0); TS(1);
  const uint32_t qreg = q_region(sb, w);
  for (int t = 0; t < 5; t++) {
    const int nk = t < 4 ? 16 : 7;
#pragma unroll 1
    for (int k = 0; k < nk; k++) {
      const int it = t * 16 + k, s = k & 3;
      mbar_wait(bar_addr(sb, B_P1_FULL + s), (it >> 2) & 1);
      TR(1);
      const uint64_t da = desc_k(sb + s * P1_STAGE + w * 8192), db = desc_mn(sb + s * P1_STAGE + 16384);
      turn_begin();
      wg_fence();
#pragma unroll
      for (int kk = 0; kk < 4; kk++) wgmma_ss_n256_tb(acc, desc_add(da, kk * 32), desc_add(db, kk * 2048), (k | kk) != 0);
      wg_commit();
      turn_end();
      TR(3);
      wg_wait<1>();
      if (k > 0) release(bar_addr(sb, B_P1_EMPTY + ((k - 1) & 3)), lane, rank, true);
      const int k1 = t < 4 ? STG_K1 : STG_Q1, k2 = t < 4 ? STG_K2 : STG_Q2;
      if (t > 0 && (k == k1 || k == k2)) {
        const int job = 2 * (t - 1) + (k != k1);
        if (job > 0) mbar_wait(st_empty, (job - 1) & 1);
        if (k == k1) store_blocks<0, 2>(stg, lb, pk); else store_blocks<32, 2>(stg, lb, pk);
      }
      if (t > 0 && (k == k1 + 1 || k == k2 + 1)) { fence_async_smem(); warp_arrive(st_full, lane); }
      TR(5);
    }
    wg_wait<0>();
    TR(6);
    reg_fence(acc);
    release(bar_addr(sb, B_P1_EMPTY + ((nk - 1) & 3)), lane, rank, true);
#pragma unroll
    for (int i = 0; i < 64; i++) pk[i] = pack_bf16(acc[2 * i], acc[2 * i + 1]);
    TS(t < 4 ? 2 + t : 60);
  }
  TS(6);
  {
    const uint32_t wq = lb >> 11, ln = lane, cx = sb + CV_X;
    float ca[8][4];
#pragma unroll
    for (int i = 0; i < 8; i++) { ca[i][0] = 0.f; ca[i][1] = 0.f; ca[i][2] = 0.f; ca[i][3] = 0.f; }
    const uint32_t xa = cx + cv_x_lane(ln) - wq * 64, ha = cv_h_lane(ln, cx + CV_HE, cx + CV_HE + CV_HCOPY) + wq * 64;
    mbar_wait(bar_addr(sb, B_RG_FULL + 4), 0);
    TR(7); TS(19); TS(20);
    if (w) conv_mma<1>(ca, xa, ha); else conv_mma<0>(ca, xa, ha);
    TR(8); TS(21);
    mbar_wait(bar_addr(sb, B_P1_EMPTY + 2), 1);
    const uint32_t ex = sb + CV_R + w * 16384 + ln * 16;
#pragma unroll
    for (int u = 0; u < 8; u++)
      sts16(ex + (wq * 8 + u) * 512, __float_as_uint(ca[u][0]), __float_as_uint(ca[u][1]), __float_as_uint(ca[u][2]), __float_as_uint(ca[u][3]));
  }
  auto conv_finish = [&]() {
    const uint32_t wq = lb >> 11, cx = sb + CV_X, ex = sb + CV_R + w * 16384 + lane * 16;
    const Role ro = get_role();
    uint8_t* gz = g_xs + (size_t)(ro.h * 8 + ro.j) * CV_BYTES;
    const uint32_t Dd = lds4(cx + CV_D);
    uint32_t z[2][2];
#pragma unroll
    for (int e = 0; e < 2; e++) {
      const uint32_t u = 2 * wq + e, nt = 2 * u + ((e ^ w) & 1);
      float y[4] = {0.f, 0.f, 0.f, 0.f};
#pragma unroll
      for (int v = 0; v < 4; v++) {
        const uint4 t = lds16(ex + (v * 8 + u) * 512);
        y[0] += __uint_as_float(t.x); y[1] += __uint_as_float(t.y); y[2] += __uint_as_float(t.z); y[3] += __uint_as_float(t.w);
      }
      const uint32_t o = (16 + 16 * nt) * 16 + lane * 4;
      *reinterpret_cast<uint32_t*>(gz + o)       = badd(pack_bf16(y[0], y[1]), bmul(lds4(cx + o), Dd));
      *reinterpret_cast<uint32_t*>(gz + o + 128) = badd(pack_bf16(y[2], y[3]), bmul(lds4(cx + o + 128), Dd));
    }
    __syncwarp();
    release(bar_addr(sb, B_RG_EMPTY + 3), lane, rank, true);
    release(bar_addr(sb, B_RG_EMPTY + 4), lane, rank, true);
    if (lane == 0) mbar_arrive(bar_addr(sb, B_CONV));
  };
  TS(15);
  TR(10);
  Ring r{0, 1};
  auto take = [&]() { const uint32_t sl = r.slot; mbar_wait(bar_addr(sb, B_RG_FULL + sl), r.phase); r.next(); return sl; };
  constexpr float SC = 0.0625f * 1.4426950408889634f;
#pragma unroll 1
  for (int which = 0;; which++) {
    float s[32];
#pragma unroll
    for (int i = 0; i < 32; i++) s[i] = 0.f;
    uint32_t pa[16];
    float m0 = -INFINITY, m1 = -INFINITY, l0 = 0.f, l1 = 0.f;
    const uint64_t dq = desc_k(qreg);
    uint64_t dk = 0, dqq = 0, dv = 0;
    auto prep_qk = [&](uint32_t kaddr) { dk = desc_k(kaddr); dqq = dq + (kaddr >> 31); asm volatile("" : "+l"(dk), "+l"(dqq)); };
    auto prep_pv = [&](uint32_t vaddr) { dv = desc_mn(vaddr); asm volatile("" : "+l"(dv)); };
    auto issue_qk = [&]() {
#pragma unroll
      for (int kk = 0; kk < 16; kk++)
        wgmma_ss_n64(s, desc_add(dqq, (kk >> 2) * 8192 + (kk & 3) * 32), desc_add(dk, (kk >> 2) * 8192 + (kk & 3) * 32), kk != 0);
    };
    auto issue_pv = [&](int accumulate) {
#pragma unroll
      for (int kk = 0; kk < 4; kk++)
        wgmma_rs_n256_tb(acc, pa[4 * kk], pa[4 * kk + 1], pa[4 * kk + 2], pa[4 * kk + 3], desc_add(dv, kk * 2048), accumulate | kk);
    };
    auto mask_diag = [&]() {
      const int d = (int)((lb >> 11) << 4) + (lane >> 2) - 2 * (lane & 3);
#pragma unroll
      for (int jj = 0; jj < 8; jj++) {
        if (8 * jj > d)     s[4 * jj]     = -INFINITY;
        if (8 * jj + 1 > d) s[4 * jj + 1] = -INFINITY;
        if (8 * jj - 8 > d) s[4 * jj + 2] = -INFINITY;
        if (8 * jj - 7 > d) s[4 * jj + 3] = -INFINITY;
      }
    };
    float a0, a1;
    auto softmax = [&]() -> bool {
      float x0 = fmaxf(s[0], s[1]), x1 = fmaxf(s[2], s[3]);
#pragma unroll
      for (int jj = 1; jj < 8; jj++) {
        x0 = fmaxf(x0, fmaxf(s[4 * jj], s[4 * jj + 1]));
        x1 = fmaxf(x1, fmaxf(s[4 * jj + 2], s[4 * jj + 3]));
      }
      x0 = fmaxf(x0, __shfl_xor_sync(0xffffffffu, x0, 1));
      x1 = fmaxf(x1, __shfl_xor_sync(0xffffffffu, x1, 1));
      x0 = fmaxf(x0, __shfl_xor_sync(0xffffffffu, x0, 2));
      x1 = fmaxf(x1, __shfl_xor_sync(0xffffffffu, x1, 2));
      const bool grow = __any_sync(0xffffffffu, fmaxf(x0 - m0, x1 - m1) * SC > 8.f);
      if (grow) {
        x0 = fmaxf(x0, m0); x1 = fmaxf(x1, m1);
        a0 = ex2((m0 - x0) * SC); a1 = ex2((m1 - x1) * SC);
        m0 = x0; m1 = x1;
        l0 *= a0; l1 *= a1;
      }
      const float b0 = -m0 * SC, b1 = -m1 * SC;
      float t0 = 0.f, t1 = 0.f, t2 = 0.f, t3 = 0.f;
#pragma unroll
      for (int jj = 0; jj < 8; jj++) {
        s[4 * jj]     = ex2(fmaf(s[4 * jj], SC, b0));
        s[4 * jj + 1] = ex2(fmaf(s[4 * jj + 1], SC, b0));
        s[4 * jj + 2] = ex2(fmaf(s[4 * jj + 2], SC, b1));
        s[4 * jj + 3] = ex2(fmaf(s[4 * jj + 3], SC, b1));
        t0 += s[4 * jj]; t1 += s[4 * jj + 1]; t2 += s[4 * jj + 2]; t3 += s[4 * jj + 3];
      }
      l0 += t0 + t1; l1 += t2 + t3;
      return grow;
    };
    auto softmax_fast = [&]() -> bool {
      const float b0 = -m0 * SC, b1 = -m1 * SC;
      float t0 = 0.f, t1 = 0.f, t2 = 0.f, t3 = 0.f;
#pragma unroll
      for (int jj = 0; jj < 8; jj++) {
        s[4 * jj]     = ex2(fmaf(s[4 * jj], SC, b0));
        s[4 * jj + 1] = ex2(fmaf(s[4 * jj + 1], SC, b0));
        s[4 * jj + 2] = ex2(fmaf(s[4 * jj + 2], SC, b1));
        s[4 * jj + 3] = ex2(fmaf(s[4 * jj + 3], SC, b1));
        t0 += s[4 * jj]; t1 += s[4 * jj + 1]; t2 += s[4 * jj + 2]; t3 += s[4 * jj + 3];
      }
      t0 += t1; t2 += t3;
      uint32_t redo;
      asm volatile("{\n.reg .pred p, q;\nsetp.le.f32 p, %1, 0f47800000;\nbarrier.cta.red.or.aligned.pred q, %2, 128, !p;\nselp.u32 %0, 1, 0, q;\n}"
                   : "=r"(redo) : "f"(fmaxf(t0, t2) + (t0 - t0) + (t2 - t2)), "r"(RED_BAR + w) : "memory");
      if (!redo) { l0 += t0; l1 += t2; }
      return redo;
    };
    auto rescale = [&]() {
#pragma unroll
      for (int i = 0; i < 32; i++) { acc[4 * i] *= a0; acc[4 * i + 1] *= a0; acc[4 * i + 2] *= a1; acc[4 * i + 3] *= a1; }
    };
    auto to_p = [&]() {
#pragma unroll
      for (int i = 0; i < 16; i++) pa[i] = pack_bf16(s[2 * i], s[2 * i + 1]);
    };

    const bool up = w == which;
    const int n = 2 * qt + 2, nw = n - up, npriv = num_private(qt);
    int fd = which ? 0 : 2 * n - 1;
    const int dir = which ? 1 : -1;
    auto skip = [&]() { r.next(); fd += dir; };
    auto give = [&](uint32_t sl, int d) {
      if (lane < 2) mbar_arrive_remote_n(bar_addr(sb, B_RG_EMPTY + sl), d < npriv ? rank : rank ^ lane, (d & ~2) == 0 ? 2 : 1);
    };
    if (which && up) skip();
    uint32_t ks = take();
    TS(62 + which);
    TR(20);
    prep_qk(sb + ks * SLOT);
    turn_begin();
    wg_fence();
#pragma unroll
    for (int kk = 0; kk < 16; kk++)
      wgmma_rs_n64(s, pk[4 * kk], pk[4 * kk + 1], pk[4 * kk + 2], pk[4 * kk + 3], desc_add(dk, (kk >> 2) * 8192 + (kk & 3) * 32), kk != 0);
    wg_commit();
    turn_end();
    TR(21);
    if (!which) conv_finish();
    TR(23);
    if (which || w == 0) mbar_wait(st_empty, which ^ 1);
    if (!which && w == 0) mbar_wait(bar_addr(sb, B_ST_EMPTY + 1), 1);
    store_blocks<0, Q_PRE>(qreg, lb, pk);
#pragma unroll
    for (int i = 0; i < 96; i++) asm volatile("mov.b32 %0, 0;" : "=f"(acc[i]));
    TR(24);
    wg_wait<0>();
    TR(22);
    reg_fence(s);
    reg_fence(pk);
#pragma unroll
    for (int i = 96; i < 128; i++) asm volatile("mov.b32 %0, 0;" : "=f"(acc[i]));
    give(ks, fd);
    fd += dir;
    if (which && up) skip();
    if (which || nw == 1) mask_diag();
    softmax();
    store_blocks<16 * Q_PRE, 4 - Q_PRE>(qreg + Q_PRE * 8192, lb, pk);
    to_p();
    fence_async_smem();
    if (which && nw == 1) warp_arrive(bar_addr(sb, B_QFREE + w), lane);
#pragma unroll 1
    for (int jj = 1; jj < nw; jj++) {
      ks = take();
      const uint32_t vs = take();
      TR(30);
      prep_qk(sb + ks * SLOT);
      prep_pv(sb + vs * SLOT);
      turn_begin();
      wg_fence();
      issue_qk();
      wg_commit();
      issue_pv(1);
      wg_commit();
      turn_end();
      TR(31);
      wg_wait<1>();
      TR(32);
      reg_fence(s);
      const bool diag = !which && jj == nw - 1;
      if (diag) mask_diag();
      bool grow = false;
      if (softmax_fast()) {
#pragma unroll 1
        for (int kb = 0; kb < 4; kb++) {
          const uint64_t da = desc_k(qreg + kb * 8192), db = desc_k(sb + ks * SLOT + kb * 8192);
          wg_fence();
#pragma unroll
          for (int kk = 0; kk < 4; kk++) wgmma_ss_n64(s, desc_add(da, kk * 32), desc_add(db, kk * 32), (kb | kk) != 0);
          wg_commit();
          wg_wait<0>();
          reg_fence(s);
        }
        if (diag) mask_diag();
        grow = softmax();
      }
      give(ks, fd);
      if (which && jj == nw - 1 && lane == 0) mbar_arrive(bar_addr(sb, B_QFREE + w));
      wg_wait<0>();
      reg_fence(acc);
      reg_fence(pa);
      give(vs, fd + dir);
      fd += 2 * dir;
      if (grow) rescale();
      to_p();
    }
    if (!which && up) skip();
    const uint32_t vs = take();
    TR(40);
    prep_pv(sb + vs * SLOT);
    turn_begin();
    wg_fence();
    issue_pv(1);
    wg_commit();
    turn_end();
    TR(41);
    l0 += __shfl_xor_sync(0xffffffffu, l0, 1); l1 += __shfl_xor_sync(0xffffffffu, l1, 1);
    l0 += __shfl_xor_sync(0xffffffffu, l0, 2); l1 += __shfl_xor_sync(0xffffffffu, l1, 2);
    float i0 = 1.f / l0, i1 = 1.f / l1;
    asm volatile("" : "+f"(i0), "+f"(i1) :: "memory");
    wg_wait<0>();
    TR(42);
    reg_fence(acc);
    reg_fence(pa);
    give(vs, fd);
    if (!which && up) r.next();
    TS(7 + 3 * which);
#pragma unroll
    for (int i = 0; i < 32; i++) {
      pk[2 * i]     = pack_bf16(acc[4 * i] * i0, acc[4 * i + 1] * i0);
      pk[2 * i + 1] = pack_bf16(acc[4 * i + 2] * i1, acc[4 * i + 3] * i1);
    }
    TS(8 + 3 * which); TR(46);
    if (which) break;
    TS(31);
    uint32_t xaddr = 0, xs = 0, pw = 0, px = 0;
#pragma unroll 1
    for (int kc = 0; kc < 7; kc++) {
      const uint32_t ws = take();
      if (kc == 0 || (kc & 1)) { xs = take(); xaddr = sb + xs * SLOT + (w ^ 1) * 8192; } else xaddr += 16384;
      TR(11);
      const uint64_t da = desc_k(xaddr), db = desc_mn(sb + ws * SLOT);
      turn_begin();
      wg_fence();
#pragma unroll
      for (int kk = 0; kk < 4; kk++) wgmma_ss_n256_tb(acc, desc_add(da, kk * 32), desc_add(db, kk * 2048), (kc | kk) != 0);
      wg_commit();
      turn_end();
      TR(13);
      wg_wait<1>();
      if (kc > 0) {
        release(bar_addr(sb, B_RG_EMPTY + pw), lane, rank, false);
        if (kc & 1) release(bar_addr(sb, B_RG_EMPTY + px), lane, rank, false);
      }
      pw = ws; px = xs;
      const int cb = kc - CTX_K;
      if (cb >= 1 && cb <= 4) { fence_async_smem(); warp_arrive(bar_addr(sb, B_CTXS + 4 * w + cb - 1), lane); }
      if (cb == 0) store_blocks<0, 1>(qreg, lb, pk);
      else if (cb == 1) store_blocks<16, 1>(qreg + 8192, lb, pk);
      else if (cb == 2) store_blocks<32, 1>(qreg + 16384, lb, pk);
      else if (cb == 3) store_blocks<48, 1>(qreg + 24576, lb, pk);
      TR(15);
    }
    wg_wait<0>();
    reg_fence(acc);
    TS(61); TR(16);
    release(bar_addr(sb, B_RG_EMPTY + pw), lane, rank, false);
    release(bar_addr(sb, B_RG_EMPTY + px), lane, rank, false);
#pragma unroll
    for (int i = 0; i < 64; i++) pk[i] = pack_bf16(acc[2 * i], acc[2 * i + 1]);
    TS(9); TR(19);
    qt = 15 - qt;
  }

  {
    float oa[32], ob[32];
#pragma unroll
    for (int i = 0; i < 32; i++) { oa[i] = 0.f; ob[i] = 0.f; }
    auto stage_o = [&](float (&o)[32], int ch) {
      reg_fence(o);
      uint32_t q[16];
#pragma unroll
      for (int i = 0; i < 16; i++) q[i] = pack_bf16(o[2 * i], o[2 * i + 1]);
      if (ch >= 2) mbar_wait(bar_addr(sb, B_S2_EMPTY + w * 2 + (ch & 1)), ((ch >> 1) - 1) & 1);
      store_blocks<0, 1>(qreg + (ch & 1) * 8192, lb, q);
    };
    auto hand_over = [&](int ch) {
      fence_async_smem();
      warp_arrive(bar_addr(sb, B_S2_FULL + w * 2 + (ch & 1)), lane);
    };
    uint32_t pk2[64];
#pragma unroll
    for (int i = 0; i < 64; i++) pk2[i] = 0;
    uint32_t p2 = 0;
    auto chunk = [&](int ch, float (&o)[32], float (&oprev)[32]) {
      const uint32_t s1 = take();
      TR(50);
      const uint64_t d1 = desc_mn(sb + s1 * SLOT);
      turn_begin();
      wg_fence();
#pragma unroll
      for (int kk = 0; kk < 16; kk++) {
        wgmma_rs_n64_tb(o, pk[4 * kk], pk[4 * kk + 1], pk[4 * kk + 2], pk[4 * kk + 3], desc_add(d1, kk * 2048), kk != 0);
        if (kk == ARRIVE_KK) turn_end();
      }
      wg_commit();
      TR(51);
      if (ch >= 1) {
        wg_wait<1>();
        if (ch <= 4) release(bar_addr(sb, B_RG_EMPTY + p2), lane, rank, true);
        stage_o(oprev, ch - 1);
      } else {
        mbar_wait(bar_addr(sb, B_CTXF + w), 0);
#pragma unroll
        for (int kk = 0; kk < 16; kk++) {
          uint32_t f[4];
          ldsm4(f, qreg + (kk >> 2) * 8192 + (lb ^ ((kk & 3) << 5)));
          pk2[4 * kk] = f[0]; pk2[4 * kk + 1] = f[1]; pk2[4 * kk + 2] = f[2]; pk2[4 * kk + 3] = f[3];
        }
      }
      const uint32_t s2 = take();
      TR(53);
      const uint64_t d2 = desc_mn(sb + s2 * SLOT);
      turn_begin();
      wg_fence();
#pragma unroll
      for (int kk = 0; kk < 16; kk++) {
        wgmma_rs_n64_tb(o, pk2[4 * kk], pk2[4 * kk + 1], pk2[4 * kk + 2], pk2[4 * kk + 3], desc_add(d2, kk * 2048), 1);
        if (kk == ARRIVE_KK && (ch < 6 || w == 1)) turn_end();
      }
      wg_commit();
      TR(54);
      if (ch >= 1) hand_over(ch - 1);
      wg_wait<1>();
      TR(55);
      if (ch <= 4) release(bar_addr(sb, B_RG_EMPTY + s1), lane, rank, true);
      p2 = s2;
    };
#pragma unroll 1
    for (int ch = 0; ch < 6; ch += 2) { chunk(ch, oa, ob); chunk(ch + 1, ob, oa); }
    chunk(6, oa, ob);
    wg_wait<0>();
    TR(58);
    reg_fence(pk);
    reg_fence(pk2);
    stage_o(oa, 6);
    hand_over(6);
  }
  TS(12); TR(59);
  if ((threadIdx.x & 127) == 0) GT(54 + w);

  TS(16); TS(18); TS(17);
  TR(99); TR_END();
  TS(13); TSG(14);
}

#define CONV_STAGGER_NS 1200
namespace ssm {
#define CONV_GROUPS (D_SPARE / 8 / NCONV)
constexpr int GROUPS = CONV_GROUPS;
constexpr uint32_t ZROWS = 16;
constexpr uint32_t CHAN = (ZROWS + 256 + 1) * 16;
constexpr uint32_t XBUF = 8 * CHAN;
constexpr uint32_t OFF_X = 0;
constexpr uint32_t HCOPY = 4160;
constexpr uint32_t OFF_H = 2 * XBUF;
constexpr uint32_t HWARP = 3 * HCOPY;
constexpr uint32_t IO_K = 128, IO_V = IO_K + 4096, IO_Q = IO_V + 4096, IOBUF = IO_Q + 4096;
constexpr uint32_t OFF_IO = (OFF_H + 8 * HWARP + 127) / 128 * 128;
constexpr uint32_t END = OFF_IO + 4 * IOBUF;
static_assert(IOBUF % 128 == 0 && OFF_H % 16 == 0, "TMA destination alignment");
static_assert(END <= BARS, "smem");
enum : uint32_t { B_XREADY = 0, B_ZDONE = 2, B_KV = 4, B_Q = 8, B_HRAW = 12, B_QLAST = 20 };
constexpr int CW_BAR = 4;

__device__ __forceinline__ int group_d0(int cidx, int grp) { return (grp * NCONV + cidx) * 8; }
__device__ __forceinline__ uint32_t x_lane(int lane) { return (lane & 7) * CHAN + (ZROWS + (lane >> 3)) * 16; }
__device__ __forceinline__ uint32_t t_lane(int lane) { return (uint32_t)(8 * (lane >> 3) + 7 - (lane & 7)) * 16; }
struct Taps { uint32_t s[4]; };
__device__ __forceinline__ Taps load_taps(const Params& p, int d0, int c) {
  const uint2 s0 = __ldg(reinterpret_cast<const uint2*>(p.a_shift + (d0 + 2 * c) * 4)), s1 = __ldg(reinterpret_cast<const uint2*>(p.a_shift + (d0 + 2 * c + 1) * 4));
  return Taps{{__byte_perm(s0.x, s1.x, 0x5410), __byte_perm(s0.x, s1.x, 0x7632), __byte_perm(s0.y, s1.y, 0x5410), __byte_perm(s0.y, s1.y, 0x7632)}};
}
__device__ __forceinline__ uint32_t short_conv(const Taps& t, uint32_t k0, uint32_t k1, uint32_t k2, uint32_t k3, uint32_t v) {
  return bmul(bfma(k3, t.s[0], bfma(k2, t.s[1], bfma(k1, t.s[2], bmul(k0, t.s[3])))), v);
}
__device__ __forceinline__ void gate_chunk(uint32_t xa, uint32_t qa) {
#pragma unroll 4
  for (int i = 0; i < 8; i++) {
    uint32_t zz[4], qq[4];
    ldsm4t(zz, xa + i * 64);
    ldsm4(qq, qa + i * 512);
    stsm4(qa + i * 512, bmul(qq[0], zz[0]), bmul(qq[1], zz[1]), bmul(qq[2], zz[2]), bmul(qq[3], zz[3]));
  }
}

__device__ __forceinline__ void io_warp(const Params& p, uint32_t sb, int cidx, int wq) {
  const int lane = threadIdx.x & 31;
  const uint32_t io = sb + OFF_IO + wq * IOBUF, bkv = bar_addr(sb, B_KV + wq), bq = bar_addr(sb, B_Q + wq);
  auto load_kv = [&](int e) {
    __syncwarp();
    if (lane != 0) return;
    const int d0 = group_d0(cidx, e >> 1), row = (2 * wq + (e & 1)) * 256;
    if (e < 2 * GROUPS) {
      mbar_expect_tx(bkv, IO_Q);
      tma_ld2(io, &p.ak8, bkv, d0, row - 8);
      tma_ld2(io + IO_K, &p.ak, bkv, d0, row);
      tma_ld2(io + IO_V, &p.av, bkv, d0, row);
    } else {
      const uint32_t bar = bar_addr(sb, B_QLAST + 2 * wq + 1);
      mbar_expect_tx(bar, 4096);
      tma_ld2(io + IO_K, &p.aq, bar, group_d0(cidx, GROUPS - 1), row + 256);
    }
  };
  auto load_q = [&](int e) {
    __syncwarp();
    if (lane != 0) return;
    const uint32_t bar = e < 2 * GROUPS - 2 ? bq : bar_addr(sb, B_QLAST + 2 * wq);
    mbar_expect_tx(bar, 4096);
    tma_ld2(io + IO_Q, &p.aq, bar, group_d0(cidx, e >> 1), (2 * wq + (e & 1)) * 256);
  };
  TR_DECL;
  TR(0);
  load_kv(0);
  const uint32_t xl = sb + OFF_X + x_lane(lane) + wq * 1024, tl = io + t_lane(lane);
#pragma unroll 1
  for (int grp = -2; grp + 1 < GROUPS; grp++) {
    const bool more = grp + 2 < GROUPS;
    const Taps taps = load_taps(p, group_d0(cidx, more ? grp + 2 : 0), lane & 3);
    PCLK(c0);
    if (grp >= 0) mbar_wait_nap(bar_addr(sb, B_ZDONE + (grp & 1)), (grp >> 1) & 1);
    PACC(tp, c0);
    PCLK(c1);
    TR(80);
#pragma unroll 1
    for (int i = 0; i < 2; i++) {
      const uint32_t xa = xl + (grp & 1) * XBUF + i * 512;
      if (grp >= 0) {
        mbar_wait_nap(bq, i);
        TR(81);
        gate_chunk(xa, tl + IO_Q);
      }
      if (more) {
        TR(82);
        mbar_wait_nap(bkv, i);
        TR(83);
#pragma unroll 2
        for (int u = 0; u < 8; u++) {
          const uint32_t ka = tl + IO_K + u * 512;
          uint32_t k0[4], k1[4], k2[4], k3[4], vv[4];
          ldsm4(k0, ka - 48); ldsm4(k1, ka - 32); ldsm4(k2, ka - 16); ldsm4(k3, ka); ldsm4(vv, ka + 4096);
          stsm4t(xa + u * 64, short_conv(taps, k0[0], k1[0], k2[0], k3[0], vv[0]), short_conv(taps, k0[1], k1[1], k2[1], k3[1], vv[1]),
                 short_conv(taps, k0[2], k1[2], k2[2], k3[2], vv[2]), short_conv(taps, k0[3], k1[3], k2[3], k3[3], vv[3]));
        }
        load_kv(2 * (grp + 2) + i + 1);
        TR(84);
        if (i == 1) warp_arrive(bar_addr(sb, B_XREADY + (grp & 1)), lane);
      }
      if (grp >= 0) {
        fence_async_smem();
        __syncwarp();
        if (lane == 0) {
          tma_st2(&p.ao, io + IO_Q, group_d0(cidx, grp), (2 * wq + i) * 256);
          bulk_commit();
          bulk_wait_read();
        }
      }
      if (2 * grp + i + 1 >= 0) load_q(2 * grp + i + 1);
      TR(85);
    }
    PACC(te, c1);
  }
  if (lane == 0) bulk_wait_all();
  TR(99); TR_END();
}

__device__ __forceinline__ void conv_warp(const Params& p, uint32_t sb, int cidx, int ch) {
  const int lane = threadIdx.x & 31;
  const uint32_t hE0 = sb + OFF_H + ch * HWARP, hO = hE0 + HCOPY;
  const uint32_t hbar = bar_addr(sb, B_HRAW + ch);
  auto fetch_h = [&](int grp) {
    if (lane == 0) {
      mbar_expect_tx(hbar, 4096);
      asm volatile("cp.async.bulk.shared::cluster.global.mbarrier::complete_tx::bytes [%0], [%1], %2, [%3];"
                   :: "r"(hE0 + (grp & 1) * 2 * HCOPY + 32), "l"(p.a_ssmk + (size_t)(group_d0(cidx, grp) + ch) * SEQ), "r"(4096), "r"(hbar) : "memory");
    }
  };
  TR_DECL;
  TR(0);
  fetch_h(0);
#pragma unroll 1
  for (int grp = 0; grp < GROUPS; grp++) {
    const uint32_t xc = sb + OFF_X + (grp & 1) * XBUF + ch * CHAN;
    const uint32_t Dd = (uint32_t)__ldg(reinterpret_cast<const unsigned short*>(p.a_D + group_d0(cidx, grp) + ch)) * 0x10001u;
    PCLK(k0);
    mbar_wait(hbar, grp & 1);
    const uint32_t hE = hE0 + (grp & 1) * 2 * HCOPY;
    if (grp + 1 < GROUPS) fetch_h(grp + 1);
#pragma unroll
    for (int i = 0; i < 8; i++) {
      const uint32_t o = 32 + (i * 32 + lane) * 16;
      const uint4 w = lds16(hE + o);
      const uint32_t nx = lds4(hE + o + 16);
      sts16(hO + o, __byte_perm(w.x, w.y, 0x5432), __byte_perm(w.y, w.z, 0x5432), __byte_perm(w.z, w.w, 0x5432), __byte_perm(w.w, nx, 0x5432));
      if (o == 32) asm volatile("st.shared.u32 [%0], %1;" :: "r"(hO + 28), "r"(w.x << 16) : "memory");
    }
    __syncwarp();
    const uint32_t ha = cv_h_lane(lane, hE, hO), xa = xc + cv_x_lane(lane);
    TR(71);
    mbar_wait(bar_addr(sb, B_XREADY + (grp & 1)), (grp >> 1) & 1);
    TR(72);
    if (grp == 0 && ch >= 4) __nanosleep(CONV_STAGGER_NS);
    PACC(tw, k0);
    PCLK(k1);
    float acc[16][4];
#pragma unroll
    for (int i = 0; i < 16; i++) { acc[i][0] = 0.f; acc[i][1] = 0.f; acc[i][2] = 0.f; acc[i][3] = 0.f; }
#pragma unroll 1
    for (int r = 0; r < 8; r++) {
      uint32_t fx[16][4], fh[16][2];
#pragma unroll
      for (int i = 0; i < 16; i++) { fh[i][0] = lds4(ha + i * 256 + r * 32); fh[i][1] = lds4(ha + i * 256 + r * 32 + 16); }
#pragma unroll
      for (int i = 0; i < 16; i++) ldsm4(fx[i], xa + i * 256 - r * 32);
#pragma unroll
      for (int sx = 0; sx < 16; sx++)
#pragma unroll
        for (int jj = 0; jj < 16 - sx; jj++) mma16816(acc[jj + sx], fx[sx], fh[jj][0], fh[jj][1]);
    }
    PACC(tm, k1);
    PCLK(k2);
    TR(73);
#pragma unroll
    for (int i = 0; i < 8; i++) {
      uint32_t x[4];
      const uint32_t ad = xc + (ZROWS + lane) * 16 + i * 512;
      ldsm4(x, ad);
      stsm4(ad, badd(pack_bf16(acc[2 * i][0], acc[2 * i][1]), bmul(x[0], Dd)), badd(pack_bf16(acc[2 * i][2], acc[2 * i][3]), bmul(x[1], Dd)),
            badd(pack_bf16(acc[2 * i + 1][0], acc[2 * i + 1][1]), bmul(x[2], Dd)), badd(pack_bf16(acc[2 * i + 1][2], acc[2 * i + 1][3]), bmul(x[3], Dd)));
    }
    if (grp + 1 < GROUPS) warp_arrive(bar_addr(sb, B_ZDONE + (grp & 1)), lane);
    PACC(tr, k2);
    TR(74);
  }
  {
    mbar_wait(bar_addr(sb, B_QLAST + ch), 0);
    named_sync(CW_BAR, 256);
    TR(75);
    const uint32_t qb = sb + OFF_IO + (ch >> 1) * IOBUF + ((ch & 1) ? IO_K : IO_Q);
    gate_chunk(sb + OFF_X + ((GROUPS - 1) & 1) * XBUF + x_lane(lane) + ch * 512, qb + t_lane(lane));
    fence_async_smem();
    __syncwarp();
    if (lane == 0) { tma_st2(&p.ao, qb, group_d0(cidx, GROUPS - 1), ch * 256); bulk_commit(); bulk_wait_all(); }
    TR(99); TR_END();
  }
}

__device__ __forceinline__ void init(uint32_t sb) {
  if (threadIdx.x < 16 * ZROWS) sts16(sb + OFF_X + (threadIdx.x >> 4) * CHAN + (threadIdx.x & 15) * 16, 0, 0, 0, 0);
  if (threadIdx.x < 96) sts16(sb + OFF_H + (threadIdx.x >> 2) * HCOPY + (threadIdx.x & 1) * 16 + ((threadIdx.x & 2) ? 4128 : 0), 0, 0, 0, 0);
  if (threadIdx.x == 0) {
    for (int i = 0; i < 2; i++) { mbar_init(bar_addr(sb, B_XREADY + i), 4); mbar_init(bar_addr(sb, B_ZDONE + i), 8); }
    for (int i = 0; i < 4; i++) { mbar_init(bar_addr(sb, B_KV + i), 1); mbar_init(bar_addr(sb, B_Q + i), 1); }
    for (int i = 0; i < 8; i++) { mbar_init(bar_addr(sb, B_HRAW + i), 1); mbar_init(bar_addr(sb, B_QLAST + i), 1); }
    fence_async_smem();
  }
}
}

__device__ __forceinline__ void ssm_side_work(const Params& p, uint32_t sb, unsigned epoch) {
  const Role ro = get_role();
  const int h = ro.h, j = ro.j;
  const int lane = threadIdx.x & 31, g = lane >> 2, c = lane & 3;
  const int d0 = D_SPARE + 8 * h;
  uint8_t* xs = g_xs + (size_t)(h * 8 + g) * CV_BYTES + c * 4;
  auto xrow = [&](int beta) { return xs + (16 + beta) * 16; };
  {
    const uint4* hp = reinterpret_cast<const uint4*>(p.a_ssmk + (size_t)(d0 + j) * SEQ) + lane;
    uint8_t* he = g_xs + (size_t)(h * 8 + j) * CV_BYTES + CV_HE;
#pragma unroll 2
    for (int i = 0; i < 8; i++) {
      const uint4 wv = __ldg(hp + i * 32);
      const uint32_t nx = i * 32 + lane < 255 ? __ldg(reinterpret_cast<const uint32_t*>(hp + i * 32 + 1)) : 0u;
      const uint32_t o = 32 + (i * 32 + lane) * 16;
      *reinterpret_cast<uint4*>(he + o) = wv;
      *reinterpret_cast<uint4*>(he + CV_HCOPY + o) =
          make_uint4(__byte_perm(wv.x, wv.y, 0x5432), __byte_perm(wv.y, wv.z, 0x5432), __byte_perm(wv.z, wv.w, 0x5432), __byte_perm(wv.w, nx, 0x5432));
      if (o == 32) *reinterpret_cast<uint32_t*>(he + CV_HCOPY + 28) = wv.x << 16;
    }
    if (lane == 0) *reinterpret_cast<uint32_t*>(he + CV_D - CV_HE) = (uint32_t)__ldg(reinterpret_cast<const unsigned short*>(p.a_D + d0 + j)) * 0x10001u;
  }
  {
    const ssm::Taps taps = ssm::load_taps(p, d0, c);
    const uint32_t* kp = reinterpret_cast<const uint32_t*>(p.a_k + (size_t)(256 * j + 7 - g) * DA + d0) + c;
    const uint32_t* vp = reinterpret_cast<const uint32_t*>(p.a_v + (size_t)(256 * j + 7 - g) * DA + d0) + c;
    uint32_t kprev = j > 0 ? __ldg(kp - 8 * (DA / 2)) : 0u;
#pragma unroll 1
    for (int i0 = 0; i0 < 32; i0 += 8) {
      uint32_t kk[8], vv[8];
#pragma unroll
      for (int i = 0; i < 8; i++) { kk[i] = __ldg(kp + (i0 + i) * 8 * (DA / 2)); vv[i] = __ldg(vp + (i0 + i) * 8 * (DA / 2)); }
#pragma unroll
      for (int i = 0; i < 8; i++) {
        const uint32_t k2 = __shfl_sync(0xffffffffu, g < 1 ? kprev : kk[i], (lane + 4) & 31);
        const uint32_t k1 = __shfl_sync(0xffffffffu, g < 2 ? kprev : kk[i], (lane + 8) & 31);
        const uint32_t k0 = __shfl_sync(0xffffffffu, g < 3 ? kprev : kk[i], (lane + 12) & 31);
        *reinterpret_cast<uint32_t*>(xrow(32 * j + i0 + i)) = transpose8(ssm::short_conv(taps, k0, k1, k2, kk[i], vv[i]));
        kprev = kk[i];
      }
    }
    __syncwarp();
    if (lane == 0) {
      flag_signal(&g_flags.xs_ready[h].v);
      flag_wait(&g_flags.xs_ready[h].v, 8, epoch);
      fence_async_all();
      mbar_arrive(bar_addr(sb, B_XS));
    }
  }
  if (lane == 0) {
    for (int i = 0; i < 2; i++) {
      flag_wait(&g_flags.kv_ready[2 * h + i].v, 16, epoch);
      fence_async_all();
      mbar_arrive(bar_addr(sb, B_KV + i));
      if (PF_CV && i == 0) bulk_prefetch(g_xs + (size_t)(h * 8 + j) * CV_BYTES, CV_BYTES);
    }
    mbar_wait(bar_addr(sb, B_CONV), 0);
    flag_signal(&g_flags.zs_ready[h].v);
    flag_wait(&g_flags.zs_ready[h].v, 8, epoch);
    asm volatile("red.relaxed.gpu.global.add.u64 [%0], 1;" :: "l"(&g_flags.done) : "memory");
  }
  __syncwarp();
  fence_async_all();
  const uint32_t qb = q_region(sb, 1) + 16384, zb = qb + 4096, bar = bar_addr(sb, B_GATE);
  constexpr uint32_t ZCH = 528;
  mbar_wait_slow(bar_addr(sb, B_GFREE), 0);
  if (lane == 0) { mbar_expect_tx(bar, 8192); tma_ld2(qb, &p.aq, bar, d0, 256 * j); }
  __syncwarp();
  if (lane < 8) bulk_ld(zb + lane * ZCH, g_xs + (size_t)(h * 8 + lane) * CV_BYTES + (16 + 32 * j) * 16, 512, bar);
  mbar_wait(bar, 0);
  ssm::gate_chunk(zb + (lane & 7) * ZCH + (lane >> 3) * 16, qb + ssm::t_lane(lane));
  fence_async_smem();
  __syncwarp();
  if (lane == 0) { tma_st2(&p.ao, qb, d0, 256 * j); bulk_commit(); bulk_wait_all(); }
}

__global__ void __cluster_dims__(2, 1, 1) __launch_bounds__(NTHREADS, 1)
concat_heads__ssm_conv_h3__compressed_kv_cla__prompt_kernel(const __grid_constant__ Params p) {
  extern __shared__ uint8_t smem_raw[];
  const uint32_t sb = (smem_u32(smem_raw) + 1023) & ~1023u;
  const int warp = __shfl_sync(0xffffffffu, threadIdx.x >> 5, 0);
  const int wg = warp >> 2;
  const int cta = blockIdx.x;
  const bool attn = cta < NMAIN;
  if (!attn) ssm::init(sb);
  if (attn && threadIdx.x == 0) {
    for (int i = 0; i < 4; i++) { mbar_init(bar_addr(sb, B_P1_FULL + i), 1); mbar_init(bar_addr(sb, B_P1_EMPTY + i), 16); }
    for (int i = 0; i < NSLOT; i++) {
      mbar_init(bar_addr(sb, B_RG_FULL + i), 1); mbar_init(bar_addr(sb, B_RG_EMPTY + i), 16); mbar_init(bar_addr(sb, B_PFREE + i), 1);
    }
    for (int i = 0; i < 2; i++) { mbar_init(bar_addr(sb, B_ST_FULL + i), 4); mbar_init(bar_addr(sb, B_ST_EMPTY + i), 1); }
    mbar_init(bar_addr(sb, B_XS), 1); mbar_init(bar_addr(sb, B_CONV), 8); mbar_init(bar_addr(sb, B_GATE), 1); mbar_init(bar_addr(sb, B_GFREE), 1);
    mbar_init(bar_addr(sb, B_KV), 1); mbar_init(bar_addr(sb, B_KV + 1), 1);
    for (int i = 0; i < 8; i++) mbar_init(bar_addr(sb, B_CTXS + i), 4);
    for (int i = 0; i < 4; i++) { mbar_arrive(bar_addr(sb, B_RG_FULL + i)); if (i < 3) mbar_arrive_n(bar_addr(sb, B_RG_EMPTY + i), 16); }
    for (int i = 0; i < 4; i++) { mbar_init(bar_addr(sb, B_S2_FULL + i), 4); mbar_init(bar_addr(sb, B_S2_EMPTY + i), 1); }
    for (int i = 0; i < 2; i++) { mbar_init(bar_addr(sb, B_QFREE + i), 4); mbar_init(bar_addr(sb, B_CTXF + i), 1); }
    asm volatile("fence.mbarrier_init.release.cluster;" ::: "memory");
  }
  if (attn && threadIdx.x == 32) {
    prefetch_map(&p.ckv); prefetch_map(&p.wuk); prefetch_map(&p.wuv); prefetch_map(&p.x); prefetch_map(&p.wq);
    prefetch_map(&p.kv); prefetch_map(&p.part); prefetch_map(&p.wo); prefetch_map(&p.ctx);
  }
  __syncwarp();
  asm volatile("barrier.cluster.arrive.release.aligned;" ::: "memory");
  if (attn && threadIdx.x == 0) {
    const Role ro = get_role();
    const int h = ro.h, j = ro.j;
    for (int k = 0; k < EARLY_LD; k++) {
      const uint32_t full = bar_addr(sb, B_P1_FULL + k), dst = sb + k * P1_STAGE;
      mbar_expect_tx(full, P1_STAGE);
      tma_ld2(dst, &p.ckv, full, k * 64, 2 * j * 128);
      load_tile4(dst + 16384, &p.wuk, full, k * 64, h * 4, j & 1, false);
    }
  }
  __syncwarp();
  asm volatile("barrier.cluster.wait.acquire.aligned;" ::: "memory");

  const int lane = threadIdx.x & 31;
  if (wg == 0) {
    if (!attn) {
      asm volatile("setmaxnreg.dec.sync.aligned.u32 72;");
      if (threadIdx.x == 0) GT(0);
      if (p.out != nullptr) ssm::io_warp(p, sb, cta - NMAIN, fresh_warp());
      if (threadIdx.x == 0) GT(14);
      return;
    }
    asm volatile("setmaxnreg.dec.sync.aligned.u32 40;");
    if (warp == 0) {
      if (lane == 0) producer_main(p, sb);
    } else if (warp < 3) {
      storer_main(p, sb);
    } else {
      const unsigned epoch = load_epoch();
      mbar_wait(bar_addr(sb, B_P1_FULL + 3), 0);
      __nanosleep(SIDE_DELAY_NS);
      ssm_side_work(p, sb, epoch);
    }
  } else {
    if (!attn) {
      asm volatile("setmaxnreg.inc.sync.aligned.u32 216;");
      if (threadIdx.x == 128) { GT(12); PT(10); }
      if (p.out != nullptr) ssm::conv_warp(p, sb, cta - NMAIN, fresh_warp() - 4);
      if (threadIdx.x == 128) { PT(9); GT(13); }
      return;
    }
    asm volatile("setmaxnreg.inc.sync.aligned.u32 232;");
    if (p.out != nullptr) {
      consumer_main(p, sb);
    }
  }
}

typedef CUresult (*EncodeTiledFn)(CUtensorMap*, CUtensorMapDataType, cuuint32_t, void*, const cuuint64_t*, const cuuint64_t*,
                                  const cuuint32_t*, const cuuint32_t*, CUtensorMapInterleave, CUtensorMapSwizzle,
                                  CUtensorMapL2promotion, CUtensorMapFloatOOBfill);

void make_map(EncodeTiledFn enc, CUtensorMap* m, const void* ptr, int rank, const uint64_t* dims, const uint64_t* strides, const uint32_t* box) {
  cuuint64_t d[3], s[2]; cuuint32_t b[3], e[3] = {1, 1, 1};
  for (int i = 0; i < rank; i++) { d[i] = dims[i]; b[i] = box[i]; if (i) s[i - 1] = strides[i - 1]; }
  enc(m, CU_TENSOR_MAP_DATA_TYPE_BFLOAT16, rank, const_cast<void*>(ptr), d, s, b, e, CU_TENSOR_MAP_INTERLEAVE_NONE,
      CU_TENSOR_MAP_SWIZZLE_128B, CU_TENSOR_MAP_L2_PROMOTION_L2_256B, CU_TENSOR_MAP_FLOAT_OOB_FILL_NONE);
}
void map2(EncodeTiledFn enc, CUtensorMap* m, const void* ptr, uint64_t cols, uint64_t rows, uint32_t bc, uint32_t br) {
  const uint64_t dims[2] = {cols, rows}, st[1] = {cols * 2}; const uint32_t box[2] = {bc, br};
  make_map(enc, m, ptr, 2, dims, st, box);
}
void map2_plain(EncodeTiledFn enc, CUtensorMap* m, const void* ptr, uint64_t cols, uint64_t rows, uint32_t bc, uint32_t br) {
  cuuint64_t d[2] = {cols, rows}, st[1] = {cols * 2}; cuuint32_t b[2] = {bc, br}, e[2] = {1, 1};
  enc(m, CU_TENSOR_MAP_DATA_TYPE_BFLOAT16, 2, const_cast<void*>(ptr), d, st, b, e, CU_TENSOR_MAP_INTERLEAVE_NONE,
      CU_TENSOR_MAP_SWIZZLE_NONE, CU_TENSOR_MAP_L2_PROMOTION_L2_128B, CU_TENSOR_MAP_FLOAT_OOB_FILL_NONE);
}
void map3(EncodeTiledFn enc, CUtensorMap* m, const void* ptr, uint64_t rows, uint32_t nblk) {
  const uint64_t dims[3] = {64, rows, 64}, st[2] = {8192, 128}; const uint32_t box[3] = {64, 64, nblk};
  make_map(enc, m, ptr, 3, dims, st, box);
}

}

extern "C" void kernel_launch(void* const* d_in, const int* in_sizes, int n_in, void* d_out, int out_size) {
  (void)in_sizes; (void)n_in; (void)out_size;
  static EncodeTiledFn enc = nullptr;
  static void *kv_ptr = nullptr, *acc_ptr = nullptr;
  if (!enc) {
    void* fn = nullptr; cudaDriverEntryPointQueryResult qr;
    cudaGetDriverEntryPoint("cuTensorMapEncodeTiled", &fn, cudaEnableDefault, &qr);
    enc = (EncodeTiledFn)fn;
    cudaGetSymbolAddress(&kv_ptr, g_kv);
    cudaGetSymbolAddress(&acc_ptr, g_ctx);
    cudaFuncSetAttribute(concat_heads__ssm_conv_h3__compressed_kv_cla__prompt_kernel, cudaFuncAttributeMaxDynamicSharedMemorySize, SMEM_BYTES);
  }
  Params p;
  p.a_q = (const bf16*)d_in[0]; p.a_k = (const bf16*)d_in[1]; p.a_v = (const bf16*)d_in[2];
  map2_plain(enc, &p.aq, d_in[0], DA, SEQ, 8, 256);
  map2_plain(enc, &p.ak, d_in[1], DA, SEQ, 8, 256);
  map2_plain(enc, &p.ak8, d_in[1], DA, SEQ, 8, 8);
  map2_plain(enc, &p.av, d_in[2], DA, SEQ, 8, 256);
  map2_plain(enc, &p.ao, d_out, OUTW, SEQ, 8, 256);
  p.a_shift = (const bf16*)d_in[3]; p.a_ssmk = (const bf16*)d_in[4]; p.a_D = (const bf16*)d_in[5];
  p.out = (bf16*)d_out; p.b_x = (const bf16*)d_in[6]; p.b_wo = (const bf16*)d_in[11];
  map2(enc, &p.x, d_in[6], DM, SEQ, 64, 128);
  map2(enc, &p.ckv, d_in[7], DC, SEQ, 64, 128);
  map3(enc, &p.wq, d_in[8], DM, 2);
  map2_plain(enc, &p.wqp, d_in[8], NH * HD, DM, 256, 4);
  map3(enc, &p.wuk, d_in[9], DC, 2);
  map3(enc, &p.wuv, d_in[10], DC, 2);
  map2(enc, &p.wo, d_in[11], DM, NH * HD, 64, 128);
  {
    const uint64_t dims[3] = {64, 2 * NH * SEQ, 4}, st[2] = {HD * 2, 128}; const uint32_t box[3] = {64, 64, 2};
    make_map(enc, &p.kv, kv_ptr, 3, dims, st, box);
    const uint32_t box1[3] = {64, KV_TMA ? KV_TMA : 64, 1};
    make_map(enc, &p.kvs, kv_ptr, 3, dims, st, box1);
  }
  map2(enc, &p.part, d_out, OUTW, SEQ, 64, 64);
  {
    const uint64_t dims[3] = {64, NMAIN * 128, 4}, st[2] = {HD * 2, 128}; const uint32_t box[3] = {64, 64, 4};
    make_map(enc, &p.ctx, acc_ptr, 3, dims, st, box);
    const uint32_t box1[3] = {64, 64, 1};
    make_map(enc, &p.ctxs, acc_ptr, 3, dims, st, box1);
  }
  concat_heads__ssm_conv_h3__compressed_kv_cla__prompt_kernel<<<NCTA, NTHREADS, SMEM_BYTES>>>(p);
}
```

```cpp
#include <cuda_runtime.h>
#include <cuda_bf16.h>
#include <cuda.h>
#include <stdint.h>

namespace {

typedef __nv_bfloat16 bf16;

constexpr int SEQ  = 2048;
constexpr int DA   = 448;
constexpr int NH   = 16;
constexpr int HD   = 256;
constexpr int DM   = 448;
constexpr int DC   = 1024;
constexpr int OUTW = DA + DM;
constexpr int NMAIN = 128;
constexpr int NCONV = 4;
constexpr int NCTA  = NMAIN + NCONV;
constexpr int NTHREADS = 384;
constexpr int D_SPARE = 320;

__device__ __align__(1024) bf16 g_kv[2ull * SEQ * NH * HD];
__device__ __align__(1024) bf16 g_ctx[(size_t)NMAIN * 128 * HD];
constexpr uint32_t CV_HE = 272 * 16, CV_HCOPY = 4160, CV_D = CV_HE + 4144, CV_BYTES = CV_HE + 2 * CV_HCOPY;
__device__ __align__(128) uint8_t g_xs[NMAIN * CV_BYTES];
struct alignas(128) Flag { unsigned v; unsigned pad[31]; };
struct Flags {
  Flag kv_ready[3 * NH];
  Flag ctx_ready[NMAIN * 2];
  Flag out_ready[16 * 2];
  Flag xs_ready[NH];
  Flag zs_ready[NH];
  alignas(128) unsigned long long done;
};
__device__ Flags g_flags;
#define TS(i)
#define TSG(i)
#define GT(i)
#define PT(i)
#define WHICH_TS 0
#define PCLK(var)
#define PACC(acc, t0)
#define PDECL
#define PDUMP()

#define TR_DECL
#define TR(tag)
#define TR_END()

struct alignas(64) Params {
  CUtensorMap ckv;
  CUtensorMap wuk;
  CUtensorMap wuv;
  CUtensorMap x;
  CUtensorMap wq;
  CUtensorMap wqp;
  CUtensorMap kv;
  CUtensorMap kvs;
  CUtensorMap part;
  CUtensorMap ctx;
  CUtensorMap ctxs;
  CUtensorMap wo;
  CUtensorMap ak, ak8, av, aq, ao;
  const bf16 *a_q, *a_k, *a_v, *a_shift, *a_ssmk, *a_D, *b_x, *b_wo;
  bf16* out;
  uint32_t one;
};

constexpr uint32_t P1_STAGE = 49152;
constexpr uint32_t P1_STG   = 196608;
constexpr uint32_t SLOT     = 32768;
constexpr int      NSLOT    = 5;
constexpr uint32_t QREG     = 163840;
constexpr uint32_t CV_X = 4 * SLOT + 16384, CV_R = 3 * SLOT;
static_assert(CV_BYTES <= 16384 && CV_BYTES % 128 == 0, "SSM operands");
constexpr uint32_t BARS     = 229376;
constexpr uint32_t SMEM_BYTES = BARS + 512 + 1024;
enum : uint32_t {
  B_P1_FULL = 0, B_P1_EMPTY = 4, B_RG_FULL = 8, B_RG_EMPTY = 13, B_ST_FULL = 18, B_ST_EMPTY = 20,
  B_XS = 22, B_PFREE = 23, B_S2_FULL = 28, B_S2_EMPTY = 32, B_QFREE = 36, B_CTXF = 38, B_KV = 40, B_GATE = 43, B_CTXS = 44, B_GFREE = 52, B_CONV = 53, B_COUNT = 54
};

__device__ __forceinline__ uint32_t smem_u32(const void* p) { return (uint32_t)__cvta_generic_to_shared(p); }
__device__ __forceinline__ void mbar_init(uint32_t bar, uint32_t cnt) {
  asm volatile("mbarrier.init.shared::cta.b64 [%0], %1;" :: "r"(bar), "r"(cnt) : "memory");
}
__device__ __forceinline__ void mbar_expect_tx(uint32_t bar, uint32_t bytes) {
  asm volatile("mbarrier.arrive.expect_tx.shared::cta.b64 _, [%0], %1;" :: "r"(bar), "r"(bytes) : "memory");
}
__device__ __forceinline__ void mbar_arrive(uint32_t bar) {
  asm volatile("mbarrier.arrive.shared::cta.b64 _, [%0];" :: "r"(bar) : "memory");
}
__device__ __forceinline__ void mbar_arrive_n(uint32_t bar, uint32_t n) {
  asm volatile("mbarrier.arrive.shared::cta.b64 _, [%0], %1;" :: "r"(bar), "r"(n) : "memory");
}
__device__ __forceinline__ void mbar_arrive_remote(uint32_t bar, uint32_t cta) {
  asm volatile("{\n.reg .b32 ra;\nmapa.shared::cluster.u32 ra, %0, %1;\n"
               "mbarrier.arrive.shared::cluster.b64 _, [ra];\n}" :: "r"(bar), "r"(cta) : "memory");
}
__device__ __forceinline__ uint32_t map_cta(uint32_t a, uint32_t cta) { uint32_t r; asm("mapa.shared::cluster.u32 %0, %1, %2;" : "=r"(r) : "r"(a), "r"(cta)); return r; }
__device__ __forceinline__ void mbar_arrive_pair(uint32_t mapped, uint32_t n, int lane) {
  asm volatile("{\n.reg .pred p;\nsetp.lt.s32 p, %2, 2;\n@p mbarrier.arrive.shared::cluster.b64 _, [%0], %1;\n}" :: "r"(mapped), "r"(n), "r"(lane) : "memory");
}
__device__ __forceinline__ bool mbar_try(uint32_t bar, uint32_t parity) {
  uint32_t ok;
  asm volatile("{\n.reg .pred p;\nmbarrier.try_wait.parity.shared::cta.b64 p, [%1], %2;\nselp.u32 %0, 1, 0, p;\n}"
               : "=r"(ok) : "r"(bar), "r"(parity) : "memory");
  return ok;
}
#define FLAG_NS 100
#define NAP_NS 100
constexpr uint32_t SPIN_LIMIT = 1u << 24;
__device__ __forceinline__ void mbar_wait(uint32_t bar, uint32_t parity) {
  if (mbar_try(bar, parity)) return;
  uint32_t n = 0;
  while (!mbar_try(bar, parity)) { if (++n > SPIN_LIMIT) __trap(); }
}
__device__ __forceinline__ void mbar_wait_nap(uint32_t bar, uint32_t parity) {
  uint32_t n = 0;
  while (!mbar_try(bar, parity)) { if (++n > (SPIN_LIMIT >> 2)) __trap(); __nanosleep(NAP_NS); }
}
__device__ __forceinline__ void mbar_wait_slow(uint32_t bar, uint32_t parity) {
  uint32_t n = 0;
  while (!mbar_try(bar, parity)) { if (++n > (SPIN_LIMIT >> 4)) __trap(); __nanosleep(500); }
}
__device__ __forceinline__ unsigned load_epoch() {
  unsigned long long e; asm volatile("ld.relaxed.gpu.global.u64 %0, [%1];" : "=l"(e) : "l"(&g_flags.done) : "memory"); return (unsigned)(e / NMAIN);
}
__device__ __forceinline__ void flag_wait(const unsigned* f, unsigned count, unsigned epoch) {
  const unsigned target = (epoch + 1) * count;
  uint32_t n = 0;
  while (true) {
    unsigned v;
    asm volatile("ld.acquire.gpu.global.u32 %0, [%1];" : "=r"(v) : "l"(f) : "memory");
    if ((int)(v - target) >= 0) break;
    if (++n > SPIN_LIMIT) __trap();
    __nanosleep(FLAG_NS);
  }
}
__device__ __forceinline__ void flag_wait_fast(const unsigned* f, unsigned count, unsigned epoch) {
  const unsigned target = (epoch + 1) * count;
  uint32_t n = 0;
  while (true) {
    unsigned v;
    asm volatile("ld.acquire.gpu.global.u32 %0, [%1];" : "=r"(v) : "l"(f) : "memory");
    if ((int)(v - target) >= 0) break;
    if (++n > SPIN_LIMIT) __trap();
  }
}
__device__ __forceinline__ void fence_async_all() { asm volatile("fence.proxy.async;" ::: "memory"); }
__device__ __forceinline__ void flag_signal(unsigned* f) {
  asm volatile("fence.acq_rel.gpu;" ::: "memory");
  asm volatile("red.relaxed.gpu.global.add.u32 [%0], 1;" :: "l"(f) : "memory");
}
__device__ __forceinline__ void flag_signal_after_bulk(unsigned* f) {
  asm volatile("red.relaxed.gpu.global.add.u32 [%0], 1;" :: "l"(f) : "memory");
}
__device__ __forceinline__ void fence_async_smem() { asm volatile("fence.proxy.async.shared::cta;" ::: "memory"); }
constexpr uint64_t POL_NORMAL = 0x1000000000000000ull, POL_FIRST = 0x12F0000000000000ull;
__device__ __forceinline__ void tma_ld2(uint32_t dst, const CUtensorMap* m, uint32_t bar, int c0, int c1, uint64_t pol = POL_NORMAL) {
  asm volatile("cp.async.bulk.tensor.2d.shared::cluster.global.mbarrier::complete_tx::bytes.L2::cache_hint [%0], [%1, {%3, %4}], [%2], %5;"
               :: "r"(dst), "l"(m), "r"(bar), "r"(c0), "r"(c1), "l"(pol) : "memory");
}
__device__ __forceinline__ void tma_ld3(uint32_t dst, const CUtensorMap* m, uint32_t bar, int c0, int c1, int c2, uint64_t pol = POL_NORMAL) {
  asm volatile("cp.async.bulk.tensor.3d.shared::cluster.global.mbarrier::complete_tx::bytes.L2::cache_hint [%0], [%1, {%3, %4, %5}], [%2], %6;"
               :: "r"(dst), "l"(m), "r"(bar), "r"(c0), "r"(c1), "r"(c2), "l"(pol) : "memory");
}
__device__ __forceinline__ void tma_ld3_mc(uint32_t dst, const CUtensorMap* m, uint32_t bar, int c0, int c1, int c2, uint64_t pol = POL_NORMAL) {
  asm volatile("cp.async.bulk.tensor.3d.shared::cluster.global.mbarrier::complete_tx::bytes.multicast::cluster.L2::cache_hint [%0], [%1, {%3, %4, %5}], [%2], %6, %7;"
               :: "r"(dst), "l"(m), "r"(bar), "r"(c0), "r"(c1), "r"(c2), "h"((uint16_t)3), "l"(pol) : "memory");
}
__device__ __forceinline__ void bulk_ld(uint32_t dst, const void* src, uint32_t bytes, uint32_t bar) {
  asm volatile("cp.async.bulk.shared::cluster.global.mbarrier::complete_tx::bytes [%0], [%1], %2, [%3];"
               :: "r"(dst), "l"(src), "r"(bytes), "r"(bar) : "memory");
}
__device__ __forceinline__ void tma_st3(const CUtensorMap* m, uint32_t src, int c0, int c1, int c2, uint64_t pol = POL_NORMAL) {
  asm volatile("cp.async.bulk.tensor.3d.global.shared::cta.bulk_group.L2::cache_hint [%0, {%2, %3, %4}], [%1], %5;"
               :: "l"(m), "r"(src), "r"(c0), "r"(c1), "r"(c2), "l"(pol) : "memory");
}
__device__ __forceinline__ void tma_ld2_mc(uint32_t dst, const CUtensorMap* m, uint32_t bar, int c0, int c1) {
  asm volatile("cp.async.bulk.tensor.2d.shared::cluster.global.mbarrier::complete_tx::bytes.multicast::cluster [%0], [%1, {%3, %4}], [%2], %5;"
               :: "r"(dst), "l"(m), "r"(bar), "r"(c0), "r"(c1), "h"((uint16_t)3) : "memory");
}
__device__ __forceinline__ void tma_st2(const CUtensorMap* m, uint32_t src, int c0, int c1) {
  asm volatile("cp.async.bulk.tensor.2d.global.shared::cta.bulk_group [%0, {%2, %3}], [%1];"
               :: "l"(m), "r"(src), "r"(c0), "r"(c1) : "memory");
}
__device__ __forceinline__ void tma_red2(const CUtensorMap* m, uint32_t src, int c0, int c1) {
  asm volatile("cp.reduce.async.bulk.tensor.2d.global.shared::cta.add.tile.bulk_group [%0, {%2, %3}], [%1];"
               :: "l"(m), "r"(src), "r"(c0), "r"(c1) : "memory");
}
__device__ __forceinline__ void tma_pf3(const CUtensorMap* m, int c0, int c1, int c2) {
  asm volatile("cp.async.bulk.prefetch.tensor.3d.L2.global.tile [%0, {%1, %2, %3}];" :: "l"(m), "r"(c0), "r"(c1), "r"(c2) : "memory");
}
__device__ __forceinline__ void tma_pf2(const CUtensorMap* m, int c0, int c1) {
  asm volatile("cp.async.bulk.prefetch.tensor.2d.L2.global.tile [%0, {%1, %2}];" :: "l"(m), "r"(c0), "r"(c1) : "memory");
}
__device__ __forceinline__ void bulk_prefetch(const void* src, uint32_t bytes) {
  asm volatile("cp.async.bulk.prefetch.L2.global [%0], %1;" :: "l"(src), "r"(bytes) : "memory");
}
__device__ __forceinline__ void bulk_commit() { asm volatile("cp.async.bulk.commit_group;" ::: "memory"); }
__device__ __forceinline__ void bulk_wait_read() { asm volatile("cp.async.bulk.wait_group.read 0;" ::: "memory"); }
__device__ __forceinline__ void bulk_wait_all() { asm volatile("cp.async.bulk.wait_group 0;" ::: "memory"); }
__device__ __forceinline__ void prefetch_map(const CUtensorMap* m) { asm volatile("prefetch.tensormap [%0];" :: "l"(m) : "memory"); }
__device__ __forceinline__ void wg_fence() { asm volatile("wgmma.fence.sync.aligned;" ::: "memory"); }
__device__ __forceinline__ void wg_commit() { asm volatile("wgmma.commit_group.sync.aligned;" ::: "memory"); }
template <int N> __device__ __forceinline__ void wg_wait() { asm volatile("wgmma.wait_group.sync.aligned %0;" :: "n"(N) : "memory"); }
template <int N> __device__ __forceinline__ void reg_fence(float (&d)[N]) {
#pragma unroll
  for (int i = 0; i < N; i++) asm volatile("" : "+f"(d[i]) :: "memory");
}
template <int N> __device__ __forceinline__ void reg_fence(uint32_t (&d)[N]) {
#pragma unroll
  for (int i = 0; i < N; i++) asm volatile("" : "+r"(d[i]) :: "memory");
}
__device__ __forceinline__ uint32_t fresh_tid() { uint32_t t; asm volatile("mov.u32 %0, %%tid.x;" : "=r"(t)); return t; }
__device__ __forceinline__ uint32_t lane_base16() {
  const uint32_t t = fresh_tid(), lane = t & 31, wq = (t >> 5) & 3;
  return (16 * wq + (lane & 7) + 8 * ((lane >> 3) & 1)) * 128 + (((lane >> 4) ^ (lane & 7)) << 4);
}
__device__ __forceinline__ void named_sync(int id, int n) { asm volatile("bar.sync %0, %1;" :: "r"(id), "r"(n) : "memory"); }
__device__ __forceinline__ void named_arrive(int id, int n) { asm volatile("bar.arrive %0, %1;" :: "r"(id), "r"(n) : "memory"); }
__device__ __forceinline__ uint32_t pack_bf16(float lo, float hi) {
  uint32_t r; asm("cvt.rn.bf16x2.f32 %0, %1, %2;" : "=r"(r) : "f"(hi), "f"(lo)); return r;
}
__device__ __forceinline__ float ex2(float x) { float y; asm("ex2.approx.ftz.f32 %0, %1;" : "=f"(y) : "f"(x)); return y; }
__device__ __forceinline__ void stsm4(uint32_t addr, uint32_t a, uint32_t b, uint32_t c, uint32_t d) {
  asm volatile("stmatrix.sync.aligned.m8n8.x4.shared.b16 [%0], {%1, %2, %3, %4};" :: "r"(addr), "r"(a), "r"(b), "r"(c), "r"(d) : "memory");
}
__device__ __forceinline__ void stsm4t(uint32_t addr, uint32_t a, uint32_t b, uint32_t c, uint32_t d) {
  asm volatile("stmatrix.sync.aligned.m8n8.x4.trans.shared.b16 [%0], {%1, %2, %3, %4};" :: "r"(addr), "r"(a), "r"(b), "r"(c), "r"(d) : "memory");
}
__device__ __forceinline__ uint64_t mk_desc(uint32_t addr, uint32_t lbo, uint32_t sbo) {
  return (uint64_t)(((addr & 0x3FFFF) >> 4) | ((lbo >> 4) << 16)) | ((uint64_t)((sbo >> 4) | (1u << 30)) << 32);
}
__device__ __forceinline__ uint64_t desc_k(uint32_t addr)  { return mk_desc(addr, 16, 1024); }
__device__ __forceinline__ uint64_t desc_mn(uint32_t addr) { return mk_desc(addr, 8192, 1024); }
__device__ __forceinline__ uint64_t desc_add(uint64_t d, uint32_t bytes) { return d + (bytes >> 4); }

__device__ __forceinline__ void wgmma_ss_n256_tb(float (&d)[128], uint64_t da, uint64_t db, int sd) {
  asm volatile("{\n.reg .pred p;\nsetp.ne.b32 p, %130, 0;\n"
    "wgmma.mma_async.sync.aligned.m64n256k16.f32.bf16.bf16 "
    "{%0, %1, %2, %3, %4, %5, %6, %7, %8, %9, %10, %11, %12, %13, %14, %15, "
    "%16, %17, %18, %19, %20, %21, %22, %23, %24, %25, %26, %27, %28, %29, %30, %31, "
    "%32, %33, %34, %35, %36, %37, %38, %39, %40, %41, %42, %43, %44, %45, %46, %47, "
    "%48, %49, %50, %51, %52, %53, %54, %55, %56, %57, %58, %59, %60, %61, %62, %63, "
    "%64, %65, %66, %67, %68, %69, %70, %71, %72, %73, %74, %75, %76, %77, %78, %79, "
    "%80, %81, %82, %83, %84, %85, %86, %87, %88, %89, %90, %91, %92, %93, %94, %95, "
    "%96, %97, %98, %99, %100, %101, %102, %103, %104, %105, %106, %107, %108, %109, %110, %111, "
    "%112, %113, %114, %115, %116, %117, %118, %119, %120, %121, %122, %123, %124, %125, %126, %127}, "
    "%128, %129, p, 1, 1, 0, 1;\n}"
    : "+f"(d[0]), "+f"(d[1]), "+f"(d[2]), "+f"(d[3]), "+f"(d[4]), "+f"(d[5]), "+f"(d[6]), "+f"(d[7]),
      "+f"(d[8]), "+f"(d[9]), "+f"(d[10]), "+f"(d[11]), "+f"(d[12]), "+f"(d[13]), "+f"(d[14]), "+f"(d[15]),
      "+f"(d[16]), "+f"(d[17]), "+f"(d[18]), "+f"(d[19]), "+f"(d[20]), "+f"(d[21]), "+f"(d[22]), "+f"(d[23]),
      "+f"(d[24]), "+f"(d[25]), "+f"(d[26]), "+f"(d[27]), "+f"(d[28]), "+f"(d[29]), "+f"(d[30]), "+f"(d[31]),
      "+f"(d[32]), "+f"(d[33]), "+f"(d[34]), "+f"(d[35]), "+f"(d[36]), "+f"(d[37]), "+f"(d[38]), "+f"(d[39]),
      "+f"(d[40]), "+f"(d[41]), "+f"(d[42]), "+f"(d[43]), "+f"(d[44]), "+f"(d[45]), "+f"(d[46]), "+f"(d[47]),
      "+f"(d[48]), "+f"(d[49]), "+f"(d[50]), "+f"(d[51]), "+f"(d[52]), "+f"(d[53]), "+f"(d[54]), "+f"(d[55]),
      "+f"(d[56]), "+f"(d[57]), "+f"(d[58]), "+f"(d[59]), "+f"(d[60]), "+f"(d[61]), "+f"(d[62]), "+f"(d[63]),
      "+f"(d[64]), "+f"(d[65]), "+f"(d[66]), "+f"(d[67]), "+f"(d[68]), "+f"(d[69]), "+f"(d[70]), "+f"(d[71]),
      "+f"(d[72]), "+f"(d[73]), "+f"(d[74]), "+f"(d[75]), "+f"(d[76]), "+f"(d[77]), "+f"(d[78]), "+f"(d[79]),
      "+f"(d[80]), "+f"(d[81]), "+f"(d[82]), "+f"(d[83]), "+f"(d[84]), "+f"(d[85]), "+f"(d[86]), "+f"(d[87]),
      "+f"(d[88]), "+f"(d[89]), "+f"(d[90]), "+f"(d[91]), "+f"(d[92]), "+f"(d[93]), "+f"(d[94]), "+f"(d[95]),
      "+f"(d[96]), "+f"(d[97]), "+f"(d[98]), "+f"(d[99]), "+f"(d[100]), "+f"(d[101]), "+f"(d[102]), "+f"(d[103]),
      "+f"(d[104]), "+f"(d[105]), "+f"(d[106]), "+f"(d[107]), "+f"(d[108]), "+f"(d[109]), "+f"(d[110]), "+f"(d[111]),
      "+f"(d[112]), "+f"(d[113]), "+f"(d[114]), "+f"(d[115]), "+f"(d[116]), "+f"(d[117]), "+f"(d[118]), "+f"(d[119]),
      "+f"(d[120]), "+f"(d[121]), "+f"(d[122]), "+f"(d[123]), "+f"(d[124]), "+f"(d[125]), "+f"(d[126]), "+f"(d[127])
    : "l"(da), "l"(db), "r"(sd));
}
__device__ __forceinline__ void wgmma_ss_n64(float (&d)[32], uint64_t da, uint64_t db, int sd) {
  asm volatile("{\n.reg .pred p;\nsetp.ne.b32 p, %34, 0;\n"
    "wgmma.mma_async.sync.aligned.m64n64k16.f32.bf16.bf16 "
    "{%0, %1, %2, %3, %4, %5, %6, %7, %8, %9, %10, %11, %12, %13, %14, %15, "
    "%16, %17, %18, %19, %20, %21, %22, %23, %24, %25, %26, %27, %28, %29, %30, %31}, "
    "%32, %33, p, 1, 1, 0, 0;\n}"
    : "+f"(d[0]), "+f"(d[1]), "+f"(d[2]), "+f"(d[3]), "+f"(d[4]), "+f"(d[5]), "+f"(d[6]), "+f"(d[7]),
      "+f"(d[8]), "+f"(d[9]), "+f"(d[10]), "+f"(d[11]), "+f"(d[12]), "+f"(d[13]), "+f"(d[14]), "+f"(d[15]),
      "+f"(d[16]), "+f"(d[17]), "+f"(d[18]), "+f"(d[19]), "+f"(d[20]), "+f"(d[21]), "+f"(d[22]), "+f"(d[23]),
      "+f"(d[24]), "+f"(d[25]), "+f"(d[26]), "+f"(d[27]), "+f"(d[28]), "+f"(d[29]), "+f"(d[30]), "+f"(d[31])
    : "l"(da), "l"(db), "r"(sd));
}
__device__ __forceinline__ void wgmma_rs_n256_tb(float (&d)[128], uint32_t a0, uint32_t a1, uint32_t a2, uint32_t a3, uint64_t db, int sd) {
  asm volatile("{\n.reg .pred p;\nsetp.ne.b32 p, %133, 0;\n"
    "wgmma.mma_async.sync.aligned.m64n256k16.f32.bf16.bf16 "
    "{%0, %1, %2, %3, %4, %5, %6, %7, %8, %9, %10, %11, %12, %13, %14, %15, "
    "%16, %17, %18, %19, %20, %21, %22, %23, %24, %25, %26, %27, %28, %29, %30, %31, "
    "%32, %33, %34, %35, %36, %37, %38, %39, %40, %41, %42, %43, %44, %45, %46, %47, "
    "%48, %49, %50, %51, %52, %53, %54, %55, %56, %57, %58, %59, %60, %61, %62, %63, "
    "%64, %65, %66, %67, %68, %69, %70, %71, %72, %73, %74, %75, %76, %77, %78, %79, "
    "%80, %81, %82, %83, %84, %85, %86, %87, %88, %89, %90, %91, %92, %93, %94, %95, "
    "%96, %97, %98, %99, %100, %101, %102, %103, %104, %105, %106, %107, %108, %109, %110, %111, "
    "%112, %113, %114, %115, %116, %117, %118, %119, %120, %121, %122, %123, %124, %125, %126, %127}, "
    "{%128, %129, %130, %131}, %132, p, 1, 1, 1;\n}"
    : "+f"(d[0]), "+f"(d[1]), "+f"(d[2]), "+f"(d[3]), "+f"(d[4]), "+f"(d[5]), "+f"(d[6]), "+f"(d[7]),
      "+f"(d[8]), "+f"(d[9]), "+f"(d[10]), "+f"(d[11]), "+f"(d[12]), "+f"(d[13]), "+f"(d[14]), "+f"(d[15]),
      "+f"(d[16]), "+f"(d[17]), "+f"(d[18]), "+f"(d[19]), "+f"(d[20]), "+f"(d[21]), "+f"(d[22]), "+f"(d[23]),
      "+f"(d[24]), "+f"(d[25]), "+f"(d[26]), "+f"(d[27]), "+f"(d[28]), "+f"(d[29]), "+f"(d[30]), "+f"(d[31]),
      "+f"(d[32]), "+f"(d[33]), "+f"(d[34]), "+f"(d[35]), "+f"(d[36]), "+f"(d[37]), "+f"(d[38]), "+f"(d[39]),
      "+f"(d[40]), "+f"(d[41]), "+f"(d[42]), "+f"(d[43]), "+f"(d[44]), "+f"(d[45]), "+f"(d[46]), "+f"(d[47]),
      "+f"(d[48]), "+f"(d[49]), "+f"(d[50]), "+f"(d[51]), "+f"(d[52]), "+f"(d[53]), "+f"(d[54]), "+f"(d[55]),
      "+f"(d[56]), "+f"(d[57]), "+f"(d[58]), "+f"(d[59]), "+f"(d[60]), "+f"(d[61]), "+f"(d[62]), "+f"(d[63]),
      "+f"(d[64]), "+f"(d[65]), "+f"(d[66]), "+f"(d[67]), "+f"(d[68]), "+f"(d[69]), "+f"(d[70]), "+f"(d[71]),
      "+f"(d[72]), "+f"(d[73]), "+f"(d[74]), "+f"(d[75]), "+f"(d[76]), "+f"(d[77]), "+f"(d[78]), "+f"(d[79]),
      "+f"(d[80]), "+f"(d[81]), "+f"(d[82]), "+f"(d[83]), "+f"(d[84]), "+f"(d[85]), "+f"(d[86]), "+f"(d[87]),
      "+f"(d[88]), "+f"(d[89]), "+f"(d[90]), "+f"(d[91]), "+f"(d[92]), "+f"(d[93]), "+f"(d[94]), "+f"(d[95]),
      "+f"(d[96]), "+f"(d[97]), "+f"(d[98]), "+f"(d[99]), "+f"(d[100]), "+f"(d[101]), "+f"(d[102]), "+f"(d[103]),
      "+f"(d[104]), "+f"(d[105]), "+f"(d[106]), "+f"(d[107]), "+f"(d[108]), "+f"(d[109]), "+f"(d[110]), "+f"(d[111]),
      "+f"(d[112]), "+f"(d[113]), "+f"(d[114]), "+f"(d[115]), "+f"(d[116]), "+f"(d[117]), "+f"(d[118]), "+f"(d[119]),
      "+f"(d[120]), "+f"(d[121]), "+f"(d[122]), "+f"(d[123]), "+f"(d[124]), "+f"(d[125]), "+f"(d[126]), "+f"(d[127])
    : "r"(a0), "r"(a1), "r"(a2), "r"(a3), "l"(db), "r"(sd));
}
__device__ __forceinline__ void wgmma_rs_n64_tb(float (&d)[32], uint32_t a0, uint32_t a1, uint32_t a2, uint32_t a3, uint64_t db, int sd) {
  asm volatile("{\n.reg .pred p;\nsetp.ne.b32 p, %37, 0;\n"
    "wgmma.mma_async.sync.aligned.m64n64k16.f32.bf16.bf16 "
    "{%0, %1, %2, %3, %4, %5, %6, %7, %8, %9, %10, %11, %12, %13, %14, %15, "
    "%16, %17, %18, %19, %20, %21, %22, %23, %24, %25, %26, %27, %28, %29, %30, %31}, "
    "{%32, %33, %34, %35}, %36, p, 1, 1, 1;\n}"
    : "+f"(d[0]), "+f"(d[1]), "+f"(d[2]), "+f"(d[3]), "+f"(d[4]), "+f"(d[5]), "+f"(d[6]), "+f"(d[7]),
      "+f"(d[8]), "+f"(d[9]), "+f"(d[10]), "+f"(d[11]), "+f"(d[12]), "+f"(d[13]), "+f"(d[14]), "+f"(d[15]),
      "+f"(d[16]), "+f"(d[17]), "+f"(d[18]), "+f"(d[19]), "+f"(d[20]), "+f"(d[21]), "+f"(d[22]), "+f"(d[23]),
      "+f"(d[24]), "+f"(d[25]), "+f"(d[26]), "+f"(d[27]), "+f"(d[28]), "+f"(d[29]), "+f"(d[30]), "+f"(d[31])
    : "r"(a0), "r"(a1), "r"(a2), "r"(a3), "l"(db), "r"(sd));
}
__device__ __forceinline__ void wgmma_rs_n64(float (&d)[32], uint32_t a0, uint32_t a1, uint32_t a2, uint32_t a3, uint64_t db, int sd) {
  asm volatile("{\n.reg .pred p;\nsetp.ne.b32 p, %37, 0;\n"
    "wgmma.mma_async.sync.aligned.m64n64k16.f32.bf16.bf16 "
    "{%0, %1, %2, %3, %4, %5, %6, %7, %8, %9, %10, %11, %12, %13, %14, %15, "
    "%16, %17, %18, %19, %20, %21, %22, %23, %24, %25, %26, %27, %28, %29, %30, %31}, "
    "{%32, %33, %34, %35}, %36, p, 1, 1, 0;\n}"
    : "+f"(d[0]), "+f"(d[1]), "+f"(d[2]), "+f"(d[3]), "+f"(d[4]), "+f"(d[5]), "+f"(d[6]), "+f"(d[7]),
      "+f"(d[8]), "+f"(d[9]), "+f"(d[10]), "+f"(d[11]), "+f"(d[12]), "+f"(d[13]), "+f"(d[14]), "+f"(d[15]),
      "+f"(d[16]), "+f"(d[17]), "+f"(d[18]), "+f"(d[19]), "+f"(d[20]), "+f"(d[21]), "+f"(d[22]), "+f"(d[23]),
      "+f"(d[24]), "+f"(d[25]), "+f"(d[26]), "+f"(d[27]), "+f"(d[28]), "+f"(d[29]), "+f"(d[30]), "+f"(d[31])
    : "r"(a0), "r"(a1), "r"(a2), "r"(a3), "l"(db), "r"(sd));
}

__device__ __forceinline__ uint4 lds16(uint32_t a) {
  uint4 v; asm volatile("ld.shared.v4.u32 {%0, %1, %2, %3}, [%4];" : "=r"(v.x), "=r"(v.y), "=r"(v.z), "=r"(v.w) : "r"(a) : "memory"); return v;
}
__device__ __forceinline__ void sts16(uint32_t a, uint32_t x, uint32_t y, uint32_t z, uint32_t w) {
  asm volatile("st.shared.v4.u32 [%0], {%1, %2, %3, %4};" :: "r"(a), "r"(x), "r"(y), "r"(z), "r"(w) : "memory");
}
__device__ __forceinline__ uint32_t lds4(uint32_t a) { uint32_t v; asm volatile("ld.shared.u32 %0, [%1];" : "=r"(v) : "r"(a) : "memory"); return v; }
__device__ __forceinline__ uint32_t lds4v(uint32_t a) { uint32_t v; asm volatile("ld.volatile.shared.u32 %0, [%1];" : "=r"(v) : "r"(a) : "memory"); return v; }
__device__ __forceinline__ uint32_t bmul(uint32_t a, uint32_t b) { uint32_t r; asm("mul.rn.bf16x2 %0, %1, %2;" : "=r"(r) : "r"(a), "r"(b)); return r; }
__device__ __forceinline__ uint32_t bfma(uint32_t a, uint32_t b, uint32_t c) { uint32_t r; asm("fma.rn.bf16x2 %0, %1, %2, %3;" : "=r"(r) : "r"(a), "r"(b), "r"(c)); return r; }
__device__ __forceinline__ uint32_t badd(uint32_t a, uint32_t b) { uint32_t r; asm("add.rn.bf16x2 %0, %1, %2;" : "=r"(r) : "r"(a), "r"(b)); return r; }

__device__ __forceinline__ void ldsm4(uint32_t (&r)[4], uint32_t a) {
  asm volatile("ldmatrix.sync.aligned.m8n8.x4.shared.b16 {%0, %1, %2, %3}, [%4];" : "=r"(r[0]), "=r"(r[1]), "=r"(r[2]), "=r"(r[3]) : "r"(a) : "memory");
}
__device__ __forceinline__ void ldsm4t(uint32_t (&r)[4], uint32_t a) {
  asm volatile("ldmatrix.sync.aligned.m8n8.x4.trans.shared.b16 {%0, %1, %2, %3}, [%4];" : "=r"(r[0]), "=r"(r[1]), "=r"(r[2]), "=r"(r[3]) : "r"(a) : "memory");
}
__device__ __forceinline__ uint32_t transpose8(uint32_t a) { uint32_t d; asm volatile("movmatrix.sync.aligned.m8n8.trans.b16 %0, %1;" : "=r"(d) : "r"(a)); return d; }

__device__ __forceinline__ void mma16816(float (&d)[4], const uint32_t (&a)[4], uint32_t b0, uint32_t b1) {
  asm volatile("mma.sync.aligned.m16n8k16.row.col.f32.bf16.bf16.f32 {%0, %1, %2, %3}, {%4, %5, %6, %7}, {%8, %9}, {%0, %1, %2, %3};"
               : "+f"(d[0]), "+f"(d[1]), "+f"(d[2]), "+f"(d[3]) : "r"(a[0]), "r"(a[1]), "r"(a[2]), "r"(a[3]), "r"(b0), "r"(b1));
}

#define P1_SPLIT 0
#define O_ROT 1
#define STG_K1 2
#define STG_K2 10
#define STG_Q1 (KV_TMA ? 1 : 2)
#define STG_Q2 (KV_TMA ? 5 : 6)
#define CTX_K 0
#define PF_QA 48
#define PF_WV 99
#define PF_X 8
#define PF_WO 11
#define PF_CV 64
#define PACE_A 850
#define PACE_B 400
#define Q_PRE 2
#define KV_TMA 16
#define TPACE_A 3200
#define TPACE_B 800
#define EF_A 0
#define EF_W 0
#define EF_KV 0
#define EF_JS 8
#define EF_JL 8
#define EF_CTX 0
#define RELAXED_ARRIVE 1
#define ARRIVE_KK 12
#define SIDE_DELAY_NS 4000
#define KVH(h) (h)
#define HEAD_MAP 1
#define EARLY_LD 3
constexpr int RED_BAR = 6;
constexpr int CV_BAR = 5;
constexpr int PP_BAR = 3;
template <int V> struct Int { static constexpr int value = V; };
struct Ring {
  uint32_t slot, phase;
  __device__ __forceinline__ void next() { if (++slot == NSLOT) { slot = 0; phase ^= 1; } }
};
__device__ __forceinline__ uint32_t bar_addr(uint32_t sb, uint32_t i) { return sb + BARS + 8 * i; }
__device__ __forceinline__ uint32_t q_region(uint32_t sb, int w) { return sb + QREG + (w ^ 1) * 32768; }

struct Role { int h, j; };
__device__ __forceinline__ Role get_role() {
  int cta; asm volatile("mov.u32 %0, %%ctaid.x;" : "=r"(cta));
  const int c = cta >> 1;
  int h, u;
  if (c < 4) { h = 15; u = c; }
  else if (c < 36) { h = (c - 4) & 7; u = (c - 4) >> 3; }
  else { h = 8 + (c - 36) % 7; u = (c - 36) / 7; }
  return Role{h, 2 * u + (cta & 1)};
}
__device__ __forceinline__ int fresh_warp() { return __shfl_sync(0xffffffffu, fresh_tid() >> 5, 0); }

__device__ __forceinline__ int q_tile(int h, int j, int which) { return ((h < 8) == (which == 0)) ? 15 - j : j; }

__device__ __forceinline__ int o_chunk(int h, int c) { const int x = c + O_ROT * (h & 7); return x % 7; }

__device__ __forceinline__ int num_private(int qt) { return (qt & 1) ? 5 : 1; }
__device__ __forceinline__ void ring_acquire(uint32_t sb, Ring& r, uint32_t bytes) {
  mbar_wait(bar_addr(sb, B_RG_EMPTY + r.slot), r.phase ^ 1);
  mbar_expect_tx(bar_addr(sb, B_RG_FULL + r.slot), bytes);
}
__device__ __forceinline__ void load_tile4(uint32_t dst, const CUtensorMap* m, uint32_t full, int row, int blk0, int rank, bool shared, uint64_t pol = POL_NORMAL) {
  if (shared) {
    tma_ld3_mc(dst + rank * 16384, m, full, 0, row, blk0 + 2 * rank, pol);
  } else {
    tma_ld3(dst, m, full, 0, row, blk0, pol);
    tma_ld3(dst + 16384, m, full, 0, row, blk0 + 2, pol);
  }
}
__device__ __forceinline__ void producer_main(const Params& p, uint32_t sb) {
  const Role ro = get_role();
  const int h = ro.h, j = ro.j, rank = j & 1;
  for (int it = EARLY_LD; it < 71; it++) {
    const int t = it >> 4, k = it & 15, s = it & 3;
    mbar_wait(bar_addr(sb, B_P1_EMPTY + s), ((it >> 2) & 1) ^ 1);
    const uint32_t full = bar_addr(sb, B_P1_FULL + s), dst = sb + s * P1_STAGE;
    mbar_expect_tx(full, P1_STAGE);
    if (t < 4) {
      tma_ld2(dst, &p.ckv, full, k * 64, (2 * j + (t & 1)) * 128, ((EF_A >> t) & 1) ? POL_FIRST : POL_NORMAL);
      load_tile4(dst + 16384, (t >> 1) ? &p.wuv : &p.wuk, full, k * 64, h * 4, rank, true, ((EF_W >> t) & 1) ? POL_FIRST : POL_NORMAL);
    } else {
      tma_ld2(dst, &p.x, full, k * 64, q_tile(h, j, 0) * 128);
      load_tile4(dst + 16384, &p.wq, full, k * 64, h * 4, rank, true);
    }
    if (it >= PF_QA && it < PF_QA + 14) {
      const int i = it - PF_QA;
      bulk_prefetch(p.b_x + (size_t)(q_tile(h, j, 0) * 128 + (h & 7) * 16) * DM + i * 512, 1024);
      tma_pf2(&p.wqp, h * HD, (i * 8 + j) * 4);
    }
    if (it >= PF_CV && it < PF_CV + 3) {
      mbar_wait(bar_addr(sb, B_XS), 0);
      bulk_prefetch(g_xs + (size_t)(h * 8 + j) * CV_BYTES + (it - PF_CV) * (CV_BYTES / 3), CV_BYTES / 3);
    }
  }
  mbar_wait(bar_addr(sb, B_P1_EMPTY + 3), 0);
  mbar_wait(bar_addr(sb, B_XS), 0);
  mbar_expect_tx(bar_addr(sb, B_RG_FULL + 4), CV_BYTES);
  bulk_ld(sb + CV_X, g_xs + (size_t)(h * 8 + j) * CV_BYTES, CV_BYTES, bar_addr(sb, B_RG_FULL + 4));
  Ring r{0, 1};
  int hs = 5;
  auto acquire = [&](bool shared) {
    mbar_wait(bar_addr(sb, B_RG_EMPTY + r.slot), r.phase ^ 1);
    if (shared && hs < 5) {
      mbar_arrive_remote(bar_addr(sb, B_PFREE + r.slot), rank ^ 1);
      mbar_wait(bar_addr(sb, B_PFREE + r.slot), 0);
      hs++;
    }
    mbar_expect_tx(bar_addr(sb, B_RG_FULL + r.slot), 32768);
  };
  auto prefetch_wo = [&](int left) {
    const int i = PF_WO - left;
    if (PF_WO && i >= 0 && i < 8) bulk_prefetch(p.b_wo + (size_t)(h * HD + j * 32 + 4 * i) * DM, 4 * DM * 2);
  };
  mbar_wait(bar_addr(sb, B_KV), 0);
  for (int which = 0; which < 2; which++) {
    const int qt = q_tile(h, j, which);
    if (which == 1) {
      for (int kc = 0; kc < 7; kc++) {
        prefetch_wo(4 * qt + 4 + 7 - kc);
        ring_acquire(sb, r, 32768);
        load_tile4(sb + r.slot * SLOT, &p.wq, bar_addr(sb, B_RG_FULL + r.slot), kc * 64, h * 4, rank, false);
        r.next();
        if (kc == 0 || (kc & 1)) {
          ring_acquire(sb, r, kc == 0 ? 16384 : 32768);
          const uint32_t full = bar_addr(sb, B_RG_FULL + r.slot), dst = sb + r.slot * SLOT;
          tma_ld2(dst, &p.x, full, kc * 64, qt * 128);
          if (kc > 0) tma_ld2(dst + 16384, &p.x, full, kc * 64 + 64, qt * 128);
          r.next();
        }
      }
      hs = 0;
    }
    const int n = 2 * qt + 2, npriv = num_private(qt), nb = qt & ~1;
    for (int f = 0; f < 2 * n; f++) {
      if (which == 0) {
        const int i = f - max(2 * n - PF_X, 0);
        if (PF_X && i >= 0 && i < 4) bulk_prefetch(p.b_x + (size_t)((15 - qt) * 128 + (h & 7) * 16 + 4 * i) * DM, 4 * DM * 2);
      } else prefetch_wo(2 * n - f);
      const bool isK = (f == 0) || ((f & 1) && f < 2 * n - 1);
      const int i = isK ? (f + 1) >> 1 : (f == 2 * n - 1 ? n - 1 : (f >> 1) - 1);
      int tile = n - 1 - i;
      if (which == 0) { const int b = i >> 1; tile = b >= nb ? i : 2 * (2 * b < nb ? 2 * b : 2 * b - nb + 1) + (i & 1); }
      if (!isK) mbar_wait(bar_addr(sb, B_KV + 1 + ((tile >> 1) & 1)), 0);
      if (which == 0 && f < 2) mbar_wait(bar_addr(sb, B_P1_EMPTY + f), 1);
      const bool shared = (which ? f : 2 * n - 1 - f) >= npriv;
      acquire(shared);
      load_tile4(sb + r.slot * SLOT, &p.kv, bar_addr(sb, B_RG_FULL + r.slot), ((isK ? 0 : NH) + KVH(h)) * SEQ + tile * 64, 0, rank, shared,
                 (which ? (EF_KV & 2) : ((EF_KV & 1) && tile >= 16) || (EF_KV & 4)) ? POL_FIRST : POL_NORMAL);
      r.next();
    }
  }
  for (int i = 0; i < 14; i++) {
    acquire(true);
    tma_ld2_mc(sb + r.slot * SLOT + rank * 16384, &p.wo, bar_addr(sb, B_RG_FULL + r.slot), o_chunk(h, i >> 1) * 64, ((i & 1) ? h ^ 8 : h) * HD + rank * 128);
    r.next();
  }
}

__device__ __forceinline__ void storer_main(const Params& p, uint32_t sb) {
  const Role ro = get_role();
  const int h = ro.h, j = ro.j, w = fresh_warp() - 1;
  const uint32_t full = bar_addr(sb, B_ST_FULL + w), empty = bar_addr(sb, B_ST_EMPTY + w);
  const int lane = threadIdx.x & 31;
  const unsigned epoch = load_epoch();
  if (lane == 0) {
    for (int job = 0; job < 8; job++) {
      const int t = job >> 1, row = ((t >> 1) * NH + KVH(h)) * SEQ + (2 * j + (t & 1)) * 128 + w * 64;
      mbar_wait_nap(full, job & 1);
      for (int i = 0; i < 128 / KV_TMA; i++) {
        if (i) __nanosleep((job < 6 ? TPACE_A : TPACE_B) * KV_TMA / 128);
        tma_st3(&p.kvs, sb + P1_STG + w * 16384 + i * KV_TMA * 128, 0, row + (i * KV_TMA & 63), (job & 1) * 2 + (i * KV_TMA >> 6),
                j >= (h >= 8 ? EF_JS : EF_JL) ? POL_FIRST : POL_NORMAL);
      }
      bulk_commit();
      bulk_wait_read();
      mbar_arrive(empty);
      if (job >= 3 && (job & 1)) { bulk_wait_all(); flag_signal(&g_flags.kv_ready[3 * h + t - 1].v); }
    }
  }
  __syncwarp();
  const int cta = h * 8 + j, qt = q_tile(h, j, 1);
  const uint32_t qreg = q_region(sb, w);
  {
    mbar_wait_nap(bar_addr(sb, B_CTXS + 4 * w), 0);
    uint4* z = reinterpret_cast<uint4*>(p.out + (size_t)(qt * 128 + w * 64 + (h & 7) * 8 + (lane >> 2)) * OUTW + DA) + (lane & 3);
#pragma unroll
    for (int i = 0; i < 14; i++) z[4 * i] = make_uint4(0, 0, 0, 0);
    __syncwarp();
    if (lane != 0) return;
    for (int b = 0; b < 4; b++) {
      mbar_wait(bar_addr(sb, B_CTXS + 4 * w + b), 0);
      tma_st3(&p.ctxs, qreg + b * 8192, 0, cta * 128 + w * 64, b, ((EF_CTX >> (h >> 3)) & 1) ? POL_FIRST : POL_NORMAL);
      bulk_commit();
    }
    bulk_wait_read();
    mbar_arrive(empty);
    bulk_wait_all();
    flag_signal(&g_flags.ctx_ready[cta * 2 + w].v);
    flag_signal_after_bulk(&g_flags.out_ready[qt * 2 + w].v);
  }
  {
    const int wx = w ^ 1;
    flag_wait(&g_flags.ctx_ready[(cta ^ 64) * 2 + wx].v, 1, epoch);
    flag_wait(&g_flags.out_ready[qt * 2 + wx].v, 8, epoch);
    fence_async_all();
    mbar_wait_nap(bar_addr(sb, B_QFREE + w), 0);
    mbar_expect_tx(bar_addr(sb, B_CTXF + w), 32768);
    tma_ld3(qreg, &p.ctx, bar_addr(sb, B_CTXF + w), 0, (cta ^ 64) * 128 + wx * 64, 0);
    for (int ch = 0; ch < 7; ch++) {
      const int b = ch & 1;
      mbar_wait(bar_addr(sb, B_S2_FULL + w * 2 + b), (ch >> 1) & 1);
      tma_red2(&p.part, qreg + b * 8192, DA + o_chunk(h, ch) * 64, qt * 128 + wx * 64);
      bulk_commit();
      if (ch == 0 && w == 1) mbar_arrive(bar_addr(sb, B_GFREE));
      bulk_wait_read();
      mbar_arrive(bar_addr(sb, B_S2_EMPTY + w * 2 + b));
    }
    GT(48 + w);
    bulk_wait_all();
    GT(50 + w); GT(52 + w); GT(56);
  }
}

template <int OFF, int NB, int NREG>
__device__ __forceinline__ void store_blocks(uint32_t base, uint32_t lanebase, const uint32_t (&pk)[NREG]) {
#pragma unroll
  for (int J = 0; J < NB * 8; J += 2) {
    const uint32_t a = base + (J >> 3) * 8192 + (lanebase ^ ((J & 7) << 4));
    stsm4(a, pk[OFF + 2 * J], pk[OFF + 2 * J + 1], pk[OFF + 2 * J + 2], pk[OFF + 2 * J + 3]);
  }
}
__device__ __forceinline__ void warp_arrive(uint32_t bar, int lane) { __syncwarp(); if (lane == 0) mbar_arrive(bar); }
__device__ __forceinline__ void release(uint32_t bar, int lane, int rank, bool shared) {
  if (shared) { if (lane < 2) mbar_arrive_remote(bar, rank ^ lane); }
  else if (lane == 0) mbar_arrive_n(bar, 2);
}

template <int W> __device__ __forceinline__ constexpr int cv_tile(int u) { return 2 * u + ((u ^ W) & 1); }
__device__ __forceinline__ uint32_t cv_x_lane(uint32_t lane) { return (16 + (lane & 15) - (lane >> 4)) * 16; }
__device__ __forceinline__ uint32_t cv_h_lane(uint32_t lane, uint32_t hE, uint32_t hO) {
  const uint32_t g = lane >> 2, c = lane & 3;
  return (g & 1) ? hO + (15 + 2 * c - g) * 2 : hE + (16 + 2 * c - g) * 2;
}
template <int W>
__device__ __forceinline__ void conv_mma(float (&ca)[8][4], uint32_t xa, uint32_t ha, uint32_t sb, uint32_t lb, const uint32_t (&pk)[64]) {
  constexpr int N = 16 - W;
  uint32_t fx[N][4], fh[N][2];
  auto ld_h = [&](int i, int rr) { fh[i][0] = lds4(ha + i * 256 + rr * 32); fh[i][1] = lds4(ha + i * 256 + rr * 32 + 16); };
  ldsm4(fx[0], xa);
#pragma unroll
  for (int u = 0; u < 8; u++) ld_h(cv_tile<W>(u), 0);
  ldsm4(fx[1], xa + 256);
#pragma unroll
  for (int u = 0; u < 8; u++) if (cv_tile<W ^ 1>(u) < N) ld_h(cv_tile<W ^ 1>(u), 0);
#pragma unroll
  for (int i = 2; i < N; i++) ldsm4(fx[i], xa + i * 256);
#pragma unroll
  for (int sx = 0; sx < N; sx++) {
#pragma unroll
    for (int u = 0; u < 8; u++) {
      const int jj = cv_tile<W>(u) - sx;
      if (jj >= 0) mma16816(ca[u], fx[sx], fh[jj < 0 ? 0 : jj][0], fh[jj < 0 ? 0 : jj][1]);
    }
    ldsm4(fx[sx], xa + sx * 256 - 32);
    ld_h(N - 1 - sx, 1);
  }
  mbar_wait(bar_addr(sb, B_P1_EMPTY + 2), 1);
  if (W == 0) { mbar_wait(bar_addr(sb, B_ST_EMPTY), 1); mbar_wait(bar_addr(sb, B_ST_EMPTY + 1), 1); }
#pragma unroll
  for (int jj = 15; jj >= 0; jj--) {
    stsm4(q_region(sb, W) + (jj >> 2) * 8192 + (lb ^ ((jj & 3) << 5)), pk[4 * jj], pk[4 * jj + 1], pk[4 * jj + 2], pk[4 * jj + 3]);
#pragma unroll
    for (int u = 0; u < 8; u++) {
      const int sx = cv_tile<W>(u) - jj;
      if (sx >= 0) mma16816(ca[u], fx[sx < 0 ? 0 : sx], fh[jj < N ? jj : 0][0], fh[jj < N ? jj : 0][1]);
    }
  }
}

__device__ __forceinline__ void consumer_main(const Params& p, uint32_t sb) {
  const int lane = fresh_tid() & 31, w = (fresh_warp() >> 2) - 1;
  const uint32_t lb = lane_base16(), one = p.one;
  int qt, rank;
  { const Role ro = get_role(); qt = q_tile(ro.h, ro.j, 0); rank = ro.j & 1; }
  const uint32_t st_full = bar_addr(sb, B_ST_FULL + w), st_empty = bar_addr(sb, B_ST_EMPTY + w);
  const uint32_t stg = sb + P1_STG + w * 16384;

  auto turn_begin = [&]() { named_sync(PP_BAR + w, 256); };
  auto turn_end = [&]() { named_arrive(PP_BAR + (w ^ 1), 256); };
  if (w == 0) named_arrive(PP_BAR + 1, 256);
  float acc[128];
#pragma unroll
  for (int i = 0; i < 128; i++) acc[i] = 0.f;
  uint32_t pk[64];
#pragma unroll
  for (int i = 0; i < 64; i++) pk[i] = 0;
  PDECL;
  TR_DECL;
  TR(0);
  TSG(0); TS(1);
  const uint32_t qreg = q_region(sb, w);
  for (int t = 0; t < 5; t++) {
    const int nk = t < 4 ? 16 : 7;
#pragma unroll 1
    for (int k = 0; k < nk; k++) {
      const int it = t * 16 + k, s = k & 3;
      mbar_wait(bar_addr(sb, B_P1_FULL + s), (it >> 2) & 1);
      TR(1);
      const uint64_t da = desc_k(sb + s * P1_STAGE + w * 8192), db = desc_mn(sb + s * P1_STAGE + 16384);
      turn_begin();
      wg_fence();
#pragma unroll
      for (int kk = 0; kk < 4; kk++) wgmma_ss_n256_tb(acc, desc_add(da, kk * 32), desc_add(db, kk * 2048), (k | kk) != 0);
      wg_commit();
      turn_end();
      TR(3);
      wg_wait<1>();
      if (k > 0) release(bar_addr(sb, B_P1_EMPTY + ((k - 1) & 3)), lane, rank, true);
      const int k1 = t < 4 ? STG_K1 : STG_Q1, k2 = t < 4 ? STG_K2 : STG_Q2;
      if (t > 0 && (k == k1 || k == k2)) {
        const int job = 2 * (t - 1) + (k != k1);
        if (job > 0) mbar_wait(st_empty, (job - 1) & 1);
        if (k == k1) store_blocks<0, 2>(stg, lb, pk); else store_blocks<32, 2>(stg, lb, pk);
      }
      if (t > 0 && (k == k1 + 1 || k == k2 + 1)) { fence_async_smem(); warp_arrive(st_full, lane); }
      TR(5);
    }
    wg_wait<0>();
    TR(6);
    reg_fence(acc);
    release(bar_addr(sb, B_P1_EMPTY + ((nk - 1) & 3)), lane, rank, true);
#pragma unroll
    for (int i = 0; i < 64; i++) pk[i] = pack_bf16(acc[2 * i], acc[2 * i + 1]);
    TS(t < 4 ? 2 + t : 60);
  }
  TS(6);
  {
    const uint32_t wq = lb >> 11, ln = lane, cx = sb + CV_X;
    float ca[8][4];
#pragma unroll
    for (int i = 0; i < 8; i++) { ca[i][0] = 0.f; ca[i][1] = 0.f; ca[i][2] = 0.f; ca[i][3] = 0.f; }
    const uint32_t xa = cx + cv_x_lane(ln) - wq * 64, ha = cv_h_lane(ln, cx + CV_HE, cx + CV_HE + CV_HCOPY) + wq * 64;
    mbar_wait(bar_addr(sb, B_RG_FULL + 4), 0);
    TR(7); TS(19); TS(20);
    if (w) conv_mma<1>(ca, xa, ha, sb, lb, pk); else conv_mma<0>(ca, xa, ha, sb, lb, pk);
    TR(8); TS(21);
    const uint32_t ex = sb + CV_R + w * 16384 + ln * 16;
#pragma unroll
    for (int u = 0; u < 8; u++)
      sts16(ex + (wq * 8 + u) * 512, __float_as_uint(ca[u][0]), __float_as_uint(ca[u][1]), __float_as_uint(ca[u][2]), __float_as_uint(ca[u][3]));
  }
  auto conv_finish = [&]() {
    const uint32_t wq = lb >> 11, cx = sb + CV_X, ex = sb + CV_R + w * 16384 + lane * 16;
    const Role ro = get_role();
    uint8_t* gz = g_xs + (size_t)(ro.h * 8 + ro.j) * CV_BYTES;
    const uint32_t Dd = lds4(cx + CV_D);
    uint32_t z[2][2];
#pragma unroll
    for (int e = 0; e < 2; e++) {
      const uint32_t u = 2 * wq + e, nt = 2 * u + ((e ^ w) & 1);
      float y[4] = {0.f, 0.f, 0.f, 0.f};
#pragma unroll
      for (int v = 0; v < 4; v++) {
        const uint4 t = lds16(ex + (v * 8 + u) * 512);
        y[0] += __uint_as_float(t.x); y[1] += __uint_as_float(t.y); y[2] += __uint_as_float(t.z); y[3] += __uint_as_float(t.w);
      }
      const uint32_t o = (16 + 16 * nt) * 16 + lane * 4;
      *reinterpret_cast<uint32_t*>(gz + o)       = badd(pack_bf16(y[0], y[1]), bmul(lds4(cx + o), Dd));
      *reinterpret_cast<uint32_t*>(gz + o + 128) = badd(pack_bf16(y[2], y[3]), bmul(lds4(cx + o + 128), Dd));
    }
    __syncwarp();
    release(bar_addr(sb, B_RG_EMPTY + 3), lane, rank, true);
    release(bar_addr(sb, B_RG_EMPTY + 4), lane, rank, true);
    if (lane == 0) mbar_arrive(bar_addr(sb, B_CONV));
  };
  TS(15);
  TR(10);
  Ring r{0, 1};
  auto take = [&]() { const uint32_t sl = r.slot; mbar_wait(bar_addr(sb, B_RG_FULL + sl), r.phase); r.next(); return sl; };
  constexpr float SC = 0.0625f * 1.4426950408889634f;
  uint32_t ws;
#pragma unroll 1
  for (int which = 0;; which++) {
    float s[32];
#pragma unroll
    for (int i = 0; i < 32; i++) s[i] = 0.f;
    uint32_t pa[16];
    float b0, b1, l0, l1;
    const uint64_t dq = desc_k(qreg);
    uint64_t dk = 0, dqq = 0, dv = 0;
    auto prep_qk = [&](uint32_t kaddr) { dk = desc_k(kaddr); dqq = dq + (kaddr >> 31); asm volatile("" : "+l"(dk), "+l"(dqq)); };
    auto prep_pv = [&](uint32_t vaddr) { dv = desc_mn(vaddr); asm volatile("" : "+l"(dv)); };
    auto issue_qk = [&]() {
#pragma unroll
      for (int kk = 0; kk < 16; kk++)
        wgmma_ss_n64(s, desc_add(dqq, (kk >> 2) * 8192 + (kk & 3) * 32), desc_add(dk, (kk >> 2) * 8192 + (kk & 3) * 32), kk != 0);
    };
    auto issue_pv = [&](int accumulate) {
#pragma unroll
      for (int kk = 0; kk < 4; kk++)
        wgmma_rs_n256_tb(acc, pa[4 * kk], pa[4 * kk + 1], pa[4 * kk + 2], pa[4 * kk + 3], desc_add(dv, kk * 2048), accumulate | kk);
    };
    auto mask_diag = [&]() {
      const int d = (int)((lb >> 11) << 4) + (lane >> 2) - 2 * (lane & 3);
#pragma unroll
      for (int jj = 0; jj < 8; jj++) {
        if (8 * jj > d)     s[4 * jj]     = -INFINITY;
        if (8 * jj + 1 > d) s[4 * jj + 1] = -INFINITY;
        if (8 * jj - 8 > d) s[4 * jj + 2] = -INFINITY;
        if (8 * jj - 7 > d) s[4 * jj + 3] = -INFINITY;
      }
    };
    auto row_max = [&](float& x0, float& x1) {
      x0 = fmaxf(s[0], s[1]); x1 = fmaxf(s[2], s[3]);
#pragma unroll
      for (int jj = 1; jj < 8; jj++) {
        x0 = fmaxf(x0, fmaxf(s[4 * jj], s[4 * jj + 1]));
        x1 = fmaxf(x1, fmaxf(s[4 * jj + 2], s[4 * jj + 3]));
      }
      x0 = fmaxf(x0, __shfl_xor_sync(0xffffffffu, x0, 1));
      x1 = fmaxf(x1, __shfl_xor_sync(0xffffffffu, x1, 1));
      x0 = fmaxf(x0, __shfl_xor_sync(0xffffffffu, x0, 2));
      x1 = fmaxf(x1, __shfl_xor_sync(0xffffffffu, x1, 2));
    };
    auto exps = [&](uint32_t (&pp)[16], float& r0, float& r1) {
      float t0, t1, t2, t3;
#pragma unroll
      for (int jj = 0; jj < 8; jj++) {
        const float e0 = ex2(fmaf(s[4 * jj], SC, b0)), e1 = ex2(fmaf(s[4 * jj + 1], SC, b0));
        const float e2 = ex2(fmaf(s[4 * jj + 2], SC, b1)), e3 = ex2(fmaf(s[4 * jj + 3], SC, b1));
        if (jj == 0) { t0 = e0; t1 = e1; t2 = e2; t3 = e3; } else { t0 += e0; t1 += e1; t2 += e2; t3 += e3; }
        pp[2 * jj] = pack_bf16(e0, e1); pp[2 * jj + 1] = pack_bf16(e2, e3);
      }
      r0 = t0 + t1; r1 = t2 + t3;
    };

    const bool up = w == which;
    const int n = 2 * qt + 2, nw = n - up, nloc = num_private(qt) + (which ? 0 : NSLOT);
    int fd = which ? 0 : 2 * n - 1;
    const int dir = which ? 1 : -1;
    auto skip = [&]() { r.next(); fd += dir; };
    auto give = [&](uint32_t sl, int d) {
      mbar_arrive_pair(map_cta(bar_addr(sb, B_RG_EMPTY + sl), d < nloc ? rank : rank ^ (lane & 1)), (d & ~2) == 0 ? 2 : 1, lane);
    };
    if (which && up) skip();
    uint32_t ks = take();
    TS(62 + which);
    TR(20);
    prep_qk(sb + ks * SLOT);
    turn_begin();
    wg_fence();
#pragma unroll
    for (int kk = 0; kk < 16; kk++)
      wgmma_rs_n64(s, pk[4 * kk], pk[4 * kk + 1], pk[4 * kk + 2], pk[4 * kk + 3], desc_add(dk, (kk >> 2) * 8192 + (kk & 3) * 32), kk != 0);
    wg_commit();
    turn_end();
    TR(21);
    if (!which) conv_finish();
    TR(23);
    if (which) mbar_wait(st_empty, 0);
    if (which && !up) store_blocks<0, Q_PRE>(qreg, lb, pk);
    TR(24);
    wg_wait<0>();
    TR(22);
    reg_fence(s);
    reg_fence(pk);
    give(ks, fd);
    fd += dir;
    if (which && up) { skip(); store_blocks<0, 4>(qreg, lb, pk); }
    if (which || nw == 1) mask_diag();
    row_max(b0, b1);
    if (which && !up) store_blocks<16 * Q_PRE, 4 - Q_PRE>(qreg + Q_PRE * 8192, lb, pk);
    b0 *= -SC; b1 *= -SC;
#pragma unroll
    for (int i = 0; i < 128; i++) acc[i] = 0.f;
    exps(pa, l0, l1);
    if (which && nw == 1) { fence_async_smem(); warp_arrive(bar_addr(sb, B_QFREE + w), lane); }
#pragma unroll 1
    for (int jj = 1; jj < nw; jj++) {
      ks = take();
      const uint32_t vs = take();
      if (jj == 1) fence_async_smem();
      TR(30);
#pragma unroll
      for (int i = 0; i < 32; i++) s[i] = 0.f;
      prep_qk(sb + ks * SLOT);
      prep_pv(sb + vs * SLOT);
      turn_begin();
      wg_fence();
      issue_qk();
      wg_commit();
      issue_pv(1);
      wg_commit();
      turn_end();
      TR(31);
      wg_wait<1>();
      TR(32);
      reg_fence(s);
      give(ks, fd);
      if (jj == nw - 1) {
        if (!which) mask_diag();
        else if (lane == 0) mbar_arrive(bar_addr(sb, B_QFREE + w));
      }
      uint32_t pn[16];
      float t0, t1, a0 = 1.f, a1 = 1.f;
      exps(pn, t0, t1);
      const bool redo = __any_sync(0xffffffffu, !(t0 + t1 <= 65536.f));
      if (redo) {
        row_max(a0, a1);
        const float c0 = fminf(b0, -SC * a0), c1 = fminf(b1, -SC * a1);
        a0 = ex2(c0 - b0); a1 = ex2(c1 - b1);
        b0 = c0; b1 = c1;
        l0 *= a0; l1 *= a1;
        exps(pn, t0, t1);
      }
      l0 += t0; l1 += t1;
      wg_wait<0>();
      reg_fence(acc);
      reg_fence(pa);
      give(vs, fd + dir);
      fd += 2 * dir;
      if (redo) {
#pragma unroll
        for (int i = 0; i < 32; i++) { acc[4 * i] *= a0; acc[4 * i + 1] *= a0; acc[4 * i + 2] *= a1; acc[4 * i + 3] *= a1; }
      }
#pragma unroll
      for (int i = 0; i < 16; i++) pa[i] = (i & 1) ? pn[i] ^ (one - 1) : pn[i] * one;
    }
    if (!which && up) skip();
    const uint32_t vs = take();
    TR(40);
    prep_pv(sb + vs * SLOT);
    turn_begin();
    wg_fence();
    issue_pv(1);
    wg_commit();
    turn_end();
    TR(41);
    if (!which && up) r.next();
    ws = take();
    l0 += __shfl_xor_sync(0xffffffffu, l0, 1); l1 += __shfl_xor_sync(0xffffffffu, l1, 1);
    l0 += __shfl_xor_sync(0xffffffffu, l0, 2); l1 += __shfl_xor_sync(0xffffffffu, l1, 2);
    float i0, i1;
    asm volatile("rcp.approx.ftz.f32 %0, %1;" : "=f"(i0) : "f"(l0));
    asm volatile("rcp.approx.ftz.f32 %0, %1;" : "=f"(i1) : "f"(l1));
    uint32_t xs = 0;
    if (!which) xs = take();
    wg_wait<0>();
    TR(42);
    reg_fence(acc);
    reg_fence(pa);
    give(vs, fd);
    TS(7 + 3 * which);
#pragma unroll
    for (int i = 0; i < 32; i++) {
      pk[2 * i]     = pack_bf16(acc[4 * i] * i0, acc[4 * i + 1] * i0);
      pk[2 * i + 1] = pack_bf16(acc[4 * i + 2] * i1, acc[4 * i + 3] * i1);
    }
    TS(8 + 3 * which); TR(46);
    if (which) break;
    TS(31);
    uint32_t xaddr = sb + xs * SLOT + (w ^ 1) * 8192;
#pragma unroll 1
    for (int kc = 0;; kc++) {
      TR(11);
      const uint64_t da = desc_k(xaddr), db = desc_mn(sb + ws * SLOT);
      turn_begin();
      wg_fence();
#pragma unroll
      for (int kk = 0; kk < 4; kk++) wgmma_ss_n256_tb(acc, desc_add(da, kk * 32), desc_add(db, kk * 2048), (kc | kk) != 0);
      wg_commit();
      turn_end();
      TR(13);
      const int cb = kc - CTX_K;
      if (cb >= 1 && cb <= 4) { fence_async_smem(); warp_arrive(bar_addr(sb, B_CTXS + 4 * w + cb - 1), lane); }
      if (cb == 0) store_blocks<0, 1>(qreg, lb, pk);
      else if (cb == 1) store_blocks<16, 1>(qreg + 8192, lb, pk);
      else if (cb == 2) store_blocks<32, 1>(qreg + 16384, lb, pk);
      else if (cb == 3) store_blocks<48, 1>(qreg + 24576, lb, pk);
      TR(15);
      wg_wait<0>();
      release(bar_addr(sb, B_RG_EMPTY + ws), lane, rank, false);
      if (!(kc & 1)) release(bar_addr(sb, B_RG_EMPTY + xs), lane, rank, false);
      if (kc == 6) break;
      ws = take();
      if (!(kc & 1)) { xs = take(); xaddr = sb + xs * SLOT + (w ^ 1) * 8192; } else xaddr += 16384;
    }
    reg_fence(acc);
    TS(61); TR(16);
#pragma unroll
    for (int i = 0; i < 64; i++) pk[i] = pack_bf16(acc[2 * i], acc[2 * i + 1]);
    TS(9); TR(19);
    qt = 15 - qt;
  }

  {
    float oa[32], ob[32];
#pragma unroll
    for (int i = 0; i < 32; i++) { oa[i] = 0.f; ob[i] = 0.f; }
    auto stage_o = [&](float (&o)[32], int ch) {
      reg_fence(o);
      uint32_t q[16];
#pragma unroll
      for (int i = 0; i < 16; i++) q[i] = pack_bf16(o[2 * i], o[2 * i + 1]);
      if (ch >= 2) mbar_wait(bar_addr(sb, B_S2_EMPTY + w * 2 + (ch & 1)), ((ch >> 1) - 1) & 1);
      store_blocks<0, 1>(qreg + (ch & 1) * 8192, lb, q);
    };
    auto hand_over = [&](int ch) {
      fence_async_smem();
      warp_arrive(bar_addr(sb, B_S2_FULL + w * 2 + (ch & 1)), lane);
    };
    uint32_t pk2[64];
    uint32_t p2 = 0;
    auto chunk = [&](int ch, auto first, float (&o)[32], float (&oprev)[32]) {
      constexpr bool FIRST = decltype(first)::value;
      const uint32_t s1 = FIRST ? ws : take();
      TR(50);
      const uint64_t d1 = desc_mn(sb + s1 * SLOT);
      turn_begin();
      wg_fence();
#pragma unroll
      for (int kk = 0; kk < 16; kk++) {
        wgmma_rs_n64_tb(o, pk[4 * kk], pk[4 * kk + 1], pk[4 * kk + 2], pk[4 * kk + 3], desc_add(d1, kk * 2048), kk != 0);
        if (kk == ARRIVE_KK) turn_end();
      }
      wg_commit();
      TR(51);
      if constexpr (!FIRST) {
        wg_wait<1>();
        if (ch <= 4) release(bar_addr(sb, B_RG_EMPTY + p2), lane, rank, true);
        stage_o(oprev, ch - 1);
      } else {
        mbar_wait(bar_addr(sb, B_CTXF + w), 0);
#pragma unroll
        for (int kk = 0; kk < 16; kk++) {
          uint32_t f[4];
          ldsm4(f, qreg + (kk >> 2) * 8192 + (lb ^ ((kk & 3) << 5)));
          pk2[4 * kk] = f[0]; pk2[4 * kk + 1] = f[1]; pk2[4 * kk + 2] = f[2]; pk2[4 * kk + 3] = f[3];
        }
      }
      const uint32_t s2 = take();
      TR(53);
      const uint64_t d2 = desc_mn(sb + s2 * SLOT);
      turn_begin();
      wg_fence();
#pragma unroll
      for (int kk = 0; kk < 16; kk++) {
        wgmma_rs_n64_tb(o, pk2[4 * kk], pk2[4 * kk + 1], pk2[4 * kk + 2], pk2[4 * kk + 3], desc_add(d2, kk * 2048), 1);
        if (kk == ARRIVE_KK && (ch < 6 || w == 1)) turn_end();
      }
      wg_commit();
      TR(54);
      if (!FIRST) hand_over(ch - 1);
      wg_wait<1>();
      TR(55);
      if (ch <= 4) release(bar_addr(sb, B_RG_EMPTY + s1), lane, rank, true);
      p2 = s2;
    };
    chunk(0, Int<1>(), oa, ob);
#pragma unroll 1
    for (int ch = 1; ch < 7; ch += 2) { chunk(ch, Int<0>(), ob, oa); chunk(ch + 1, Int<0>(), oa, ob); }
    wg_wait<0>();
    TR(58);
    reg_fence(pk);
    reg_fence(pk2);
    stage_o(oa, 6);
    hand_over(6);
  }
  TS(12); TR(59);
  if ((threadIdx.x & 127) == 0) GT(54 + w);

  TS(16); TS(18); TS(17);
  TR(99); TR_END();
  TS(13); TSG(14);
}

#define CONV_STAGGER_NS 1200
namespace ssm {
#define CONV_GROUPS (D_SPARE / 8 / NCONV)
constexpr int GROUPS = CONV_GROUPS;
constexpr uint32_t ZROWS = 16;
constexpr uint32_t CHAN = (ZROWS + 256 + 1) * 16;
constexpr uint32_t XBUF = 8 * CHAN;
constexpr uint32_t OFF_X = 0;
constexpr uint32_t HCOPY = 4160;
constexpr uint32_t OFF_H = 2 * XBUF;
constexpr uint32_t HWARP = 3 * HCOPY;
constexpr uint32_t IO_K = 128, IO_V = IO_K + 4096, IO_Q = IO_V + 4096, IOBUF = IO_Q + 4096;
constexpr uint32_t OFF_IO = (OFF_H + 8 * HWARP + 127) / 128 * 128;
constexpr uint32_t END = OFF_IO + 4 * IOBUF;
static_assert(IOBUF % 128 == 0 && OFF_H % 16 == 0, "TMA destination alignment");
static_assert(END <= BARS, "smem");
enum : uint32_t { B_XREADY = 0, B_ZDONE = 2, B_KV = 4, B_Q = 8, B_HRAW = 12, B_QLAST = 20 };
constexpr int CW_BAR = 4;

__device__ __forceinline__ int group_d0(int cidx, int grp) { return (grp * NCONV + cidx) * 8; }
__device__ __forceinline__ uint32_t x_lane(int lane) { return (lane & 7) * CHAN + (ZROWS + (lane >> 3)) * 16; }
__device__ __forceinline__ uint32_t t_lane(int lane) { return (uint32_t)(8 * (lane >> 3) + 7 - (lane & 7)) * 16; }
struct Taps { uint32_t s[4]; };
__device__ __forceinline__ Taps load_taps(const Params& p, int d0, int c) {
  const uint2 s0 = __ldg(reinterpret_cast<const uint2*>(p.a_shift + (d0 + 2 * c) * 4)), s1 = __ldg(reinterpret_cast<const uint2*>(p.a_shift + (d0 + 2 * c + 1) * 4));
  return Taps{{__byte_perm(s0.x, s1.x, 0x5410), __byte_perm(s0.x, s1.x, 0x7632), __byte_perm(s0.y, s1.y, 0x5410), __byte_perm(s0.y, s1.y, 0x7632)}};
}
__device__ __forceinline__ uint32_t short_conv(const Taps& t, uint32_t k0, uint32_t k1, uint32_t k2, uint32_t k3, uint32_t v) {
  return bmul(bfma(k3, t.s[0], bfma(k2, t.s[1], bfma(k1, t.s[2], bmul(k0, t.s[3])))), v);
}
__device__ __forceinline__ void gate_chunk(uint32_t xa, uint32_t qa) {
#pragma unroll 4
  for (int i = 0; i < 8; i++) {
    uint32_t zz[4], qq[4];
    ldsm4t(zz, xa + i * 64);
    ldsm4(qq, qa + i * 512);
    stsm4(qa + i * 512, bmul(qq[0], zz[0]), bmul(qq[1], zz[1]), bmul(qq[2], zz[2]), bmul(qq[3], zz[3]));
  }
}

__device__ __forceinline__ void io_warp(const Params& p, uint32_t sb, int cidx, int wq) {
  const int lane = threadIdx.x & 31;
  const uint32_t io = sb + OFF_IO + wq * IOBUF, bkv = bar_addr(sb, B_KV + wq), bq = bar_addr(sb, B_Q + wq);
  auto load_kv = [&](int e) {
    __syncwarp();
    if (lane != 0) return;
    const int d0 = group_d0(cidx, e >> 1), row = (2 * wq + (e & 1)) * 256;
    if (e < 2 * GROUPS) {
      mbar_expect_tx(bkv, IO_Q);
      tma_ld2(io, &p.ak8, bkv, d0, row - 8);
      tma_ld2(io + IO_K, &p.ak, bkv, d0, row);
      tma_ld2(io + IO_V, &p.av, bkv, d0, row);
    } else {
      const uint32_t bar = bar_addr(sb, B_QLAST + 2 * wq + 1);
      mbar_expect_tx(bar, 4096);
      tma_ld2(io + IO_K, &p.aq, bar, group_d0(cidx, GROUPS - 1), row + 256);
    }
  };
  auto load_q = [&](int e) {
    __syncwarp();
    if (lane != 0) return;
    const uint32_t bar = e < 2 * GROUPS - 2 ? bq : bar_addr(sb, B_QLAST + 2 * wq);
    mbar_expect_tx(bar, 4096);
    tma_ld2(io + IO_Q, &p.aq, bar, group_d0(cidx, e >> 1), (2 * wq + (e & 1)) * 256);
  };
  TR_DECL;
  TR(0);
  load_kv(0);
  const uint32_t xl = sb + OFF_X + x_lane(lane) + wq * 1024, tl = io + t_lane(lane);
#pragma unroll 1
  for (int grp = -2; grp + 1 < GROUPS; grp++) {
    const bool more = grp + 2 < GROUPS;
    const Taps taps = load_taps(p, group_d0(cidx, more ? grp + 2 : 0), lane & 3);
    PCLK(c0);
    if (grp >= 0) mbar_wait_nap(bar_addr(sb, B_ZDONE + (grp & 1)), (grp >> 1) & 1);
    PACC(tp, c0);
    PCLK(c1);
    TR(80);
#pragma unroll 1
    for (int i = 0; i < 2; i++) {
      const uint32_t xa = xl + (grp & 1) * XBUF + i * 512;
      if (grp >= 0) {
        mbar_wait_nap(bq, i);
        TR(81);
        gate_chunk(xa, tl + IO_Q);
      }
      if (more) {
        TR(82);
        mbar_wait_nap(bkv, i);
        TR(83);
#pragma unroll 2
        for (int u = 0; u < 8; u++) {
          const uint32_t ka = tl + IO_K + u * 512;
          uint32_t k0[4], k1[4], k2[4], k3[4], vv[4];
          ldsm4(k0, ka - 48); ldsm4(k1, ka - 32); ldsm4(k2, ka - 16); ldsm4(k3, ka); ldsm4(vv, ka + 4096);
          stsm4t(xa + u * 64, short_conv(taps, k0[0], k1[0], k2[0], k3[0], vv[0]), short_conv(taps, k0[1], k1[1], k2[1], k3[1], vv[1]),
                 short_conv(taps, k0[2], k1[2], k2[2], k3[2], vv[2]), short_conv(taps, k0[3], k1[3], k2[3], k3[3], vv[3]));
        }
        load_kv(2 * (grp + 2) + i + 1);
        TR(84);
        if (i == 1) warp_arrive(bar_addr(sb, B_XREADY + (grp & 1)), lane);
      }
      if (grp >= 0) {
        fence_async_smem();
        __syncwarp();
        if (lane == 0) {
          tma_st2(&p.ao, io + IO_Q, group_d0(cidx, grp), (2 * wq + i) * 256);
          bulk_commit();
          bulk_wait_read();
        }
      }
      if (2 * grp + i + 1 >= 0) load_q(2 * grp + i + 1);
      TR(85);
    }
    PACC(te, c1);
  }
  if (lane == 0) bulk_wait_all();
  TR(99); TR_END();
}

__device__ __forceinline__ void conv_warp(const Params& p, uint32_t sb, int cidx, int ch) {
  const int lane = threadIdx.x & 31;
  const uint32_t hE0 = sb + OFF_H + ch * HWARP, hO = hE0 + HCOPY;
  const uint32_t hbar = bar_addr(sb, B_HRAW + ch);
  auto fetch_h = [&](int grp) {
    if (lane == 0) {
      mbar_expect_tx(hbar, 4096);
      asm volatile("cp.async.bulk.shared::cluster.global.mbarrier::complete_tx::bytes [%0], [%1], %2, [%3];"
                   :: "r"(hE0 + (grp & 1) * 2 * HCOPY + 32), "l"(p.a_ssmk + (size_t)(group_d0(cidx, grp) + ch) * SEQ), "r"(4096), "r"(hbar) : "memory");
    }
  };
  TR_DECL;
  TR(0);
  fetch_h(0);
#pragma unroll 1
  for (int grp = 0; grp < GROUPS; grp++) {
    const uint32_t xc = sb + OFF_X + (grp & 1) * XBUF + ch * CHAN;
    const uint32_t Dd = (uint32_t)__ldg(reinterpret_cast<const unsigned short*>(p.a_D + group_d0(cidx, grp) + ch)) * 0x10001u;
    PCLK(k0);
    mbar_wait(hbar, grp & 1);
    const uint32_t hE = hE0 + (grp & 1) * 2 * HCOPY;
    if (grp + 1 < GROUPS) fetch_h(grp + 1);
#pragma unroll
    for (int i = 0; i < 8; i++) {
      const uint32_t o = 32 + (i * 32 + lane) * 16;
      const uint4 w = lds16(hE + o);
      const uint32_t nx = lds4(hE + o + 16);
      sts16(hO + o, __byte_perm(w.x, w.y, 0x5432), __byte_perm(w.y, w.z, 0x5432), __byte_perm(w.z, w.w, 0x5432), __byte_perm(w.w, nx, 0x5432));
      if (o == 32) asm volatile("st.shared.u32 [%0], %1;" :: "r"(hO + 28), "r"(w.x << 16) : "memory");
    }
    __syncwarp();
    const uint32_t ha = cv_h_lane(lane, hE, hO), xa = xc + cv_x_lane(lane);
    TR(71);
    mbar_wait(bar_addr(sb, B_XREADY + (grp & 1)), (grp >> 1) & 1);
    TR(72);
    if (grp == 0 && ch >= 4) __nanosleep(CONV_STAGGER_NS);
    PACC(tw, k0);
    PCLK(k1);
    float acc[16][4];
#pragma unroll
    for (int i = 0; i < 16; i++) { acc[i][0] = 0.f; acc[i][1] = 0.f; acc[i][2] = 0.f; acc[i][3] = 0.f; }
#pragma unroll 1
    for (int r = 0; r < 8; r++) {
      uint32_t fx[16][4], fh[16][2];
#pragma unroll
      for (int i = 0; i < 16; i++) { fh[i][0] = lds4(ha + i * 256 + r * 32); fh[i][1] = lds4(ha + i * 256 + r * 32 + 16); }
#pragma unroll
      for (int i = 0; i < 16; i++) ldsm4(fx[i], xa + i * 256 - r * 32);
#pragma unroll
      for (int sx = 0; sx < 16; sx++)
#pragma unroll
        for (int jj = 0; jj < 16 - sx; jj++) mma16816(acc[jj + sx], fx[sx], fh[jj][0], fh[jj][1]);
    }
    PACC(tm, k1);
    PCLK(k2);
    TR(73);
#pragma unroll
    for (int i = 0; i < 8; i++) {
      uint32_t x[4];
      const uint32_t ad = xc + (ZROWS + lane) * 16 + i * 512;
      ldsm4(x, ad);
      stsm4(ad, badd(pack_bf16(acc[2 * i][0], acc[2 * i][1]), bmul(x[0], Dd)), badd(pack_bf16(acc[2 * i][2], acc[2 * i][3]), bmul(x[1], Dd)),
            badd(pack_bf16(acc[2 * i + 1][0], acc[2 * i + 1][1]), bmul(x[2], Dd)), badd(pack_bf16(acc[2 * i + 1][2], acc[2 * i + 1][3]), bmul(x[3], Dd)));
    }
    if (grp + 1 < GROUPS) warp_arrive(bar_addr(sb, B_ZDONE + (grp & 1)), lane);
    PACC(tr, k2);
    TR(74);
  }
  {
    mbar_wait(bar_addr(sb, B_QLAST + ch), 0);
    named_sync(CW_BAR, 256);
    TR(75);
    const uint32_t qb = sb + OFF_IO + (ch >> 1) * IOBUF + ((ch & 1) ? IO_K : IO_Q);
    gate_chunk(sb + OFF_X + ((GROUPS - 1) & 1) * XBUF + x_lane(lane) + ch * 512, qb + t_lane(lane));
    fence_async_smem();
    __syncwarp();
    if (lane == 0) { tma_st2(&p.ao, qb, group_d0(cidx, GROUPS - 1), ch * 256); bulk_commit(); bulk_wait_all(); }
    TR(99); TR_END();
  }
}

__device__ __forceinline__ void init(uint32_t sb) {
  if (threadIdx.x < 16 * ZROWS) sts16(sb + OFF_X + (threadIdx.x >> 4) * CHAN + (threadIdx.x & 15) * 16, 0, 0, 0, 0);
  if (threadIdx.x < 96) sts16(sb + OFF_H + (threadIdx.x >> 2) * HCOPY + (threadIdx.x & 1) * 16 + ((threadIdx.x & 2) ? 4128 : 0), 0, 0, 0, 0);
  if (threadIdx.x == 0) {
    for (int i = 0; i < 2; i++) { mbar_init(bar_addr(sb, B_XREADY + i), 4); mbar_init(bar_addr(sb, B_ZDONE + i), 8); }
    for (int i = 0; i < 4; i++) { mbar_init(bar_addr(sb, B_KV + i), 1); mbar_init(bar_addr(sb, B_Q + i), 1); }
    for (int i = 0; i < 8; i++) { mbar_init(bar_addr(sb, B_HRAW + i), 1); mbar_init(bar_addr(sb, B_QLAST + i), 1); }
    fence_async_smem();
  }
}
}

__device__ __forceinline__ void ssm_side_work(const Params& p, uint32_t sb, unsigned epoch) {
  const Role ro = get_role();
  const int h = ro.h, j = ro.j;
  const int lane = threadIdx.x & 31, g = lane >> 2, c = lane & 3;
  const int d0 = D_SPARE + 8 * h;
  uint8_t* xs = g_xs + (size_t)(h * 8 + g) * CV_BYTES + c * 4;
  auto xrow = [&](int beta) { return xs + (16 + beta) * 16; };
  {
    const uint4* hp = reinterpret_cast<const uint4*>(p.a_ssmk + (size_t)(d0 + j) * SEQ) + lane;
    uint8_t* he = g_xs + (size_t)(h * 8 + j) * CV_BYTES + CV_HE;
#pragma unroll 2
    for (int i = 0; i < 8; i++) {
      const uint4 wv = __ldg(hp + i * 32);
      const uint32_t nx = i * 32 + lane < 255 ? __ldg(reinterpret_cast<const uint32_t*>(hp + i * 32 + 1)) : 0u;
      const uint32_t o = 32 + (i * 32 + lane) * 16;
      *reinterpret_cast<uint4*>(he + o) = wv;
      *reinterpret_cast<uint4*>(he + CV_HCOPY + o) =
          make_uint4(__byte_perm(wv.x, wv.y, 0x5432), __byte_perm(wv.y, wv.z, 0x5432), __byte_perm(wv.z, wv.w, 0x5432), __byte_perm(wv.w, nx, 0x5432));
      if (o == 32) *reinterpret_cast<uint32_t*>(he + CV_HCOPY + 28) = wv.x << 16;
    }
    if (lane == 0) *reinterpret_cast<uint32_t*>(he + CV_D - CV_HE) = (uint32_t)__ldg(reinterpret_cast<const unsigned short*>(p.a_D + d0 + j)) * 0x10001u;
  }
  {
    const ssm::Taps taps = ssm::load_taps(p, d0, c);
    const uint32_t* kp = reinterpret_cast<const uint32_t*>(p.a_k + (size_t)(256 * j + 7 - g) * DA + d0) + c;
    const uint32_t* vp = reinterpret_cast<const uint32_t*>(p.a_v + (size_t)(256 * j + 7 - g) * DA + d0) + c;
    uint32_t kprev = j > 0 ? __ldg(kp - 8 * (DA / 2)) : 0u;
#pragma unroll 1
    for (int i0 = 0; i0 < 32; i0 += 8) {
      uint32_t kk[8], vv[8];
#pragma unroll
      for (int i = 0; i < 8; i++) { kk[i] = __ldg(kp + (i0 + i) * 8 * (DA / 2)); vv[i] = __ldg(vp + (i0 + i) * 8 * (DA / 2)); }
#pragma unroll
      for (int i = 0; i < 8; i++) {
        const uint32_t k2 = __shfl_sync(0xffffffffu, g < 1 ? kprev : kk[i], (lane + 4) & 31);
        const uint32_t k1 = __shfl_sync(0xffffffffu, g < 2 ? kprev : kk[i], (lane + 8) & 31);
        const uint32_t k0 = __shfl_sync(0xffffffffu, g < 3 ? kprev : kk[i], (lane + 12) & 31);
        *reinterpret_cast<uint32_t*>(xrow(32 * j + i0 + i)) = transpose8(ssm::short_conv(taps, k0, k1, k2, kk[i], vv[i]));
        kprev = kk[i];
      }
    }
    __syncwarp();
    if (lane == 0) {
      flag_signal(&g_flags.xs_ready[h].v);
      flag_wait(&g_flags.xs_ready[h].v, 8, epoch);
      fence_async_all();
      mbar_arrive(bar_addr(sb, B_XS));
    }
  }
  if (lane == 0) {
    for (int i = 0; i < 3; i++) {
      flag_wait(&g_flags.kv_ready[3 * h + i].v, 16, epoch);
      fence_async_all();
      mbar_arrive(bar_addr(sb, B_KV + i));
    }
    mbar_wait_nap(bar_addr(sb, B_CONV), 0);
    flag_signal(&g_flags.zs_ready[h].v);
    flag_wait(&g_flags.zs_ready[h].v, 8, epoch);
    asm volatile("red.relaxed.gpu.global.add.u64 [%0], 1;" :: "l"(&g_flags.done) : "memory");
  }
  __syncwarp();
  fence_async_all();
  const uint32_t qb = q_region(sb, 1) + 16384, zb = qb + 4096, bar = bar_addr(sb, B_GATE);
  constexpr uint32_t ZCH = 528;
  mbar_wait_slow(bar_addr(sb, B_GFREE), 0);
  if (lane == 0) { mbar_expect_tx(bar, 8192); tma_ld2(qb, &p.aq, bar, d0, 256 * j); }
  __syncwarp();
  if (lane < 8) bulk_ld(zb + lane * ZCH, g_xs + (size_t)(h * 8 + lane) * CV_BYTES + (16 + 32 * j) * 16, 512, bar);
  mbar_wait(bar, 0);
  ssm::gate_chunk(zb + (lane & 7) * ZCH + (lane >> 3) * 16, qb + ssm::t_lane(lane));
  fence_async_smem();
  __syncwarp();
  if (lane == 0) { tma_st2(&p.ao, qb, d0, 256 * j); bulk_commit(); bulk_wait_all(); }
}

__global__ void __cluster_dims__(2, 1, 1) __launch_bounds__(NTHREADS, 1)
concat_heads__ssm_conv_h3__compressed_kv_cla__prompt_kernel(const __grid_constant__ Params p) {
  extern __shared__ uint8_t smem_raw[];
  const uint32_t sb = (smem_u32(smem_raw) + 1023) & ~1023u;
  const int warp = __shfl_sync(0xffffffffu, threadIdx.x >> 5, 0);
  const int wg = warp >> 2;
  const int cta = blockIdx.x;
  const bool attn = cta < NMAIN;
  if (!attn) ssm::init(sb);
  if (attn && threadIdx.x == 0) {
    for (int i = 0; i < 4; i++) { mbar_init(bar_addr(sb, B_P1_FULL + i), 1); mbar_init(bar_addr(sb, B_P1_EMPTY + i), 16); }
    for (int i = 0; i < NSLOT; i++) {
      mbar_init(bar_addr(sb, B_RG_FULL + i), 1); mbar_init(bar_addr(sb, B_RG_EMPTY + i), 16); mbar_init(bar_addr(sb, B_PFREE + i), 1);
    }
    for (int i = 0; i < 2; i++) { mbar_init(bar_addr(sb, B_ST_FULL + i), 4); mbar_init(bar_addr(sb, B_ST_EMPTY + i), 1); }
    mbar_init(bar_addr(sb, B_XS), 1); mbar_init(bar_addr(sb, B_CONV), 8); mbar_init(bar_addr(sb, B_GATE), 1); mbar_init(bar_addr(sb, B_GFREE), 1);
    for (int i = 0; i < 3; i++) mbar_init(bar_addr(sb, B_KV + i), 1);
    for (int i = 0; i < 8; i++) mbar_init(bar_addr(sb, B_CTXS + i), 4);
    for (int i = 0; i < 4; i++) { mbar_arrive(bar_addr(sb, B_RG_FULL + i)); if (i < 3) mbar_arrive_n(bar_addr(sb, B_RG_EMPTY + i), 16); }
    for (int i = 0; i < 4; i++) { mbar_init(bar_addr(sb, B_S2_FULL + i), 4); mbar_init(bar_addr(sb, B_S2_EMPTY + i), 1); }
    for (int i = 0; i < 2; i++) { mbar_init(bar_addr(sb, B_QFREE + i), 4); mbar_init(bar_addr(sb, B_CTXF + i), 1); }
    asm volatile("fence.mbarrier_init.release.cluster;" ::: "memory");
  }
  if (attn && threadIdx.x == 32) {
    prefetch_map(&p.ckv); prefetch_map(&p.wuk); prefetch_map(&p.wuv); prefetch_map(&p.x); prefetch_map(&p.wq);
    prefetch_map(&p.kv); prefetch_map(&p.part); prefetch_map(&p.wo); prefetch_map(&p.ctx);
  }
  __syncwarp();
  if (!attn) __syncthreads();
  asm volatile("barrier.cluster.arrive.relaxed.aligned;" ::: "memory");
  if (attn && threadIdx.x == 0) {
    const Role ro = get_role();
    const int h = ro.h, j = ro.j;
    for (int k = 0; k < EARLY_LD; k++) {
      const uint32_t full = bar_addr(sb, B_P1_FULL + k), dst = sb + k * P1_STAGE;
      mbar_expect_tx(full, P1_STAGE);
      tma_ld2(dst, &p.ckv, full, k * 64, 2 * j * 128);
      load_tile4(dst + 16384, &p.wuk, full, k * 64, h * 4, j & 1, false);
    }
  }
  __syncwarp();
  asm volatile("barrier.cluster.wait.acquire.aligned;" ::: "memory");

  const int lane = threadIdx.x & 31;
  if (wg == 0) {
    if (!attn) {
      asm volatile("setmaxnreg.dec.sync.aligned.u32 72;");
      if (threadIdx.x == 0) GT(0);
      if (p.out != nullptr) ssm::io_warp(p, sb, cta - NMAIN, fresh_warp());
      if (threadIdx.x == 0) GT(14);
      return;
    }
    asm volatile("setmaxnreg.dec.sync.aligned.u32 40;");
    if (warp == 0) {
      if (lane == 0) producer_main(p, sb);
    } else if (warp < 3) {
      storer_main(p, sb);
    } else {
      const unsigned epoch = load_epoch();
      mbar_wait(bar_addr(sb, B_P1_FULL + 3), 0);
      __nanosleep(SIDE_DELAY_NS);
      ssm_side_work(p, sb, epoch);
    }
  } else {
    if (!attn) {
      asm volatile("setmaxnreg.inc.sync.aligned.u32 216;");
      if (threadIdx.x == 128) { GT(12); PT(10); }
      if (p.out != nullptr) ssm::conv_warp(p, sb, cta - NMAIN, fresh_warp() - 4);
      if (threadIdx.x == 128) { PT(9); GT(13); }
      return;
    }
    asm volatile("setmaxnreg.inc.sync.aligned.u32 232;");
    if (p.out != nullptr) {
      consumer_main(p, sb);
    }
  }
}

typedef CUresult (*EncodeTiledFn)(CUtensorMap*, CUtensorMapDataType, cuuint32_t, void*, const cuuint64_t*, const cuuint64_t*,
                                  const cuuint32_t*, const cuuint32_t*, CUtensorMapInterleave, CUtensorMapSwizzle,
                                  CUtensorMapL2promotion, CUtensorMapFloatOOBfill);

void make_map(EncodeTiledFn enc, CUtensorMap* m, const void* ptr, int rank, const uint64_t* dims, const uint64_t* strides, const uint32_t* box) {
  cuuint64_t d[3], s[2]; cuuint32_t b[3], e[3] = {1, 1, 1};
  for (int i = 0; i < rank; i++) { d[i] = dims[i]; b[i] = box[i]; if (i) s[i - 1] = strides[i - 1]; }
  enc(m, CU_TENSOR_MAP_DATA_TYPE_BFLOAT16, rank, const_cast<void*>(ptr), d, s, b, e, CU_TENSOR_MAP_INTERLEAVE_NONE,
      CU_TENSOR_MAP_SWIZZLE_128B, CU_TENSOR_MAP_L2_PROMOTION_L2_256B, CU_TENSOR_MAP_FLOAT_OOB_FILL_NONE);
}
void map2(EncodeTiledFn enc, CUtensorMap* m, const void* ptr, uint64_t cols, uint64_t rows, uint32_t bc, uint32_t br) {
  const uint64_t dims[2] = {cols, rows}, st[1] = {cols * 2}; const uint32_t box[2] = {bc, br};
  make_map(enc, m, ptr, 2, dims, st, box);
}
void map2_plain(EncodeTiledFn enc, CUtensorMap* m, const void* ptr, uint64_t cols, uint64_t rows, uint32_t bc, uint32_t br) {
  cuuint64_t d[2] = {cols, rows}, st[1] = {cols * 2}; cuuint32_t b[2] = {bc, br}, e[2] = {1, 1};
  enc(m, CU_TENSOR_MAP_DATA_TYPE_BFLOAT16, 2, const_cast<void*>(ptr), d, st, b, e, CU_TENSOR_MAP_INTERLEAVE_NONE,
      CU_TENSOR_MAP_SWIZZLE_NONE, CU_TENSOR_MAP_L2_PROMOTION_L2_128B, CU_TENSOR_MAP_FLOAT_OOB_FILL_NONE);
}
void map3(EncodeTiledFn enc, CUtensorMap* m, const void* ptr, uint64_t rows, uint32_t nblk) {
  const uint64_t dims[3] = {64, rows, 64}, st[2] = {8192, 128}; const uint32_t box[3] = {64, 64, nblk};
  make_map(enc, m, ptr, 3, dims, st, box);
}

}

extern "C" void kernel_launch(void* const* d_in, const int* in_sizes, int n_in, void* d_out, int out_size) {
  (void)in_sizes; (void)n_in; (void)out_size;
  static EncodeTiledFn enc = nullptr;
  static void *kv_ptr = nullptr, *acc_ptr = nullptr;
  if (!enc) {
    void* fn = nullptr; cudaDriverEntryPointQueryResult qr;
    cudaGetDriverEntryPoint("cuTensorMapEncodeTiled", &fn, cudaEnableDefault, &qr);
    enc = (EncodeTiledFn)fn;
    cudaGetSymbolAddress(&kv_ptr, g_kv);
    cudaGetSymbolAddress(&acc_ptr, g_ctx);
    cudaFuncSetAttribute(concat_heads__ssm_conv_h3__compressed_kv_cla__prompt_kernel, cudaFuncAttributeMaxDynamicSharedMemorySize, SMEM_BYTES);
  }
  Params p;
  p.a_q = (const bf16*)d_in[0]; p.a_k = (const bf16*)d_in[1]; p.a_v = (const bf16*)d_in[2];
  map2_plain(enc, &p.aq, d_in[0], DA, SEQ, 8, 256);
  map2_plain(enc, &p.ak, d_in[1], DA, SEQ, 8, 256);
  map2_plain(enc, &p.ak8, d_in[1], DA, SEQ, 8, 8);
  map2_plain(enc, &p.av, d_in[2], DA, SEQ, 8, 256);
  map2_plain(enc, &p.ao, d_out, OUTW, SEQ, 8, 256);
  p.a_shift = (const bf16*)d_in[3]; p.a_ssmk = (const bf16*)d_in[4]; p.a_D = (const bf16*)d_in[5];
  p.one = 1;
  p.out = (bf16*)d_out; p.b_x = (const bf16*)d_in[6]; p.b_wo = (const bf16*)d_in[11];
  map2(enc, &p.x, d_in[6], DM, SEQ, 64, 128);
  map2(enc, &p.ckv, d_in[7], DC, SEQ, 64, 128);
  map3(enc, &p.wq, d_in[8], DM, 2);
  map2_plain(enc, &p.wqp, d_in[8], NH * HD, DM, 256, 4);
  map3(enc, &p.wuk, d_in[9], DC, 2);
  map3(enc, &p.wuv, d_in[10], DC, 2);
  map2(enc, &p.wo, d_in[11], DM, NH * HD, 64, 128);
  {
    const uint64_t dims[3] = {64, 2 * NH * SEQ, 4}, st[2] = {HD * 2, 128}; const uint32_t box[3] = {64, 64, 2};
    make_map(enc, &p.kv, kv_ptr, 3, dims, st, box);
    const uint32_t box1[3] = {64, KV_TMA ? KV_TMA : 64, 1};
    make_map(enc, &p.kvs, kv_ptr, 3, dims, st, box1);
  }
  map2(enc, &p.part, d_out, OUTW, SEQ, 64, 64);
  {
    const uint64_t dims[3] = {64, NMAIN * 128, 4}, st[2] = {HD * 2, 128}; const uint32_t box[3] = {64, 64, 4};
    make_map(enc, &p.ctx, acc_ptr, 3, dims, st, box);
    const uint32_t box1[3] = {64, 64, 1};
    make_map(enc, &p.ctxs, acc_ptr, 3, dims, st, box1);
  }
  concat_heads__ssm_conv_h3__compressed_kv_cla__prompt_kernel<<<NCTA, NTHREADS, SMEM_BYTES>>>(p);
}
```

```cpp
#include <cuda_runtime.h>
#include <cuda_bf16.h>
#include <cuda.h>
#include <stdint.h>

namespace {

typedef __nv_bfloat16 bf16;

constexpr int SEQ  = 2048;
constexpr int DA   = 448;
constexpr int NH   = 16;
constexpr int HD   = 256;
constexpr int DM   = 448;
constexpr int DC   = 1024;
constexpr int OUTW = DA + DM;
constexpr int NMAIN = 128;
constexpr int NCONV = 4;
constexpr int NCTA  = NMAIN + NCONV;
constexpr int NTHREADS = 384;
constexpr int D_SPARE = 320;

__device__ __align__(1024) bf16 g_kv[2ull * SEQ * NH * HD];
__device__ __align__(1024) bf16 g_ctx[(size_t)NMAIN * 128 * HD];
constexpr uint32_t CV_HE = 272 * 16, CV_HCOPY = 4160, CV_D = CV_HE + 4144, CV_BYTES = CV_HE + 2 * CV_HCOPY;
__device__ __align__(128) uint8_t g_xs[NMAIN * CV_BYTES];
struct alignas(128) Flag { unsigned v; unsigned pad[31]; };
struct Flags {
  Flag kv_ready[3 * NH];
  Flag ctx_ready[NMAIN * 2];
  Flag out_ready[16 * 2];
  Flag xs_ready[NH];
  Flag zs_ready[NH];
  alignas(128) unsigned long long done;
};
__device__ Flags g_flags;
#define TS(i)
#define TSG(i)
#define GT(i)
#define PT(i)
#define WHICH_TS 0
#define PCLK(var)
#define PACC(acc, t0)
#define PDECL
#define PDUMP()

#define ST(i)
#define STG_(i)
#define TR_DECL
#define TR(tag)
#define TR_END()
#define TRG(tag)

struct alignas(64) Params {
  CUtensorMap ckv;
  CUtensorMap wuk;
  CUtensorMap wuv;
  CUtensorMap x;
  CUtensorMap wq;
  CUtensorMap wqp;
  CUtensorMap kv;
  CUtensorMap kvs;
  CUtensorMap part;
  CUtensorMap ctx;
  CUtensorMap ctxs;
  CUtensorMap wo;
  CUtensorMap ak, ak8, av, aq, ao;
  const bf16 *a_q, *a_k, *a_v, *a_shift, *a_ssmk, *a_D, *b_x, *b_wo;
  bf16* out;
};

constexpr uint32_t P1_STAGE = 49152;
constexpr uint32_t P1_STG   = 196608;
constexpr uint32_t SLOT     = 32768;
constexpr int      NSLOT    = 5;
constexpr uint32_t QREG     = 163840;
constexpr uint32_t CV_X = 4 * SLOT + 16384, CV_R = 3 * SLOT;
static_assert(CV_BYTES <= 16384 && CV_BYTES % 128 == 0, "SSM operands");
constexpr uint32_t BARS     = 229376;
constexpr uint32_t SMEM_BYTES = BARS + 512 + 1024;
enum : uint32_t {
  B_P1_FULL = 0, B_P1_EMPTY = 4, B_RG_FULL = 8, B_RG_EMPTY = 13, B_ST_FULL = 18, B_ST_EMPTY = 20,
  B_XS = 22, B_PFREE = 23, B_S2_FULL = 28, B_S2_EMPTY = 32, B_QFREE = 36, B_CTXF = 38, B_KV = 40, B_GATE = 43, B_CTXS = 44, B_GFREE = 52, B_CONV = 53, B_COUNT = 54
};

__device__ __forceinline__ uint32_t smem_u32(const void* p) { return (uint32_t)__cvta_generic_to_shared(p); }
__device__ __forceinline__ void mbar_init(uint32_t bar, uint32_t cnt) {
  asm volatile("mbarrier.init.shared::cta.b64 [%0], %1;" :: "r"(bar), "r"(cnt) : "memory");
}
__device__ __forceinline__ void mbar_expect_tx(uint32_t bar, uint32_t bytes) {
  asm volatile("mbarrier.arrive.expect_tx.shared::cta.b64 _, [%0], %1;" :: "r"(bar), "r"(bytes) : "memory");
}
__device__ __forceinline__ void mbar_arrive(uint32_t bar) {
  asm volatile("mbarrier.arrive.shared::cta.b64 _, [%0];" :: "r"(bar) : "memory");
}
__device__ __forceinline__ void mbar_arrive_n(uint32_t bar, uint32_t n) {
  asm volatile("mbarrier.arrive.shared::cta.b64 _, [%0], %1;" :: "r"(bar), "r"(n) : "memory");
}
__device__ __forceinline__ void mbar_arrive_remote(uint32_t bar, uint32_t cta) {
  asm volatile("{\n.reg .b32 ra;\nmapa.shared::cluster.u32 ra, %0, %1;\n"
               "mbarrier.arrive.shared::cluster.b64 _, [ra];\n}" :: "r"(bar), "r"(cta) : "memory");
}
__device__ __forceinline__ uint32_t map_cta(uint32_t a, uint32_t cta) { uint32_t r; asm("mapa.shared::cluster.u32 %0, %1, %2;" : "=r"(r) : "r"(a), "r"(cta)); return r; }
__device__ __forceinline__ void mbar_arrive_pair(uint32_t mapped, uint32_t n, int lane) {
  asm volatile("{\n.reg .pred p;\nsetp.lt.s32 p, %2, 2;\n@p mbarrier.arrive.shared::cluster.b64 _, [%0], %1;\n}" :: "r"(mapped), "r"(n), "r"(lane) : "memory");
}
__device__ __forceinline__ bool mbar_try(uint32_t bar, uint32_t parity) {
  uint32_t ok;
  asm volatile("{\n.reg .pred p;\nmbarrier.try_wait.parity.shared::cta.b64 p, [%1], %2;\nselp.u32 %0, 1, 0, p;\n}"
               : "=r"(ok) : "r"(bar), "r"(parity) : "memory");
  return ok;
}
#define FLAG_NS 100
#define NAP_NS 100
constexpr uint32_t SPIN_LIMIT = 1u << 24;
__device__ __forceinline__ void mbar_wait(uint32_t bar, uint32_t parity) {
  if (mbar_try(bar, parity)) return;
  uint32_t n = 0;
  while (!mbar_try(bar, parity)) { if (++n > SPIN_LIMIT) __trap(); }
}
__device__ __forceinline__ void mbar_wait_nap(uint32_t bar, uint32_t parity) {
  uint32_t n = 0;
  while (!mbar_try(bar, parity)) { if (++n > (SPIN_LIMIT >> 2)) __trap(); __nanosleep(NAP_NS); }
}
__device__ __forceinline__ void mbar_wait_slow(uint32_t bar, uint32_t parity) {
  uint32_t n = 0;
  while (!mbar_try(bar, parity)) { if (++n > (SPIN_LIMIT >> 4)) __trap(); __nanosleep(500); }
}
__device__ __forceinline__ unsigned load_epoch() {
  unsigned long long e; asm volatile("ld.relaxed.gpu.global.u64 %0, [%1];" : "=l"(e) : "l"(&g_flags.done) : "memory"); return (unsigned)(e / NMAIN);
}
__device__ __forceinline__ void flag_wait(const unsigned* f, unsigned count, unsigned epoch) {
  const unsigned target = (epoch + 1) * count;
  uint32_t n = 0;
  while (true) {
    unsigned v;
    asm volatile("ld.acquire.gpu.global.u32 %0, [%1];" : "=r"(v) : "l"(f) : "memory");
    if ((int)(v - target) >= 0) break;
    if (++n > SPIN_LIMIT) __trap();
    __nanosleep(FLAG_NS);
  }
}
__device__ __forceinline__ void flag_wait_fast(const unsigned* f, unsigned count, unsigned epoch) {
  const unsigned target = (epoch + 1) * count;
  uint32_t n = 0;
  while (true) {
    unsigned v;
    asm volatile("ld.acquire.gpu.global.u32 %0, [%1];" : "=r"(v) : "l"(f) : "memory");
    if ((int)(v - target) >= 0) break;
    if (++n > SPIN_LIMIT) __trap();
  }
}
__device__ __forceinline__ void fence_async_all() { asm volatile("fence.proxy.async;" ::: "memory"); }
__device__ __forceinline__ void flag_signal(unsigned* f) {
  asm volatile("fence.acq_rel.gpu;" ::: "memory");
  asm volatile("red.relaxed.gpu.global.add.u32 [%0], 1;" :: "l"(f) : "memory");
}
__device__ __forceinline__ void flag_signal_after_bulk(unsigned* f) {
  asm volatile("red.relaxed.gpu.global.add.u32 [%0], 1;" :: "l"(f) : "memory");
}
__device__ __forceinline__ void fence_async_smem() { asm volatile("fence.proxy.async.shared::cta;" ::: "memory"); }
constexpr uint64_t POL_NORMAL = 0x1000000000000000ull, POL_FIRST = 0x12F0000000000000ull;
__device__ __forceinline__ void tma_ld2(uint32_t dst, const CUtensorMap* m, uint32_t bar, int c0, int c1, uint64_t pol = POL_NORMAL) {
  asm volatile("cp.async.bulk.tensor.2d.shared::cluster.global.mbarrier::complete_tx::bytes.L2::cache_hint [%0], [%1, {%3, %4}], [%2], %5;"
               :: "r"(dst), "l"(m), "r"(bar), "r"(c0), "r"(c1), "l"(pol) : "memory");
}
__device__ __forceinline__ void tma_ld3(uint32_t dst, const CUtensorMap* m, uint32_t bar, int c0, int c1, int c2, uint64_t pol = POL_NORMAL) {
  asm volatile("cp.async.bulk.tensor.3d.shared::cluster.global.mbarrier::complete_tx::bytes.L2::cache_hint [%0], [%1, {%3, %4, %5}], [%2], %6;"
               :: "r"(dst), "l"(m), "r"(bar), "r"(c0), "r"(c1), "r"(c2), "l"(pol) : "memory");
}
__device__ __forceinline__ void tma_ld3_mc(uint32_t dst, const CUtensorMap* m, uint32_t bar, int c0, int c1, int c2, uint64_t pol = POL_NORMAL) {
  asm volatile("cp.async.bulk.tensor.3d.shared::cluster.global.mbarrier::complete_tx::bytes.multicast::cluster.L2::cache_hint [%0], [%1, {%3, %4, %5}], [%2], %6, %7;"
               :: "r"(dst), "l"(m), "r"(bar), "r"(c0), "r"(c1), "r"(c2), "h"((uint16_t)3), "l"(pol) : "memory");
}
__device__ __forceinline__ void bulk_ld(uint32_t dst, const void* src, uint32_t bytes, uint32_t bar) {
  asm volatile("cp.async.bulk.shared::cluster.global.mbarrier::complete_tx::bytes [%0], [%1], %2, [%3];"
               :: "r"(dst), "l"(src), "r"(bytes), "r"(bar) : "memory");
}
__device__ __forceinline__ void tma_st3(const CUtensorMap* m, uint32_t src, int c0, int c1, int c2, uint64_t pol = POL_NORMAL) {
  asm volatile("cp.async.bulk.tensor.3d.global.shared::cta.bulk_group.L2::cache_hint [%0, {%2, %3, %4}], [%1], %5;"
               :: "l"(m), "r"(src), "r"(c0), "r"(c1), "r"(c2), "l"(pol) : "memory");
}
__device__ __forceinline__ void tma_ld2_mc(uint32_t dst, const CUtensorMap* m, uint32_t bar, int c0, int c1) {
  asm volatile("cp.async.bulk.tensor.2d.shared::cluster.global.mbarrier::complete_tx::bytes.multicast::cluster [%0], [%1, {%3, %4}], [%2], %5;"
               :: "r"(dst), "l"(m), "r"(bar), "r"(c0), "r"(c1), "h"((uint16_t)3) : "memory");
}
__device__ __forceinline__ void tma_st2(const CUtensorMap* m, uint32_t src, int c0, int c1) {
  asm volatile("cp.async.bulk.tensor.2d.global.shared::cta.bulk_group [%0, {%2, %3}], [%1];"
               :: "l"(m), "r"(src), "r"(c0), "r"(c1) : "memory");
}
__device__ __forceinline__ void tma_red2(const CUtensorMap* m, uint32_t src, int c0, int c1) {
  asm volatile("cp.reduce.async.bulk.tensor.2d.global.shared::cta.add.tile.bulk_group [%0, {%2, %3}], [%1];"
               :: "l"(m), "r"(src), "r"(c0), "r"(c1) : "memory");
}
__device__ __forceinline__ void tma_pf3(const CUtensorMap* m, int c0, int c1, int c2) {
  asm volatile("cp.async.bulk.prefetch.tensor.3d.L2.global.tile [%0, {%1, %2, %3}];" :: "l"(m), "r"(c0), "r"(c1), "r"(c2) : "memory");
}
__device__ __forceinline__ void tma_pf2(const CUtensorMap* m, int c0, int c1) {
  asm volatile("cp.async.bulk.prefetch.tensor.2d.L2.global.tile [%0, {%1, %2}];" :: "l"(m), "r"(c0), "r"(c1) : "memory");
}
__device__ __forceinline__ void bulk_prefetch(const void* src, uint32_t bytes) {
  asm volatile("cp.async.bulk.prefetch.L2.global [%0], %1;" :: "l"(src), "r"(bytes) : "memory");
}
__device__ __forceinline__ void bulk_commit() { asm volatile("cp.async.bulk.commit_group;" ::: "memory"); }
__device__ __forceinline__ void bulk_wait_read() { asm volatile("cp.async.bulk.wait_group.read 0;" ::: "memory"); }
__device__ __forceinline__ void bulk_wait_all() { asm volatile("cp.async.bulk.wait_group 0;" ::: "memory"); }
__device__ __forceinline__ void prefetch_map(const CUtensorMap* m) { asm volatile("prefetch.tensormap [%0];" :: "l"(m) : "memory"); }
__device__ __forceinline__ void wg_fence() { asm volatile("wgmma.fence.sync.aligned;" ::: "memory"); }
__device__ __forceinline__ void wg_commit() { asm volatile("wgmma.commit_group.sync.aligned;" ::: "memory"); }
template <int N> __device__ __forceinline__ void wg_wait() { asm volatile("wgmma.wait_group.sync.aligned %0;" :: "n"(N) : "memory"); }
template <int N> __device__ __forceinline__ void reg_fence(float (&d)[N]) {
#pragma unroll
  for (int i = 0; i < N; i++) asm volatile("" : "+f"(d[i]) :: "memory");
}
template <int N> __device__ __forceinline__ void reg_fence(uint32_t (&d)[N]) {
#pragma unroll
  for (int i = 0; i < N; i++) asm volatile("" : "+r"(d[i]) :: "memory");
}
__device__ __forceinline__ uint32_t fresh_tid() { uint32_t t; asm volatile("mov.u32 %0, %%tid.x;" : "=r"(t)); return t; }
__device__ __forceinline__ uint32_t lane_base16() {
  const uint32_t t = fresh_tid(), lane = t & 31, wq = (t >> 5) & 3;
  return (16 * wq + (lane & 7) + 8 * ((lane >> 3) & 1)) * 128 + (((lane >> 4) ^ (lane & 7)) << 4);
}
__device__ __forceinline__ void named_sync(int id, int n) { asm volatile("bar.sync %0, %1;" :: "r"(id), "r"(n) : "memory"); }
__device__ __forceinline__ void named_arrive(int id, int n) { asm volatile("bar.arrive %0, %1;" :: "r"(id), "r"(n) : "memory"); }
__device__ __forceinline__ uint32_t pack_bf16(float lo, float hi) {
  uint32_t r; asm("cvt.rn.bf16x2.f32 %0, %1, %2;" : "=r"(r) : "f"(hi), "f"(lo)); return r;
}
__device__ __forceinline__ float ex2(float x) { float y; asm("ex2.approx.ftz.f32 %0, %1;" : "=f"(y) : "f"(x)); return y; }
__device__ __forceinline__ void stsm4(uint32_t addr, uint32_t a, uint32_t b, uint32_t c, uint32_t d) {
  asm volatile("stmatrix.sync.aligned.m8n8.x4.shared.b16 [%0], {%1, %2, %3, %4};" :: "r"(addr), "r"(a), "r"(b), "r"(c), "r"(d) : "memory");
}
__device__ __forceinline__ void stsm4t(uint32_t addr, uint32_t a, uint32_t b, uint32_t c, uint32_t d) {
  asm volatile("stmatrix.sync.aligned.m8n8.x4.trans.shared.b16 [%0], {%1, %2, %3, %4};" :: "r"(addr), "r"(a), "r"(b), "r"(c), "r"(d) : "memory");
}
__device__ __forceinline__ uint64_t mk_desc(uint32_t addr, uint32_t lbo, uint32_t sbo) {
  return (uint64_t)(((addr & 0x3FFFF) >> 4) | ((lbo >> 4) << 16)) | ((uint64_t)((sbo >> 4) | (1u << 30)) << 32);
}
__device__ __forceinline__ uint64_t desc_k(uint32_t addr)  { return mk_desc(addr, 16, 1024); }
__device__ __forceinline__ uint64_t desc_mn(uint32_t addr) { return mk_desc(addr, 8192, 1024); }
__device__ __forceinline__ uint64_t desc_add(uint64_t d, uint32_t bytes) { return d + (bytes >> 4); }

__device__ __forceinline__ void wgmma_ss_n256_tb(float (&d)[128], uint64_t da, uint64_t db, int sd) {
  asm volatile("{\n.reg .pred p;\nsetp.ne.b32 p, %130, 0;\n"
    "wgmma.mma_async.sync.aligned.m64n256k16.f32.bf16.bf16 "
    "{%0, %1, %2, %3, %4, %5, %6, %7, %8, %9, %10, %11, %12, %13, %14, %15, "
    "%16, %17, %18, %19, %20, %21, %22, %23, %24, %25, %26, %27, %28, %29, %30, %31, "
    "%32, %33, %34, %35, %36, %37, %38, %39, %40, %41, %42, %43, %44, %45, %46, %47, "
    "%48, %49, %50, %51, %52, %53, %54, %55, %56, %57, %58, %59, %60, %61, %62, %63, "
    "%64, %65, %66, %67, %68, %69, %70, %71, %72, %73, %74, %75, %76, %77, %78, %79, "
    "%80, %81, %82, %83, %84, %85, %86, %87, %88, %89, %90, %91, %92, %93, %94, %95, "
    "%96, %97, %98, %99, %100, %101, %102, %103, %104, %105, %106, %107, %108, %109, %110, %111, "
    "%112, %113, %114, %115, %116, %117, %118, %119, %120, %121, %122, %123, %124, %125, %126, %127}, "
    "%128, %129, p, 1, 1, 0, 1;\n}"
    : "+f"(d[0]), "+f"(d[1]), "+f"(d[2]), "+f"(d[3]), "+f"(d[4]), "+f"(d[5]), "+f"(d[6]), "+f"(d[7]),
      "+f"(d[8]), "+f"(d[9]), "+f"(d[10]), "+f"(d[11]), "+f"(d[12]), "+f"(d[13]), "+f"(d[14]), "+f"(d[15]),
      "+f"(d[16]), "+f"(d[17]), "+f"(d[18]), "+f"(d[19]), "+f"(d[20]), "+f"(d[21]), "+f"(d[22]), "+f"(d[23]),
      "+f"(d[24]), "+f"(d[25]), "+f"(d[26]), "+f"(d[27]), "+f"(d[28]), "+f"(d[29]), "+f"(d[30]), "+f"(d[31]),
      "+f"(d[32]), "+f"(d[33]), "+f"(d[34]), "+f"(d[35]), "+f"(d[36]), "+f"(d[37]), "+f"(d[38]), "+f"(d[39]),
      "+f"(d[40]), "+f"(d[41]), "+f"(d[42]), "+f"(d[43]), "+f"(d[44]), "+f"(d[45]), "+f"(d[46]), "+f"(d[47]),
      "+f"(d[48]), "+f"(d[49]), "+f"(d[50]), "+f"(d[51]), "+f"(d[52]), "+f"(d[53]), "+f"(d[54]), "+f"(d[55]),
      "+f"(d[56]), "+f"(d[57]), "+f"(d[58]), "+f"(d[59]), "+f"(d[60]), "+f"(d[61]), "+f"(d[62]), "+f"(d[63]),
      "+f"(d[64]), "+f"(d[65]), "+f"(d[66]), "+f"(d[67]), "+f"(d[68]), "+f"(d[69]), "+f"(d[70]), "+f"(d[71]),
      "+f"(d[72]), "+f"(d[73]), "+f"(d[74]), "+f"(d[75]), "+f"(d[76]), "+f"(d[77]), "+f"(d[78]), "+f"(d[79]),
      "+f"(d[80]), "+f"(d[81]), "+f"(d[82]), "+f"(d[83]), "+f"(d[84]), "+f"(d[85]), "+f"(d[86]), "+f"(d[87]),
      "+f"(d[88]), "+f"(d[89]), "+f"(d[90]), "+f"(d[91]), "+f"(d[92]), "+f"(d[93]), "+f"(d[94]), "+f"(d[95]),
      "+f"(d[96]), "+f"(d[97]), "+f"(d[98]), "+f"(d[99]), "+f"(d[100]), "+f"(d[101]), "+f"(d[102]), "+f"(d[103]),
      "+f"(d[104]), "+f"(d[105]), "+f"(d[106]), "+f"(d[107]), "+f"(d[108]), "+f"(d[109]), "+f"(d[110]), "+f"(d[111]),
      "+f"(d[112]), "+f"(d[113]), "+f"(d[114]), "+f"(d[115]), "+f"(d[116]), "+f"(d[117]), "+f"(d[118]), "+f"(d[119]),
      "+f"(d[120]), "+f"(d[121]), "+f"(d[122]), "+f"(d[123]), "+f"(d[124]), "+f"(d[125]), "+f"(d[126]), "+f"(d[127])
    : "l"(da), "l"(db), "r"(sd));
}
__device__ __forceinline__ void wgmma_ss_n64(float (&d)[32], uint64_t da, uint64_t db, int sd) {
  asm volatile("{\n.reg .pred p;\nsetp.ne.b32 p, %34, 0;\n"
    "wgmma.mma_async.sync.aligned.m64n64k16.f32.bf16.bf16 "
    "{%0, %1, %2, %3, %4, %5, %6, %7, %8, %9, %10, %11, %12, %13, %14, %15, "
    "%16, %17, %18, %19, %20, %21, %22, %23, %24, %25, %26, %27, %28, %29, %30, %31}, "
    "%32, %33, p, 1, 1, 0, 0;\n}"
    : "+f"(d[0]), "+f"(d[1]), "+f"(d[2]), "+f"(d[3]), "+f"(d[4]), "+f"(d[5]), "+f"(d[6]), "+f"(d[7]),
      "+f"(d[8]), "+f"(d[9]), "+f"(d[10]), "+f"(d[11]), "+f"(d[12]), "+f"(d[13]), "+f"(d[14]), "+f"(d[15]),
      "+f"(d[16]), "+f"(d[17]), "+f"(d[18]), "+f"(d[19]), "+f"(d[20]), "+f"(d[21]), "+f"(d[22]), "+f"(d[23]),
      "+f"(d[24]), "+f"(d[25]), "+f"(d[26]), "+f"(d[27]), "+f"(d[28]), "+f"(d[29]), "+f"(d[30]), "+f"(d[31])
    : "l"(da), "l"(db), "r"(sd));
}
__device__ __forceinline__ void wgmma_rs_n256_tb(float (&d)[128], uint32_t a0, uint32_t a1, uint32_t a2, uint32_t a3, uint64_t db, int sd) {
  asm volatile("{\n.reg .pred p;\nsetp.ne.b32 p, %133, 0;\n"
    "wgmma.mma_async.sync.aligned.m64n256k16.f32.bf16.bf16 "
    "{%0, %1, %2, %3, %4, %5, %6, %7, %8, %9, %10, %11, %12, %13, %14, %15, "
    "%16, %17, %18, %19, %20, %21, %22, %23, %24, %25, %26, %27, %28, %29, %30, %31, "
    "%32, %33, %34, %35, %36, %37, %38, %39, %40, %41, %42, %43, %44, %45, %46, %47, "
    "%48, %49, %50, %51, %52, %53, %54, %55, %56, %57, %58, %59, %60, %61, %62, %63, "
    "%64, %65, %66, %67, %68, %69, %70, %71, %72, %73, %74, %75, %76, %77, %78, %79, "
    "%80, %81, %82, %83, %84, %85, %86, %87, %88, %89, %90, %91, %92, %93, %94, %95, "
    "%96, %97, %98, %99, %100, %101, %102, %103, %104, %105, %106, %107, %108, %109, %110, %111, "
    "%112, %113, %114, %115, %116, %117, %118, %119, %120, %121, %122, %123, %124, %125, %126, %127}, "
    "{%128, %129, %130, %131}, %132, p, 1, 1, 1;\n}"
    : "+f"(d[0]), "+f"(d[1]), "+f"(d[2]), "+f"(d[3]), "+f"(d[4]), "+f"(d[5]), "+f"(d[6]), "+f"(d[7]),
      "+f"(d[8]), "+f"(d[9]), "+f"(d[10]), "+f"(d[11]), "+f"(d[12]), "+f"(d[13]), "+f"(d[14]), "+f"(d[15]),
      "+f"(d[16]), "+f"(d[17]), "+f"(d[18]), "+f"(d[19]), "+f"(d[20]), "+f"(d[21]), "+f"(d[22]), "+f"(d[23]),
      "+f"(d[24]), "+f"(d[25]), "+f"(d[26]), "+f"(d[27]), "+f"(d[28]), "+f"(d[29]), "+f"(d[30]), "+f"(d[31]),
      "+f"(d[32]), "+f"(d[33]), "+f"(d[34]), "+f"(d[35]), "+f"(d[36]), "+f"(d[37]), "+f"(d[38]), "+f"(d[39]),
      "+f"(d[40]), "+f"(d[41]), "+f"(d[42]), "+f"(d[43]), "+f"(d[44]), "+f"(d[45]), "+f"(d[46]), "+f"(d[47]),
      "+f"(d[48]), "+f"(d[49]), "+f"(d[50]), "+f"(d[51]), "+f"(d[52]), "+f"(d[53]), "+f"(d[54]), "+f"(d[55]),
      "+f"(d[56]), "+f"(d[57]), "+f"(d[58]), "+f"(d[59]), "+f"(d[60]), "+f"(d[61]), "+f"(d[62]), "+f"(d[63]),
      "+f"(d[64]), "+f"(d[65]), "+f"(d[66]), "+f"(d[67]), "+f"(d[68]), "+f"(d[69]), "+f"(d[70]), "+f"(d[71]),
      "+f"(d[72]), "+f"(d[73]), "+f"(d[74]), "+f"(d[75]), "+f"(d[76]), "+f"(d[77]), "+f"(d[78]), "+f"(d[79]),
      "+f"(d[80]), "+f"(d[81]), "+f"(d[82]), "+f"(d[83]), "+f"(d[84]), "+f"(d[85]), "+f"(d[86]), "+f"(d[87]),
      "+f"(d[88]), "+f"(d[89]), "+f"(d[90]), "+f"(d[91]), "+f"(d[92]), "+f"(d[93]), "+f"(d[94]), "+f"(d[95]),
      "+f"(d[96]), "+f"(d[97]), "+f"(d[98]), "+f"(d[99]), "+f"(d[100]), "+f"(d[101]), "+f"(d[102]), "+f"(d[103]),
      "+f"(d[104]), "+f"(d[105]), "+f"(d[106]), "+f"(d[107]), "+f"(d[108]), "+f"(d[109]), "+f"(d[110]), "+f"(d[111]),
      "+f"(d[112]), "+f"(d[113]), "+f"(d[114]), "+f"(d[115]), "+f"(d[116]), "+f"(d[117]), "+f"(d[118]), "+f"(d[119]),
      "+f"(d[120]), "+f"(d[121]), "+f"(d[122]), "+f"(d[123]), "+f"(d[124]), "+f"(d[125]), "+f"(d[126]), "+f"(d[127])
    : "r"(a0), "r"(a1), "r"(a2), "r"(a3), "l"(db), "r"(sd));
}
__device__ __forceinline__ void wgmma_rs_n64_tb(float (&d)[32], uint32_t a0, uint32_t a1, uint32_t a2, uint32_t a3, uint64_t db, int sd) {
  asm volatile("{\n.reg .pred p;\nsetp.ne.b32 p, %37, 0;\n"
    "wgmma.mma_async.sync.aligned.m64n64k16.f32.bf16.bf16 "
    "{%0, %1, %2, %3, %4, %5, %6, %7, %8, %9, %10, %11, %12, %13, %14, %15, "
    "%16, %17, %18, %19, %20, %21, %22, %23, %24, %25, %26, %27, %28, %29, %30, %31}, "
    "{%32, %33, %34, %35}, %36, p, 1, 1, 1;\n}"
    : "+f"(d[0]), "+f"(d[1]), "+f"(d[2]), "+f"(d[3]), "+f"(d[4]), "+f"(d[5]), "+f"(d[6]), "+f"(d[7]),
      "+f"(d[8]), "+f"(d[9]), "+f"(d[10]), "+f"(d[11]), "+f"(d[12]), "+f"(d[13]), "+f"(d[14]), "+f"(d[15]),
      "+f"(d[16]), "+f"(d[17]), "+f"(d[18]), "+f"(d[19]), "+f"(d[20]), "+f"(d[21]), "+f"(d[22]), "+f"(d[23]),
      "+f"(d[24]), "+f"(d[25]), "+f"(d[26]), "+f"(d[27]), "+f"(d[28]), "+f"(d[29]), "+f"(d[30]), "+f"(d[31])
    : "r"(a0), "r"(a1), "r"(a2), "r"(a3), "l"(db), "r"(sd));
}
__device__ __forceinline__ void wgmma_rs_n64(float (&d)[32], uint32_t a0, uint32_t a1, uint32_t a2, uint32_t a3, uint64_t db, int sd) {
  asm volatile("{\n.reg .pred p;\nsetp.ne.b32 p, %37, 0;\n"
    "wgmma.mma_async.sync.aligned.m64n64k16.f32.bf16.bf16 "
    "{%0, %1, %2, %3, %4, %5, %6, %7, %8, %9, %10, %11, %12, %13, %14, %15, "
    "%16, %17, %18, %19, %20, %21, %22, %23, %24, %25, %26, %27, %28, %29, %30, %31}, "
    "{%32, %33, %34, %35}, %36, p, 1, 1, 0;\n}"
    : "+f"(d[0]), "+f"(d[1]), "+f"(d[2]), "+f"(d[3]), "+f"(d[4]), "+f"(d[5]), "+f"(d[6]), "+f"(d[7]),
      "+f"(d[8]), "+f"(d[9]), "+f"(d[10]), "+f"(d[11]), "+f"(d[12]), "+f"(d[13]), "+f"(d[14]), "+f"(d[15]),
      "+f"(d[16]), "+f"(d[17]), "+f"(d[18]), "+f"(d[19]), "+f"(d[20]), "+f"(d[21]), "+f"(d[22]), "+f"(d[23]),
      "+f"(d[24]), "+f"(d[25]), "+f"(d[26]), "+f"(d[27]), "+f"(d[28]), "+f"(d[29]), "+f"(d[30]), "+f"(d[31])
    : "r"(a0), "r"(a1), "r"(a2), "r"(a3), "l"(db), "r"(sd));
}

__device__ __forceinline__ uint4 lds16(uint32_t a) {
  uint4 v; asm volatile("ld.shared.v4.u32 {%0, %1, %2, %3}, [%4];" : "=r"(v.x), "=r"(v.y), "=r"(v.z), "=r"(v.w) : "r"(a) : "memory"); return v;
}
__device__ __forceinline__ void sts16(uint32_t a, uint32_t x, uint32_t y, uint32_t z, uint32_t w) {
  asm volatile("st.shared.v4.u32 [%0], {%1, %2, %3, %4};" :: "r"(a), "r"(x), "r"(y), "r"(z), "r"(w) : "memory");
}
__device__ __forceinline__ uint32_t lds4(uint32_t a) { uint32_t v; asm volatile("ld.shared.u32 %0, [%1];" : "=r"(v) : "r"(a) : "memory"); return v; }
__device__ __forceinline__ uint32_t lds4v(uint32_t a) { uint32_t v; asm volatile("ld.volatile.shared.u32 %0, [%1];" : "=r"(v) : "r"(a) : "memory"); return v; }
__device__ __forceinline__ uint32_t bmul(uint32_t a, uint32_t b) { uint32_t r; asm("mul.rn.bf16x2 %0, %1, %2;" : "=r"(r) : "r"(a), "r"(b)); return r; }
__device__ __forceinline__ uint32_t bfma(uint32_t a, uint32_t b, uint32_t c) { uint32_t r; asm("fma.rn.bf16x2 %0, %1, %2, %3;" : "=r"(r) : "r"(a), "r"(b), "r"(c)); return r; }
__device__ __forceinline__ uint32_t badd(uint32_t a, uint32_t b) { uint32_t r; asm("add.rn.bf16x2 %0, %1, %2;" : "=r"(r) : "r"(a), "r"(b)); return r; }

__device__ __forceinline__ void ldsm4(uint32_t (&r)[4], uint32_t a) {
  asm volatile("ldmatrix.sync.aligned.m8n8.x4.shared.b16 {%0, %1, %2, %3}, [%4];" : "=r"(r[0]), "=r"(r[1]), "=r"(r[2]), "=r"(r[3]) : "r"(a) : "memory");
}
__device__ __forceinline__ void ldsm4t(uint32_t (&r)[4], uint32_t a) {
  asm volatile("ldmatrix.sync.aligned.m8n8.x4.trans.shared.b16 {%0, %1, %2, %3}, [%4];" : "=r"(r[0]), "=r"(r[1]), "=r"(r[2]), "=r"(r[3]) : "r"(a) : "memory");
}
__device__ __forceinline__ uint32_t transpose8(uint32_t a) { uint32_t d; asm volatile("movmatrix.sync.aligned.m8n8.trans.b16 %0, %1;" : "=r"(d) : "r"(a)); return d; }

__device__ __forceinline__ void mma16816(float (&d)[4], const uint32_t (&a)[4], uint32_t b0, uint32_t b1) {
  asm volatile("mma.sync.aligned.m16n8k16.row.col.f32.bf16.bf16.f32 {%0, %1, %2, %3}, {%4, %5, %6, %7}, {%8, %9}, {%0, %1, %2, %3};"
               : "+f"(d[0]), "+f"(d[1]), "+f"(d[2]), "+f"(d[3]) : "r"(a[0]), "r"(a[1]), "r"(a[2]), "r"(a[3]), "r"(b0), "r"(b1));
}

#define P1_SPLIT 0
#define O_ROT 1
#define STG_K1 2
#define STG_K2 10
#define STG_Q1 (KV_TMA ? 1 : 2)
#define STG_Q2 (KV_TMA ? 5 : 6)
#define CTX_K 0
#define PF_QA 48
#define PF_WV 99
#define PF_X 8
#define PF_WO 11
#define PF_CV 64
#define PACE_A 850
#define PACE_B 400
#define Q_PRE 2
#define KV_TMA 16
#define TPACE_A 3200
#define TPACE_B 800
#define EF_A 0
#define EF_W 0
#define EF_KV 0
#define EF_JS 8
#define EF_JL 8
#define EF_CTX 0
#define RELAXED_ARRIVE 1
#define QY_A 4
#define QY_B 0
#define EXP_NOMC 0
#define COUPLE 0
#define ASCEND 1
#define SYNC_LATE 1
#define PF_MAP 1
#define ARRIVE_KK 12
#define SIDE_DELAY_NS 4000
#define KVH(h) (h)
#define HEAD_MAP 1
#define EARLY_LD 2
constexpr int RED_BAR = 6;
constexpr int CV_BAR = 5;
constexpr int PP_BAR = 3;
template <int V> struct Int { static constexpr int value = V; };
struct Ring {
  uint32_t slot, phase;
  __device__ __forceinline__ void next() { if (++slot == NSLOT) { slot = 0; phase ^= 1; } }
};
__device__ __forceinline__ uint32_t bar_addr(uint32_t sb, uint32_t i) { return sb + BARS + 8 * i; }
__device__ __forceinline__ uint32_t q_region(uint32_t sb, int w) { return sb + QREG + (w ^ 1) * 32768; }

struct Role { int h, j; };
__device__ __forceinline__ Role get_role() {
  int cta; asm volatile("mov.u32 %0, %%ctaid.x;" : "=r"(cta));
  const int c = cta >> 1;
  int h, u;
  const int a = c - 4, b = c - 36, q = (b * 37) >> 8;
  h = a < 0 ? 15 : b < 0 ? a & 7 : 8 + b - 7 * q;
  u = a < 0 ? c : b < 0 ? a >> 3 : q;
  return Role{h, 2 * u + (cta & 1)};
}
__device__ __forceinline__ int fresh_warp() { return __shfl_sync(0xffffffffu, fresh_tid() >> 5, 0); }

__device__ __forceinline__ int q_tile(int h, int j, int which) { return ((h < 8) == (which == 0)) ? 15 - j : j; }

__device__ __forceinline__ int o_chunk(int h, int c) { const int x = c + O_ROT * (h & 7); return x % 7; }

__device__ __forceinline__ int num_private(int qt) { return (qt & 1) ? 5 : 1; }
__device__ __forceinline__ void ring_acquire(uint32_t sb, Ring& r, uint32_t bytes) {
  mbar_wait(bar_addr(sb, B_RG_EMPTY + r.slot), r.phase ^ 1);
  mbar_expect_tx(bar_addr(sb, B_RG_FULL + r.slot), bytes);
}
__device__ __forceinline__ void load_tile4(uint32_t dst, const CUtensorMap* m, uint32_t full, int row, int blk0, int rank, bool shared, uint64_t pol = POL_NORMAL) {
  if (shared) {
    tma_ld3_mc(dst + rank * 16384, m, full, 0, row, blk0 + 2 * rank, pol);
  } else {
    tma_ld3(dst, m, full, 0, row, blk0, pol);
    tma_ld3(dst + 16384, m, full, 0, row, blk0 + 2, pol);
  }
}
__device__ __forceinline__ void producer_main(const Params& p, uint32_t sb) {
  const Role ro = get_role();
  const int h = ro.h, j = ro.j, rank = j & 1;
  TR_DECL;
  ST(11);
  for (int it = EARLY_LD; it < 71; it++) {
    const int t = it >> 4, k = it & 15, s = it & 3;
    mbar_wait(bar_addr(sb, B_P1_EMPTY + s), ((it >> 2) & 1) ^ 1);
    const uint32_t full = bar_addr(sb, B_P1_FULL + s), dst = sb + s * P1_STAGE;
    mbar_expect_tx(full, P1_STAGE);
    if ((it & 7) == 4) TRG(it);
    if (t < 4) {
      tma_ld2(dst, &p.ckv, full, k * 64, (2 * j + (t & 1)) * 128, ((EF_A >> t) & 1) ? POL_FIRST : POL_NORMAL);
      tma_ld3(dst + 16384, (t >> 1) ? &p.wuv : &p.wuk, full, 0, k * 64, h * 4, ((EF_W >> t) & 1) ? POL_FIRST : POL_NORMAL);
    } else {
      tma_ld2(dst, &p.x, full, k * 64, q_tile(h, j, 0) * 128);
      tma_ld3(dst + 16384, &p.wq, full, 0, k * 64, h * 4);
    }
    if (it >= PF_QA && it < PF_QA + 14) {
      const int i = it - PF_QA;
      bulk_prefetch(p.b_x + (size_t)(q_tile(h, j, 0) * 128 + (h & 7) * 16) * DM + i * 512, 1024);
      tma_pf2(&p.wqp, h * HD, (i * 8 + j) * 4);
    }
    if (it >= PF_CV && it < PF_CV + 3) {
      mbar_wait(bar_addr(sb, B_XS), 0);
      bulk_prefetch(g_xs + (size_t)(h * 8 + j) * CV_BYTES + (it - PF_CV) * (CV_BYTES / 3), CV_BYTES / 3);
    }
  }
  mbar_wait(bar_addr(sb, B_P1_EMPTY + 3), 0);
  mbar_wait(bar_addr(sb, B_XS), 0);
  mbar_expect_tx(bar_addr(sb, B_RG_FULL + 4), CV_BYTES);
  bulk_ld(sb + CV_X, g_xs + (size_t)(h * 8 + j) * CV_BYTES, CV_BYTES, bar_addr(sb, B_RG_FULL + 4));
  Ring r{0, 1};
  int hs = 5;
  auto acquire = [&](bool shared) {
    mbar_wait(bar_addr(sb, B_RG_EMPTY + r.slot), r.phase ^ 1);
    if (shared && hs < 5) {
      mbar_arrive_remote(bar_addr(sb, B_PFREE + r.slot), rank ^ 1);
      mbar_wait(bar_addr(sb, B_PFREE + r.slot), 0);
      hs++;
    }
    mbar_expect_tx(bar_addr(sb, B_RG_FULL + r.slot), 32768);
  };
  auto prefetch_wo = [&](int left) {
    const int i = PF_WO - left;
    if (PF_WO && i >= 0 && i < 8) bulk_prefetch(p.b_wo + (size_t)(h * HD + j * 32 + 4 * i) * DM, 4 * DM * 2);
  };
  mbar_wait(bar_addr(sb, B_KV), 0);
  for (int which = 0; which < 2; which++) {
    const int qt = q_tile(h, j, which);
    if (which == 1) {
      for (int kc = 0; kc < 7; kc++) {
        prefetch_wo(4 * qt + 4 + 7 - kc);
        ring_acquire(sb, r, 32768);
        tma_ld3(sb + r.slot * SLOT, &p.wq, bar_addr(sb, B_RG_FULL + r.slot), 0, kc * 64, h * 4);
        r.next();
        if (kc == 0 || (kc & 1)) {
          ring_acquire(sb, r, kc == 0 ? 16384 : 32768);
          const uint32_t full = bar_addr(sb, B_RG_FULL + r.slot), dst = sb + r.slot * SLOT;
          tma_ld2(dst, &p.x, full, kc * 64, qt * 128);
          if (kc > 0) tma_ld2(dst + 16384, &p.x, full, kc * 64 + 64, qt * 128);
          r.next();
        }
      }
      hs = 0;
    }
    const int n = 2 * qt + 2, npriv = num_private(qt), nb = qt & ~1;
    for (int f = 0; f < 2 * n; f++) {
      if (which == 0) {
        const int i = f - max(2 * n - PF_X, 0);
        if (PF_X && i >= 0 && i < 4) bulk_prefetch(p.b_x + (size_t)((15 - qt) * 128 + (h & 7) * 16 + 4 * i) * DM, 4 * DM * 2);
      } else prefetch_wo(2 * n - f);
      const bool isK = (f == 0) || ((f & 1) && f < 2 * n - 1);
      const int i = isK ? (f + 1) >> 1 : (f == 2 * n - 1 ? n - 1 : (f >> 1) - 1);
      int tile = n - 1 - i;
      if (which == 0) { const int b = i >> 1; tile = (ASCEND || b >= nb) ? i : 2 * (2 * b < nb ? 2 * b : 2 * b - nb + 1) + (i & 1); }
      if (!isK) mbar_wait(bar_addr(sb, B_KV + 1 + ((tile >> 1) & 1)), 0);
      if (which == 0 && f < 2) mbar_wait(bar_addr(sb, B_P1_EMPTY + f), 1);
      const bool shared = COUPLE && which && f >= npriv;
      acquire(shared);
      if (isK && (tile & 3) == 0) TRG(100 + 50 * which + tile);
      load_tile4(sb + r.slot * SLOT, &p.kv, bar_addr(sb, B_RG_FULL + r.slot), ((isK ? 0 : NH) + KVH(h)) * SEQ + tile * 64, 0, rank, shared && !(EXP_NOMC & (32 << which)),
                 (which ? (EF_KV & 2) : ((EF_KV & 1) && tile >= 16) || (EF_KV & 4)) ? POL_FIRST : POL_NORMAL);
      r.next();
    }
  }
  for (int i = 0; i < 14; i++) {
    acquire(COUPLE);
    if ((i & 3) == 0) TRG(200 + i);
    if (i == 13) TR_END();
    if ((EXP_NOMC & 128) || !COUPLE) {
      for (int q = 0; q < 2; q++) tma_ld2(sb + r.slot * SLOT + q * 16384, &p.wo, bar_addr(sb, B_RG_FULL + r.slot), o_chunk(h, i >> 1) * 64, ((i & 1) ? h ^ 8 : h) * HD + q * 128);
    } else
    tma_ld2_mc(sb + r.slot * SLOT + rank * 16384, &p.wo, bar_addr(sb, B_RG_FULL + r.slot), o_chunk(h, i >> 1) * 64, ((i & 1) ? h ^ 8 : h) * HD + rank * 128);
    r.next();
  }
}

__device__ __forceinline__ void storer_main(const Params& p, uint32_t sb) {
  const Role ro = get_role();
  const int h = ro.h, j = ro.j, w = fresh_warp() - 1;
  const uint32_t full = bar_addr(sb, B_ST_FULL + w), empty = bar_addr(sb, B_ST_EMPTY + w);
  const int lane = threadIdx.x & 31;
  const unsigned epoch = load_epoch();
  if (lane == 0) {
    for (int job = 0; job < 8; job++) {
      const int t = job >> 1, row = ((t >> 1) * NH + KVH(h)) * SEQ + (2 * j + (t & 1)) * 128 + w * 64;
      mbar_wait_nap(full, job & 1);
      for (int i = 0; i < 128 / KV_TMA; i++) {
        if (i) __nanosleep((job < 6 ? TPACE_A : TPACE_B) * KV_TMA / 128);
        tma_st3(&p.kvs, sb + P1_STG + w * 16384 + i * KV_TMA * 128, 0, row + (i * KV_TMA & 63), (job & 1) * 2 + (i * KV_TMA >> 6),
                j >= (h >= 8 ? EF_JS : EF_JL) ? POL_FIRST : POL_NORMAL);
      }
      bulk_commit();
      bulk_wait_read();
      mbar_arrive(empty);
      if (job >= 3 && (job & 1)) { bulk_wait_all(); flag_signal(&g_flags.kv_ready[3 * h + t - 1].v); }
    }
  }
  __syncwarp();
  const int cta = h * 8 + j, qt = q_tile(h, j, 1);
  const uint32_t qreg = q_region(sb, w);
  {
    mbar_wait_nap(bar_addr(sb, B_CTXS + 4 * w), 0);
    uint4* z = reinterpret_cast<uint4*>(p.out + (size_t)(qt * 128 + w * 64 + (h & 7) * 8 + (lane >> 2)) * OUTW + DA) + (lane & 3);
#pragma unroll
    for (int i = 0; i < 14; i++) z[4 * i] = make_uint4(0, 0, 0, 0);
    __syncwarp();
    if (lane != 0) return;
    for (int b = 0; b < 4; b++) {
      mbar_wait(bar_addr(sb, B_CTXS + 4 * w + b), 0);
      tma_st3(&p.ctxs, qreg + b * 8192, 0, cta * 128 + w * 64, b, ((EF_CTX >> (h >> 3)) & 1) ? POL_FIRST : POL_NORMAL);
      bulk_commit();
    }
    bulk_wait_read();
    mbar_arrive(empty);
    bulk_wait_all();
    flag_signal(&g_flags.ctx_ready[cta * 2 + w].v);
    flag_signal_after_bulk(&g_flags.out_ready[qt * 2 + w].v);
  }
  {
    const int wx = w ^ 1;
    flag_wait(&g_flags.ctx_ready[(cta ^ 64) * 2 + wx].v, 1, epoch);
    flag_wait(&g_flags.out_ready[qt * 2 + wx].v, 8, epoch);
    fence_async_all();
    mbar_wait_nap(bar_addr(sb, B_QFREE + w), 0);
    mbar_expect_tx(bar_addr(sb, B_CTXF + w), 32768);
    tma_ld3(qreg, &p.ctx, bar_addr(sb, B_CTXF + w), 0, (cta ^ 64) * 128 + wx * 64, 0);
    for (int ch = 0; ch < 7; ch++) {
      const int b = ch & 1;
      mbar_wait(bar_addr(sb, B_S2_FULL + w * 2 + b), (ch >> 1) & 1);
      tma_red2(&p.part, qreg + b * 8192, DA + o_chunk(h, ch) * 64, qt * 128 + wx * 64);
      bulk_commit();
      if (ch == 0 && w == 1) mbar_arrive(bar_addr(sb, B_GFREE));
      bulk_wait_read();
      mbar_arrive(bar_addr(sb, B_S2_EMPTY + w * 2 + b));
    }
    GT(48 + w);
    bulk_wait_all();
    GT(50 + w); GT(52 + w); GT(56);
    if (w == 0) { ST(12); STG_(13); }
  }
}

template <int OFF, int NB, int NREG>
__device__ __forceinline__ void store_blocks(uint32_t base, uint32_t lanebase, const uint32_t (&pk)[NREG]) {
#pragma unroll
  for (int J = 0; J < NB * 8; J += 2) {
    const uint32_t a = base + (J >> 3) * 8192 + (lanebase ^ ((J & 7) << 4));
    stsm4(a, pk[OFF + 2 * J], pk[OFF + 2 * J + 1], pk[OFF + 2 * J + 2], pk[OFF + 2 * J + 3]);
  }
}
__device__ __forceinline__ void warp_arrive(uint32_t bar, int lane) { __syncwarp(); if (lane == 0) mbar_arrive(bar); }
__device__ __forceinline__ void release(uint32_t bar, int lane, int rank, bool shared) {
  if (shared) { if (lane < 2) mbar_arrive_remote(bar, rank ^ lane); }
  else if (lane == 0) mbar_arrive_n(bar, 2);
}

template <int W> __device__ __forceinline__ constexpr int cv_tile(int u) { return 2 * u + ((u ^ W) & 1); }
__device__ __forceinline__ uint32_t cv_x_lane(uint32_t lane) { return (16 + (lane & 15) - (lane >> 4)) * 16; }
__device__ __forceinline__ uint32_t cv_h_lane(uint32_t lane, uint32_t hE, uint32_t hO) {
  const uint32_t g = lane >> 2, c = lane & 3;
  return (g & 1) ? hO + (15 + 2 * c - g) * 2 : hE + (16 + 2 * c - g) * 2;
}
template <int W>
__device__ __forceinline__ void conv_mma(float (&ca)[8][4], uint32_t xa, uint32_t ha, uint32_t sb, uint32_t lb, const uint32_t (&pk)[64]) {
  constexpr int N = 16 - W;
  uint32_t fx[N][4], fh[N][2];
  auto ld_h = [&](int i, int rr) { fh[i][0] = lds4(ha + i * 256 + rr * 32); fh[i][1] = lds4(ha + i * 256 + rr * 32 + 16); };
  ldsm4(fx[0], xa);
#pragma unroll
  for (int u = 0; u < 8; u++) ld_h(cv_tile<W>(u), 0);
  ldsm4(fx[1], xa + 256);
#pragma unroll
  for (int u = 0; u < 8; u++) if (cv_tile<W ^ 1>(u) < N) ld_h(cv_tile<W ^ 1>(u), 0);
#pragma unroll
  for (int i = 2; i < N; i++) ldsm4(fx[i], xa + i * 256);
#pragma unroll
  for (int sx = 0; sx < N; sx++) {
#pragma unroll
    for (int u = 0; u < 8; u++) {
      const int jj = cv_tile<W>(u) - sx;
      if (jj >= 0) mma16816(ca[u], fx[sx], fh[jj < 0 ? 0 : jj][0], fh[jj < 0 ? 0 : jj][1]);
    }
    ldsm4(fx[sx], xa + sx * 256 - 32);
    ld_h(N - 1 - sx, 1);
  }
  mbar_wait(bar_addr(sb, B_P1_EMPTY + 2), 1);
  if (W == 0) { mbar_wait(bar_addr(sb, B_ST_EMPTY), 1); mbar_wait(bar_addr(sb, B_ST_EMPTY + 1), 1); }
#pragma unroll
  for (int jj = 15; jj >= 0; jj--) {
    stsm4(q_region(sb, W) + (jj >> 2) * 8192 + (lb ^ ((jj & 3) << 5)), pk[4 * jj], pk[4 * jj + 1], pk[4 * jj + 2], pk[4 * jj + 3]);
#pragma unroll
    for (int u = 0; u < 8; u++) {
      const int sx = cv_tile<W>(u) - jj;
      if (sx >= 0) mma16816(ca[u], fx[sx < 0 ? 0 : sx], fh[jj < N ? jj : 0][0], fh[jj < N ? jj : 0][1]);
    }
  }
}

__device__ __forceinline__ void consumer_main(const Params& p, uint32_t sb, uint8_t* xs_base, uint32_t one) {
  const int lane = fresh_tid() & 31, w = (fresh_warp() >> 2) - 1;
  const uint32_t lb = lane_base16();
  int qt, rank, cc;
  { const Role ro = get_role(); qt = q_tile(ro.h, ro.j, 0); rank = ro.j & 1; cc = ro.h * 8 + ro.j; }
  const uint32_t st_full = bar_addr(sb, B_ST_FULL + w), st_empty = bar_addr(sb, B_ST_EMPTY + w);
  const uint32_t stg = sb + P1_STG + w * 16384;

  auto turn_begin = [&]() { named_sync(PP_BAR + w, 256); };
  auto turn_end = [&]() { named_arrive(PP_BAR + (w ^ 1), 256); };
  float acc[128];
#pragma unroll
  for (int i = 0; i < 128; i++) acc[i] = 0.f;
  uint32_t pk[64];
#pragma unroll
  for (int i = 0; i < 64; i++) pk[i] = 0;
  if (SYNC_LATE) { reg_fence(acc); reg_fence(pk); }
  if (fresh_warp() != 4) named_sync(0, NTHREADS);
  PDECL;
  TR_DECL;
  TR(0);
  TSG(0); TS(1);
  const uint32_t qreg = q_region(sb, w);
  for (int t = 0; t < 5; t++) {
    const int nk = t < 4 ? 16 : 7;
#pragma unroll 1
    for (int k = 0; k < nk; k++) {
      const int it = t * 16 + k, s = k & 3;
      if (it == 0 && threadIdx.x == 256) ST(6);
      mbar_wait(bar_addr(sb, B_P1_FULL + s), (it >> 2) & 1);
      if (it < 3 && threadIdx.x == 256) ST(7 + it);
      TR(1);
      const uint64_t da = desc_k(sb + s * P1_STAGE + w * 8192), db = desc_mn(sb + s * P1_STAGE + 16384);
      turn_begin();
      wg_fence();
#pragma unroll
      for (int kk = 0; kk < 4; kk++) wgmma_ss_n256_tb(acc, desc_add(da, kk * 32), desc_add(db, kk * 2048), (k | kk) != 0);
      wg_commit();
      turn_end();
      TR(3);
      wg_wait<1>();
      if (k > 0) release(bar_addr(sb, B_P1_EMPTY + ((k - 1) & 3)), lane, rank, false);
      const int k1 = t < 4 ? STG_K1 : STG_Q1, k2 = t < 4 ? STG_K2 : STG_Q2;
      if (t > 0 && (k == k1 || k == k2)) {
        const int job = 2 * (t - 1) + (k != k1);
        if (job > 0) mbar_wait(st_empty, (job - 1) & 1);
        if (k == k1) store_blocks<0, 2>(stg, lb, pk); else store_blocks<32, 2>(stg, lb, pk);
      }
      if (t > 0 && (k == k1 + 1 || k == k2 + 1)) { fence_async_smem(); warp_arrive(st_full, lane); }
      TR(5);
    }
    wg_wait<0>();
    TR(6);
    reg_fence(acc);
    release(bar_addr(sb, B_P1_EMPTY + ((nk - 1) & 3)), lane, rank, false);
#pragma unroll
    for (int i = 0; i < 64; i++) pk[i] = pack_bf16(acc[2 * i], acc[2 * i + 1]);
    TS(t < 4 ? 2 + t : 60);
  }
  TS(6);
  {
    const uint32_t wq = lb >> 11, ln = lane, cx = sb + CV_X;
    float ca[8][4];
#pragma unroll
    for (int i = 0; i < 8; i++) { ca[i][0] = 0.f; ca[i][1] = 0.f; ca[i][2] = 0.f; ca[i][3] = 0.f; }
    const uint32_t xa = cx + cv_x_lane(ln) - wq * 64, ha = cv_h_lane(ln, cx + CV_HE, cx + CV_HE + CV_HCOPY) + wq * 64;
    mbar_wait(bar_addr(sb, B_RG_FULL + 4), 0);
    TR(7); TS(19); TS(20);
    if (w) conv_mma<1>(ca, xa, ha, sb, lb, pk); else conv_mma<0>(ca, xa, ha, sb, lb, pk);
    TR(8); TS(21);
    const uint32_t ex = sb + CV_R + w * 16384 + ln * 16;
#pragma unroll
    for (int u = 0; u < 8; u++)
      sts16(ex + (wq * 8 + u) * 512, __float_as_uint(ca[u][0]), __float_as_uint(ca[u][1]), __float_as_uint(ca[u][2]), __float_as_uint(ca[u][3]));
  }
  auto conv_finish = [&]() {
    const uint32_t wq = lb >> 11, cx = sb + CV_X, ex = sb + CV_R + w * 16384 + lane * 16;
    uint8_t* gz = xs_base + (size_t)cc * CV_BYTES;
    const uint32_t Dd = lds4(cx + CV_D);
    uint32_t z[2][2];
#pragma unroll
    for (int e = 0; e < 2; e++) {
      const uint32_t u = 2 * wq + e, nt = 2 * u + ((e ^ w) & 1);
      float y[4] = {0.f, 0.f, 0.f, 0.f};
#pragma unroll
      for (int v = 0; v < 4; v++) {
        const uint4 t = lds16(ex + (v * 8 + u) * 512);
        y[0] += __uint_as_float(t.x); y[1] += __uint_as_float(t.y); y[2] += __uint_as_float(t.z); y[3] += __uint_as_float(t.w);
      }
      const uint32_t o = (16 + 16 * nt) * 16 + lane * 4;
      *reinterpret_cast<uint32_t*>(gz + o)       = badd(pack_bf16(y[0], y[1]), bmul(lds4(cx + o), Dd));
      *reinterpret_cast<uint32_t*>(gz + o + 128) = badd(pack_bf16(y[2], y[3]), bmul(lds4(cx + o + 128), Dd));
    }
    __syncwarp();
    release(bar_addr(sb, B_RG_EMPTY + 3), lane, rank, false);
    release(bar_addr(sb, B_RG_EMPTY + 4), lane, rank, false);
    if (lane == 0) mbar_arrive(bar_addr(sb, B_CONV));
  };
  TS(15);
  TR(10);
  Ring r{0, 1};
  auto take = [&]() { const uint32_t sl = r.slot; mbar_wait(bar_addr(sb, B_RG_FULL + sl), r.phase); r.next(); return sl; };
  constexpr float SC = 0.0625f * 1.4426950408889634f;
  uint32_t ws;
#pragma unroll 1
  for (int which = 0;; which++) {
    float s[32];
#pragma unroll
    for (int i = 0; i < 32; i++) s[i] = 0.f;
    uint32_t pa[16];
    float b0, b1, l0, l1;
    const uint64_t dq = desc_k(qreg);
    uint64_t dk = 0, dqq = 0, dv = 0;
    auto prep_qk = [&](uint32_t kaddr) { dk = desc_k(kaddr); dqq = dq + (kaddr >> 31); asm volatile("" : "+l"(dk), "+l"(dqq)); };
    auto prep_pv = [&](uint32_t vaddr) { dv = desc_mn(vaddr); asm volatile("" : "+l"(dv)); };
    auto issue_qk = [&]() {
#pragma unroll
      for (int kk = 0; kk < 16; kk++)
        wgmma_ss_n64(s, desc_add(dqq, (kk >> 2) * 8192 + (kk & 3) * 32), desc_add(dk, (kk >> 2) * 8192 + (kk & 3) * 32), kk != 0);
    };
    auto issue_pv = [&](int accumulate) {
#pragma unroll
      for (int kk = 0; kk < 4; kk++)
        wgmma_rs_n256_tb(acc, pa[4 * kk], pa[4 * kk + 1], pa[4 * kk + 2], pa[4 * kk + 3], desc_add(dv, kk * 2048), accumulate | kk);
    };
    auto mask_diag = [&]() {
      const int d = (int)((lb >> 11) << 4) + (lane >> 2) - 2 * (lane & 3);
#pragma unroll
      for (int jj = 0; jj < 8; jj++) {
        if (8 * jj > d)     s[4 * jj]     = -INFINITY;
        if (8 * jj + 1 > d) s[4 * jj + 1] = -INFINITY;
        if (8 * jj - 8 > d) s[4 * jj + 2] = -INFINITY;
        if (8 * jj - 7 > d) s[4 * jj + 3] = -INFINITY;
      }
    };
    auto row_max = [&](float& x0, float& x1) {
      x0 = fmaxf(s[0], s[1]); x1 = fmaxf(s[2], s[3]);
#pragma unroll
      for (int jj = 1; jj < 8; jj++) {
        x0 = fmaxf(x0, fmaxf(s[4 * jj], s[4 * jj + 1]));
        x1 = fmaxf(x1, fmaxf(s[4 * jj + 2], s[4 * jj + 3]));
      }
      x0 = fmaxf(x0, __shfl_xor_sync(0xffffffffu, x0, 1));
      x1 = fmaxf(x1, __shfl_xor_sync(0xffffffffu, x1, 1));
      x0 = fmaxf(x0, __shfl_xor_sync(0xffffffffu, x0, 2));
      x1 = fmaxf(x1, __shfl_xor_sync(0xffffffffu, x1, 2));
    };
    auto exps = [&](uint32_t (&pp)[16], float& r0, float& r1) {
      float t0, t1, t2, t3;
#pragma unroll
      for (int jj = 0; jj < 8; jj++) {
        const float e0 = ex2(fmaf(s[4 * jj], SC, b0)), e1 = ex2(fmaf(s[4 * jj + 1], SC, b0));
        const float e2 = ex2(fmaf(s[4 * jj + 2], SC, b1)), e3 = ex2(fmaf(s[4 * jj + 3], SC, b1));
        if (jj == 0) { t0 = e0; t1 = e1; t2 = e2; t3 = e3; } else { t0 += e0; t1 += e1; t2 += e2; t3 += e3; }
        pp[2 * jj] = pack_bf16(e0, e1); pp[2 * jj + 1] = pack_bf16(e2, e3);
      }
      r0 = t0 + t1; r1 = t2 + t3;
    };

    const bool up = w == which;
    const int n = 2 * qt + 2, nw = n - up, nloc = which && COUPLE ? num_private(qt) : 1000;
    int fd = which ? 0 : 2 * n - 1;
    const int dir = which ? 1 : -1;
    auto skip = [&]() { r.next(); fd += dir; };
    auto give = [&](uint32_t sl, int d) {
      mbar_arrive_pair(map_cta(bar_addr(sb, B_RG_EMPTY + sl), d < nloc ? rank : rank ^ (lane & 1)), (d & ~2) == 0 ? 2 : 1, lane);
    };
    if (which && up) skip();
    uint32_t ks = take();
    TS(62 + which);
    TR(20);
    prep_qk(sb + ks * SLOT);
    turn_begin();
    wg_fence();
#pragma unroll
    for (int kk = 0; kk < 16; kk++)
      wgmma_rs_n64(s, pk[4 * kk], pk[4 * kk + 1], pk[4 * kk + 2], pk[4 * kk + 3], desc_add(dk, (kk >> 2) * 8192 + (kk & 3) * 32), kk != 0);
    wg_commit();
    turn_end();
    TR(21);
    if (!which) conv_finish();
    TR(23);
    if (which) mbar_wait(st_empty, 0);
    if (which && !up) store_blocks<0, Q_PRE>(qreg, lb, pk);
    TR(24);
    wg_wait<0>();
    TR(22);
    reg_fence(s);
    reg_fence(pk);
    give(ks, fd);
    fd += dir;
    if (which && up) { skip(); store_blocks<0, QY_A>(qreg, lb, pk); }
    if (which || nw == 1) mask_diag();
    row_max(b0, b1);
    if (which && !up) store_blocks<16 * Q_PRE, 4 - Q_PRE>(qreg + Q_PRE * 8192, lb, pk);
    if (which && up) store_blocks<16 * QY_A, QY_B>(qreg + QY_A * 8192, lb, pk);
    b0 *= -SC; b1 *= -SC;
#pragma unroll
    for (int i = 0; i < 128; i++) acc[i] = 0.f;
    exps(pa, l0, l1);
    if (which && up) store_blocks<16 * (QY_A + QY_B), 4 - QY_A - QY_B>(qreg + (QY_A + QY_B) * 8192, lb, pk);
    if (which && nw == 1) { fence_async_smem(); warp_arrive(bar_addr(sb, B_QFREE + w), lane); }
#pragma unroll 1
    for (int jj = 1; jj < nw; jj++) {
      ks = take();
      const uint32_t vs = take();
      if (jj == 1) fence_async_smem();
      TR(30);
#pragma unroll
      for (int i = 0; i < 32; i++) s[i] = 0.f;
      prep_qk(sb + ks * SLOT);
      prep_pv(sb + vs * SLOT);
      turn_begin();
      wg_fence();
      issue_qk();
      wg_commit();
      issue_pv(1);
      wg_commit();
      turn_end();
      TR(31);
      wg_wait<1>();
      TR(32);
      reg_fence(s);
      give(ks, fd);
      if (jj == nw - 1) {
        if (!which) mask_diag();
        else if (lane == 0) mbar_arrive(bar_addr(sb, B_QFREE + w));
      }
      uint32_t pn[16];
      float t0, t1, a0 = 1.f, a1 = 1.f;
      exps(pn, t0, t1);
      const bool redo = __any_sync(0xffffffffu, !(t0 + t1 <= 65536.f));
      if (redo) {
        row_max(a0, a1);
        const float c0 = fminf(b0, -SC * a0), c1 = fminf(b1, -SC * a1);
        a0 = ex2(c0 - b0); a1 = ex2(c1 - b1);
        b0 = c0; b1 = c1;
        l0 *= a0; l1 *= a1;
        exps(pn, t0, t1);
      }
      l0 += t0; l1 += t1;
      wg_wait<0>();
      reg_fence(acc);
      reg_fence(pa);
      give(vs, fd + dir);
      fd += 2 * dir;
      if (redo) {
#pragma unroll
        for (int i = 0; i < 32; i++) { acc[4 * i] *= a0; acc[4 * i + 1] *= a0; acc[4 * i + 2] *= a1; acc[4 * i + 3] *= a1; }
      }
#pragma unroll
      for (int i = 0; i < 16; i++) pa[i] = (i & 1) ? pn[i] ^ (one - 1) : pn[i] * one;
    }
    if (!which && up) skip();
    const uint32_t vs = take();
    TR(40);
    prep_pv(sb + vs * SLOT);
    turn_begin();
    wg_fence();
    issue_pv(1);
    wg_commit();
    turn_end();
    TR(41);
    if (!which && up) r.next();
    ws = take();
    l0 += __shfl_xor_sync(0xffffffffu, l0, 1); l1 += __shfl_xor_sync(0xffffffffu, l1, 1);
    l0 += __shfl_xor_sync(0xffffffffu, l0, 2); l1 += __shfl_xor_sync(0xffffffffu, l1, 2);
    float i0, i1;
    asm volatile("rcp.approx.ftz.f32 %0, %1;" : "=f"(i0) : "f"(l0));
    asm volatile("rcp.approx.ftz.f32 %0, %1;" : "=f"(i1) : "f"(l1));
    uint32_t xs = 0;
    if (!which) xs = take();
    wg_wait<0>();
    TR(42);
    reg_fence(acc);
    reg_fence(pa);
    give(vs, fd);
    TS(7 + 3 * which);
#pragma unroll
    for (int i = 0; i < 32; i++) {
      pk[2 * i]     = pack_bf16(acc[4 * i] * i0, acc[4 * i + 1] * i0);
      pk[2 * i + 1] = pack_bf16(acc[4 * i + 2] * i1, acc[4 * i + 3] * i1);
    }
    TS(8 + 3 * which); TR(46);
    if (which) break;
    TS(31);
    uint32_t xaddr = sb + xs * SLOT + (w ^ 1) * 8192;
#pragma unroll 1
    for (int kc = 0;; kc++) {
      TR(11);
      const uint64_t da = desc_k(xaddr), db = desc_mn(sb + ws * SLOT);
      turn_begin();
      wg_fence();
#pragma unroll
      for (int kk = 0; kk < 4; kk++) wgmma_ss_n256_tb(acc, desc_add(da, kk * 32), desc_add(db, kk * 2048), (kc | kk) != 0);
      wg_commit();
      turn_end();
      TR(13);
      const int cb = kc - CTX_K;
      if (cb >= 1 && cb <= 4) { fence_async_smem(); warp_arrive(bar_addr(sb, B_CTXS + 4 * w + cb - 1), lane); }
      if ((unsigned)cb < 4) {
        if (cb & 2) { if (cb & 1) store_blocks<48, 1>(qreg + 24576, lb, pk); else store_blocks<32, 1>(qreg + 16384, lb, pk); }
        else        { if (cb & 1) store_blocks<16, 1>(qreg + 8192, lb, pk);  else store_blocks<0, 1>(qreg, lb, pk); }
      }
      TR(15);
      wg_wait<0>();
      release(bar_addr(sb, B_RG_EMPTY + ws), lane, rank, false);
      if (!(kc & 1)) release(bar_addr(sb, B_RG_EMPTY + xs), lane, rank, false);
      if (kc == 6) break;
      ws = take();
      if (!(kc & 1)) { xs = take(); xaddr = sb + xs * SLOT + (w ^ 1) * 8192; } else xaddr += 16384;
    }
    reg_fence(acc);
    TS(61); TR(16);
#pragma unroll
    for (int i = 0; i < 64; i++) pk[i] = pack_bf16(acc[2 * i], acc[2 * i + 1]);
    TS(9); TR(19);
    qt = 15 - qt;
  }

  {
    float oa[32], ob[32];
#pragma unroll
    for (int i = 0; i < 32; i++) { oa[i] = 0.f; ob[i] = 0.f; }
    auto stage_o = [&](float (&o)[32], int ch) {
      reg_fence(o);
      uint32_t q[16];
#pragma unroll
      for (int i = 0; i < 16; i++) q[i] = pack_bf16(o[2 * i], o[2 * i + 1]);
      if (ch >= 2) mbar_wait(bar_addr(sb, B_S2_EMPTY + w * 2 + (ch & 1)), ((ch >> 1) - 1) & 1);
      store_blocks<0, 1>(qreg + (ch & 1) * 8192, lb, q);
    };
    auto hand_over = [&](int ch) {
      fence_async_smem();
      warp_arrive(bar_addr(sb, B_S2_FULL + w * 2 + (ch & 1)), lane);
    };
    uint32_t pk2[64];
    uint32_t p2 = 0;
    auto chunk = [&](int ch, auto first, float (&o)[32], float (&oprev)[32]) {
      constexpr bool FIRST = decltype(first)::value;
      const uint32_t s1 = FIRST ? ws : take();
      TR(50);
      const uint64_t d1 = desc_mn(sb + s1 * SLOT);
      turn_begin();
      wg_fence();
#pragma unroll
      for (int kk = 0; kk < 16; kk++) {
        wgmma_rs_n64_tb(o, pk[4 * kk], pk[4 * kk + 1], pk[4 * kk + 2], pk[4 * kk + 3], desc_add(d1, kk * 2048), kk != 0);
        if (kk == ARRIVE_KK) turn_end();
      }
      wg_commit();
      TR(51);
      if constexpr (!FIRST) {
        wg_wait<1>();
        if (ch <= 4) release(bar_addr(sb, B_RG_EMPTY + p2), lane, rank, COUPLE);
        stage_o(oprev, ch - 1);
      } else {
        mbar_wait(bar_addr(sb, B_CTXF + w), 0);
#pragma unroll
        for (int kk = 0; kk < 16; kk++) {
          uint32_t f[4];
          ldsm4(f, qreg + (kk >> 2) * 8192 + (lb ^ ((kk & 3) << 5)));
          pk2[4 * kk] = f[0]; pk2[4 * kk + 1] = f[1]; pk2[4 * kk + 2] = f[2]; pk2[4 * kk + 3] = f[3];
        }
      }
      const uint32_t s2 = take();
      TR(53);
      const uint64_t d2 = desc_mn(sb + s2 * SLOT);
      turn_begin();
      wg_fence();
#pragma unroll
      for (int kk = 0; kk < 16; kk++) {
        wgmma_rs_n64_tb(o, pk2[4 * kk], pk2[4 * kk + 1], pk2[4 * kk + 2], pk2[4 * kk + 3], desc_add(d2, kk * 2048), 1);
        if (kk == ARRIVE_KK && (ch < 6 || w == 1)) turn_end();
      }
      wg_commit();
      TR(54);
      if (!FIRST) hand_over(ch - 1);
      wg_wait<1>();
      TR(55);
      if (ch <= 4) release(bar_addr(sb, B_RG_EMPTY + s1), lane, rank, COUPLE);
      p2 = s2;
    };
    chunk(0, Int<1>(), oa, ob);
#pragma unroll 1
    for (int ch = 1; ch < 7; ch += 2) { chunk(ch, Int<0>(), ob, oa); chunk(ch + 1, Int<0>(), oa, ob); }
    wg_wait<0>();
    TR(58);
    reg_fence(pk);
    reg_fence(pk2);
    stage_o(oa, 6);
    hand_over(6);
  }
  TS(12); TR(59);
  if (threadIdx.x == 128) ST(14);
  if ((threadIdx.x & 127) == 0) GT(54 + w);

  TS(16); TS(18); TS(17);
  TR(99); TR_END();
  TS(13); TSG(14);
}

#define CONV_STAGGER_NS 1200
namespace ssm {
#define CONV_GROUPS (D_SPARE / 8 / NCONV)
constexpr int GROUPS = CONV_GROUPS;
constexpr uint32_t ZROWS = 16;
constexpr uint32_t CHAN = (ZROWS + 256 + 1) * 16;
constexpr uint32_t XBUF = 8 * CHAN;
constexpr uint32_t OFF_X = 0;
constexpr uint32_t HCOPY = 4160;
constexpr uint32_t OFF_H = 2 * XBUF;
constexpr uint32_t HWARP = 3 * HCOPY;
constexpr uint32_t IO_K = 128, IO_V = IO_K + 4096, IO_Q = IO_V + 4096, IOBUF = IO_Q + 4096;
constexpr uint32_t OFF_IO = (OFF_H + 8 * HWARP + 127) / 128 * 128;
constexpr uint32_t END = OFF_IO + 4 * IOBUF;
static_assert(IOBUF % 128 == 0 && OFF_H % 16 == 0, "TMA destination alignment");
static_assert(END <= BARS, "smem");
enum : uint32_t { B_XREADY = 0, B_ZDONE = 2, B_KV = 4, B_Q = 8, B_HRAW = 12, B_QLAST = 20 };
constexpr int CW_BAR = 4;

__device__ __forceinline__ int group_d0(int cidx, int grp) { return (grp * NCONV + cidx) * 8; }
__device__ __forceinline__ uint32_t x_lane(int lane) { return (lane & 7) * CHAN + (ZROWS + (lane >> 3)) * 16; }
__device__ __forceinline__ uint32_t t_lane(int lane) { return (uint32_t)(8 * (lane >> 3) + 7 - (lane & 7)) * 16; }
struct Taps { uint32_t s[4]; };
__device__ __forceinline__ Taps load_taps(const Params& p, int d0, int c) {
  const uint2 s0 = __ldg(reinterpret_cast<const uint2*>(p.a_shift + (d0 + 2 * c) * 4)), s1 = __ldg(reinterpret_cast<const uint2*>(p.a_shift + (d0 + 2 * c + 1) * 4));
  return Taps{{__byte_perm(s0.x, s1.x, 0x5410), __byte_perm(s0.x, s1.x, 0x7632), __byte_perm(s0.y, s1.y, 0x5410), __byte_perm(s0.y, s1.y, 0x7632)}};
}
__device__ __forceinline__ uint32_t short_conv(const Taps& t, uint32_t k0, uint32_t k1, uint32_t k2, uint32_t k3, uint32_t v) {
  return bmul(bfma(k3, t.s[0], bfma(k2, t.s[1], bfma(k1, t.s[2], bmul(k0, t.s[3])))), v);
}
__device__ __forceinline__ void gate_chunk(uint32_t xa, uint32_t qa) {
#pragma unroll 4
  for (int i = 0; i < 8; i++) {
    uint32_t zz[4], qq[4];
    ldsm4t(zz, xa + i * 64);
    ldsm4(qq, qa + i * 512);
    stsm4(qa + i * 512, bmul(qq[0], zz[0]), bmul(qq[1], zz[1]), bmul(qq[2], zz[2]), bmul(qq[3], zz[3]));
  }
}

__device__ __forceinline__ void io_warp(const Params& p, uint32_t sb, int cidx, int wq) {
  const int lane = threadIdx.x & 31;
  const uint32_t io = sb + OFF_IO + wq * IOBUF, bkv = bar_addr(sb, B_KV + wq), bq = bar_addr(sb, B_Q + wq);
  auto load_kv = [&](int e) {
    __syncwarp();
    if (lane != 0) return;
    const int d0 = group_d0(cidx, e >> 1), row = (2 * wq + (e & 1)) * 256;
    if (e < 2 * GROUPS) {
      mbar_expect_tx(bkv, IO_Q);
      tma_ld2(io, &p.ak8, bkv, d0, row - 8);
      tma_ld2(io + IO_K, &p.ak, bkv, d0, row);
      tma_ld2(io + IO_V, &p.av, bkv, d0, row);
    } else {
      const uint32_t bar = bar_addr(sb, B_QLAST + 2 * wq + 1);
      mbar_expect_tx(bar, 4096);
      tma_ld2(io + IO_K, &p.aq, bar, group_d0(cidx, GROUPS - 1), row + 256);
    }
  };
  auto load_q = [&](int e) {
    __syncwarp();
    if (lane != 0) return;
    const uint32_t bar = e < 2 * GROUPS - 2 ? bq : bar_addr(sb, B_QLAST + 2 * wq);
    mbar_expect_tx(bar, 4096);
    tma_ld2(io + IO_Q, &p.aq, bar, group_d0(cidx, e >> 1), (2 * wq + (e & 1)) * 256);
  };
  TR_DECL;
  TR(0);
  load_kv(0);
  const uint32_t xl = sb + OFF_X + x_lane(lane) + wq * 1024, tl = io + t_lane(lane);
#pragma unroll 1
  for (int grp = -2; grp + 1 < GROUPS; grp++) {
    const bool more = grp + 2 < GROUPS;
    const Taps taps = load_taps(p, group_d0(cidx, more ? grp + 2 : 0), lane & 3);
    PCLK(c0);
    if (grp >= 0) mbar_wait_nap(bar_addr(sb, B_ZDONE + (grp & 1)), (grp >> 1) & 1);
    PACC(tp, c0);
    PCLK(c1);
    TR(80);
#pragma unroll 1
    for (int i = 0; i < 2; i++) {
      const uint32_t xa = xl + (grp & 1) * XBUF + i * 512;
      if (grp >= 0) {
        mbar_wait_nap(bq, i);
        TR(81);
        gate_chunk(xa, tl + IO_Q);
      }
      if (more) {
        TR(82);
        mbar_wait_nap(bkv, i);
        TR(83);
#pragma unroll 2
        for (int u = 0; u < 8; u++) {
          const uint32_t ka = tl + IO_K + u * 512;
          uint32_t k0[4], k1[4], k2[4], k3[4], vv[4];
          ldsm4(k0, ka - 48); ldsm4(k1, ka - 32); ldsm4(k2, ka - 16); ldsm4(k3, ka); ldsm4(vv, ka + 4096);
          stsm4t(xa + u * 64, short_conv(taps, k0[0], k1[0], k2[0], k3[0], vv[0]), short_conv(taps, k0[1], k1[1], k2[1], k3[1], vv[1]),
                 short_conv(taps, k0[2], k1[2], k2[2], k3[2], vv[2]), short_conv(taps, k0[3], k1[3], k2[3], k3[3], vv[3]));
        }
        load_kv(2 * (grp + 2) + i + 1);
        TR(84);
        if (i == 1) warp_arrive(bar_addr(sb, B_XREADY + (grp & 1)), lane);
      }
      if (grp >= 0) {
        fence_async_smem();
        __syncwarp();
        if (lane == 0) {
          tma_st2(&p.ao, io + IO_Q, group_d0(cidx, grp), (2 * wq + i) * 256);
          bulk_commit();
          bulk_wait_read();
        }
      }
      if (2 * grp + i + 1 >= 0) load_q(2 * grp + i + 1);
      TR(85);
    }
    PACC(te, c1);
  }
  if (lane == 0) bulk_wait_all();
  TR(99); TR_END();
}

__device__ __forceinline__ void conv_warp(const Params& p, uint32_t sb, int cidx, int ch) {
  const int lane = threadIdx.x & 31;
  const uint32_t hE0 = sb + OFF_H + ch * HWARP, hO = hE0 + HCOPY;
  const uint32_t hbar = bar_addr(sb, B_HRAW + ch);
  auto fetch_h = [&](int grp) {
    if (lane == 0) {
      mbar_expect_tx(hbar, 4096);
      asm volatile("cp.async.bulk.shared::cluster.global.mbarrier::complete_tx::bytes [%0], [%1], %2, [%3];"
                   :: "r"(hE0 + (grp & 1) * 2 * HCOPY + 32), "l"(p.a_ssmk + (size_t)(group_d0(cidx, grp) + ch) * SEQ), "r"(4096), "r"(hbar) : "memory");
    }
  };
  TR_DECL;
  TR(0);
  fetch_h(0);
#pragma unroll 1
  for (int grp = 0; grp < GROUPS; grp++) {
    const uint32_t xc = sb + OFF_X + (grp & 1) * XBUF + ch * CHAN;
    const uint32_t Dd = (uint32_t)__ldg(reinterpret_cast<const unsigned short*>(p.a_D + group_d0(cidx, grp) + ch)) * 0x10001u;
    PCLK(k0);
    mbar_wait(hbar, grp & 1);
    const uint32_t hE = hE0 + (grp & 1) * 2 * HCOPY;
    if (grp + 1 < GROUPS) fetch_h(grp + 1);
#pragma unroll
    for (int i = 0; i < 8; i++) {
      const uint32_t o = 32 + (i * 32 + lane) * 16;
      const uint4 w = lds16(hE + o);
      const uint32_t nx = lds4(hE + o + 16);
      sts16(hO + o, __byte_perm(w.x, w.y, 0x5432), __byte_perm(w.y, w.z, 0x5432), __byte_perm(w.z, w.w, 0x5432), __byte_perm(w.w, nx, 0x5432));
      if (o == 32) asm volatile("st.shared.u32 [%0], %1;" :: "r"(hO + 28), "r"(w.x << 16) : "memory");
    }
    __syncwarp();
    const uint32_t ha = cv_h_lane(lane, hE, hO), xa = xc + cv_x_lane(lane);
    TR(71);
    mbar_wait(bar_addr(sb, B_XREADY + (grp & 1)), (grp >> 1) & 1);
    TR(72);
    if (grp == 0 && ch >= 4) __nanosleep(CONV_STAGGER_NS);
    PACC(tw, k0);
    PCLK(k1);
    float acc[16][4];
#pragma unroll
    for (int i = 0; i < 16; i++) { acc[i][0] = 0.f; acc[i][1] = 0.f; acc[i][2] = 0.f; acc[i][3] = 0.f; }
#pragma unroll 1
    for (int r = 0; r < 8; r++) {
      uint32_t fx[16][4], fh[16][2];
#pragma unroll
      for (int i = 0; i < 16; i++) { fh[i][0] = lds4(ha + i * 256 + r * 32); fh[i][1] = lds4(ha + i * 256 + r * 32 + 16); }
#pragma unroll
      for (int i = 0; i < 16; i++) ldsm4(fx[i], xa + i * 256 - r * 32);
#pragma unroll
      for (int sx = 0; sx < 16; sx++)
#pragma unroll
        for (int jj = 0; jj < 16 - sx; jj++) mma16816(acc[jj + sx], fx[sx], fh[jj][0], fh[jj][1]);
    }
    PACC(tm, k1);
    PCLK(k2);
    TR(73);
#pragma unroll
    for (int i = 0; i < 8; i++) {
      uint32_t x[4];
      const uint32_t ad = xc + (ZROWS + lane) * 16 + i * 512;
      ldsm4(x, ad);
      stsm4(ad, badd(pack_bf16(acc[2 * i][0], acc[2 * i][1]), bmul(x[0], Dd)), badd(pack_bf16(acc[2 * i][2], acc[2 * i][3]), bmul(x[1], Dd)),
            badd(pack_bf16(acc[2 * i + 1][0], acc[2 * i + 1][1]), bmul(x[2], Dd)), badd(pack_bf16(acc[2 * i + 1][2], acc[2 * i + 1][3]), bmul(x[3], Dd)));
    }
    if (grp + 1 < GROUPS) warp_arrive(bar_addr(sb, B_ZDONE + (grp & 1)), lane);
    PACC(tr, k2);
    TR(74);
  }
  {
    mbar_wait(bar_addr(sb, B_QLAST + ch), 0);
    named_sync(CW_BAR, 256);
    TR(75);
    const uint32_t qb = sb + OFF_IO + (ch >> 1) * IOBUF + ((ch & 1) ? IO_K : IO_Q);
    gate_chunk(sb + OFF_X + ((GROUPS - 1) & 1) * XBUF + x_lane(lane) + ch * 512, qb + t_lane(lane));
    fence_async_smem();
    __syncwarp();
    if (lane == 0) { tma_st2(&p.ao, qb, group_d0(cidx, GROUPS - 1), ch * 256); bulk_commit(); bulk_wait_all(); }
    TR(99); TR_END();
  }
}

__device__ __forceinline__ void init(uint32_t sb) {
  if (threadIdx.x < 16 * ZROWS) sts16(sb + OFF_X + (threadIdx.x >> 4) * CHAN + (threadIdx.x & 15) * 16, 0, 0, 0, 0);
  if (threadIdx.x < 96) sts16(sb + OFF_H + (threadIdx.x >> 2) * HCOPY + (threadIdx.x & 1) * 16 + ((threadIdx.x & 2) ? 4128 : 0), 0, 0, 0, 0);
  if (threadIdx.x == 0) {
    for (int i = 0; i < 2; i++) { mbar_init(bar_addr(sb, B_XREADY + i), 4); mbar_init(bar_addr(sb, B_ZDONE + i), 8); }
    for (int i = 0; i < 4; i++) { mbar_init(bar_addr(sb, B_KV + i), 1); mbar_init(bar_addr(sb, B_Q + i), 1); }
    for (int i = 0; i < 8; i++) { mbar_init(bar_addr(sb, B_HRAW + i), 1); mbar_init(bar_addr(sb, B_QLAST + i), 1); }
    fence_async_smem();
  }
  named_sync(0, NTHREADS);
}
}

__device__ __forceinline__ void ssm_side_work(const Params& p, uint32_t sb, unsigned epoch) {
  const Role ro = get_role();
  const int h = ro.h, j = ro.j;
  const int lane = threadIdx.x & 31, g = lane >> 2, c = lane & 3;
  const int d0 = D_SPARE + 8 * h;
  uint8_t* xs = g_xs + (size_t)(h * 8 + g) * CV_BYTES + c * 4;
  auto xrow = [&](int beta) { return xs + (16 + beta) * 16; };
  {
    const uint4* hp = reinterpret_cast<const uint4*>(p.a_ssmk + (size_t)(d0 + j) * SEQ) + lane;
    uint8_t* he = g_xs + (size_t)(h * 8 + j) * CV_BYTES + CV_HE;
#pragma unroll 2
    for (int i = 0; i < 8; i++) {
      const uint4 wv = __ldg(hp + i * 32);
      const uint32_t nx = i * 32 + lane < 255 ? __ldg(reinterpret_cast<const uint32_t*>(hp + i * 32 + 1)) : 0u;
      const uint32_t o = 32 + (i * 32 + lane) * 16;
      *reinterpret_cast<uint4*>(he + o) = wv;
      *reinterpret_cast<uint4*>(he + CV_HCOPY + o) =
          make_uint4(__byte_perm(wv.x, wv.y, 0x5432), __byte_perm(wv.y, wv.z, 0x5432), __byte_perm(wv.z, wv.w, 0x5432), __byte_perm(wv.w, nx, 0x5432));
      if (o == 32) *reinterpret_cast<uint32_t*>(he + CV_HCOPY + 28) = wv.x << 16;
    }
    if (lane == 0) *reinterpret_cast<uint32_t*>(he + CV_D - CV_HE) = (uint32_t)__ldg(reinterpret_cast<const unsigned short*>(p.a_D + d0 + j)) * 0x10001u;
  }
  {
    const ssm::Taps taps = ssm::load_taps(p, d0, c);
    const uint32_t* kp = reinterpret_cast<const uint32_t*>(p.a_k + (size_t)(256 * j + 7 - g) * DA + d0) + c;
    const uint32_t* vp = reinterpret_cast<const uint32_t*>(p.a_v + (size_t)(256 * j + 7 - g) * DA + d0) + c;
    uint32_t kprev = j > 0 ? __ldg(kp - 8 * (DA / 2)) : 0u;
#pragma unroll 1
    for (int i0 = 0; i0 < 32; i0 += 8) {
      uint32_t kk[8], vv[8];
#pragma unroll
      for (int i = 0; i < 8; i++) { kk[i] = __ldg(kp + (i0 + i) * 8 * (DA / 2)); vv[i] = __ldg(vp + (i0 + i) * 8 * (DA / 2)); }
#pragma unroll
      for (int i = 0; i < 8; i++) {
        const uint32_t k2 = __shfl_sync(0xffffffffu, g < 1 ? kprev : kk[i], (lane + 4) & 31);
        const uint32_t k1 = __shfl_sync(0xffffffffu, g < 2 ? kprev : kk[i], (lane + 8) & 31);
        const uint32_t k0 = __shfl_sync(0xffffffffu, g < 3 ? kprev : kk[i], (lane + 12) & 31);
        *reinterpret_cast<uint32_t*>(xrow(32 * j + i0 + i)) = transpose8(ssm::short_conv(taps, k0, k1, k2, kk[i], vv[i]));
        kprev = kk[i];
      }
    }
    __syncwarp();
    if (lane == 0) {
      flag_signal(&g_flags.xs_ready[h].v);
      flag_wait(&g_flags.xs_ready[h].v, 8, epoch);
      fence_async_all();
      mbar_arrive(bar_addr(sb, B_XS));
    }
  }
  if (lane == 0) {
    for (int i = 0; i < 3; i++) {
      flag_wait(&g_flags.kv_ready[3 * h + i].v, 16, epoch);
      fence_async_all();
      mbar_arrive(bar_addr(sb, B_KV + i));
    }
    mbar_wait_nap(bar_addr(sb, B_CONV), 0);
    flag_signal(&g_flags.zs_ready[h].v);
    flag_wait(&g_flags.zs_ready[h].v, 8, epoch);
    asm volatile("red.relaxed.gpu.global.add.u64 [%0], 1;" :: "l"(&g_flags.done) : "memory");
  }
  __syncwarp();
  fence_async_all();
  const uint32_t qb = q_region(sb, 1) + 16384, zb = qb + 4096, bar = bar_addr(sb, B_GATE);
  constexpr uint32_t ZCH = 528;
  mbar_wait_slow(bar_addr(sb, B_GFREE), 0);
  if (lane == 0) { mbar_expect_tx(bar, 8192); tma_ld2(qb, &p.aq, bar, d0, 256 * j); }
  __syncwarp();
  if (lane < 8) bulk_ld(zb + lane * ZCH, g_xs + (size_t)(h * 8 + lane) * CV_BYTES + (16 + 32 * j) * 16, 512, bar);
  mbar_wait(bar, 0);
  ssm::gate_chunk(zb + (lane & 7) * ZCH + (lane >> 3) * 16, qb + ssm::t_lane(lane));
  fence_async_smem();
  __syncwarp();
  if (lane == 0) { tma_st2(&p.ao, qb, d0, 256 * j); bulk_commit(); bulk_wait_all(); }
}

__global__ void __cluster_dims__(2, 1, 1) __launch_bounds__(NTHREADS, 1)
concat_heads__ssm_conv_h3__compressed_kv_cla__prompt_kernel(uint8_t* xs, uint32_t one, const __grid_constant__ Params p) {
  if (PF_MAP && threadIdx.x == 0) { prefetch_map(&p.wuk); prefetch_map(&p.ckv); }
  extern __shared__ uint8_t smem_raw[];
  if (threadIdx.x == 96) { ST(0); STG_(10); }
  const uint32_t sb = (smem_u32(smem_raw) + 1023) & ~1023u;
  const int warp = __shfl_sync(0xffffffffu, threadIdx.x >> 5, 0);
  const int wg = warp >> 2;
  const int cta = blockIdx.x;
  const bool attn = cta < NMAIN;
  if (attn && (threadIdx.x >> 5) == 4) {
    const Role ro = get_role();
    auto load = [&](int k) {
      const uint32_t full = bar_addr(sb, B_P1_FULL + k), dst = sb + k * P1_STAGE;
      mbar_expect_tx(full, P1_STAGE);
      tma_ld2(dst, &p.ckv, full, k * 64, 2 * ro.j * 128);
      tma_ld3(dst + 16384, &p.wuk, full, 0, k * 64, ro.h * 4);
    };
    if (threadIdx.x == 128) {
      for (int i = 0; i < 4; i++) mbar_init(bar_addr(sb, B_P1_FULL + i), 1);
      asm volatile("fence.mbarrier_init.release.cluster;" ::: "memory");
      ST(1);
      load(0);
    }
    __syncwarp();
    named_arrive(0, NTHREADS);
    if (threadIdx.x == 128) {
      for (int k = 1; k < EARLY_LD; k++) load(k);
      ST(2);
    }
    __syncwarp();
  }
  const int lane = threadIdx.x & 31;
  if (wg == 0) {
    if (!attn) {
      asm volatile("setmaxnreg.dec.sync.aligned.u32 72;");
      if (threadIdx.x == 0) GT(0);
      if (one) { ssm::init(sb); ssm::io_warp(p, sb, cta - NMAIN, fresh_warp()); }
      if (threadIdx.x == 0) GT(14);
      return;
    }
    asm volatile("setmaxnreg.dec.sync.aligned.u32 40;");
    named_arrive(PP_BAR + 1, 256);
    if (warp == 2) {
      if (lane == 0) {
        for (int i = 0; i < 4; i++) mbar_init(bar_addr(sb, B_P1_EMPTY + i), 16);
        for (int i = 0; i < NSLOT; i++) {
          mbar_init(bar_addr(sb, B_RG_FULL + i), 1); mbar_init(bar_addr(sb, B_RG_EMPTY + i), 16); mbar_init(bar_addr(sb, B_PFREE + i), 1);
        }
        for (int i = 0; i < 2; i++) { mbar_init(bar_addr(sb, B_ST_FULL + i), 4); mbar_init(bar_addr(sb, B_ST_EMPTY + i), 1); }
        mbar_init(bar_addr(sb, B_XS), 1); mbar_init(bar_addr(sb, B_CONV), 8); mbar_init(bar_addr(sb, B_GATE), 1); mbar_init(bar_addr(sb, B_GFREE), 1);
        for (int i = 0; i < 3; i++) mbar_init(bar_addr(sb, B_KV + i), 1);
        for (int i = 0; i < 8; i++) mbar_init(bar_addr(sb, B_CTXS + i), 4);
        for (int i = 0; i < 4; i++) { mbar_arrive(bar_addr(sb, B_RG_FULL + i)); if (i < 3) mbar_arrive_n(bar_addr(sb, B_RG_EMPTY + i), 16); }
        for (int i = 0; i < 4; i++) { mbar_init(bar_addr(sb, B_S2_FULL + i), 4); mbar_init(bar_addr(sb, B_S2_EMPTY + i), 1); }
        for (int i = 0; i < 2; i++) { mbar_init(bar_addr(sb, B_QFREE + i), 4); mbar_init(bar_addr(sb, B_CTXF + i), 1); }
        asm volatile("fence.mbarrier_init.release.cluster;" ::: "memory");
        ST(3);
      }
      __syncwarp();
      named_arrive(0, NTHREADS);
    } else {
      named_sync(0, NTHREADS);
    }
    if (threadIdx.x == 96) ST(4);
    if (warp == 0) {
      if (lane == 0) producer_main(p, sb);
    } else if (warp < 3) {
      storer_main(p, sb);
    } else {
      const unsigned epoch = load_epoch();
      mbar_wait(bar_addr(sb, B_P1_FULL + 3), 0);
      __nanosleep(SIDE_DELAY_NS);
      ssm_side_work(p, sb, epoch);
    }
  } else {
    if (attn) {
      asm volatile("setmaxnreg.inc.sync.aligned.u32 232;");
      if (threadIdx.x == 256) ST(5);
      if (one) consumer_main(p, sb, xs, one);
    } else {
      asm volatile("setmaxnreg.inc.sync.aligned.u32 216;");
      if (threadIdx.x == 128) { GT(12); PT(10); }
      if (one) { ssm::init(sb); ssm::conv_warp(p, sb, cta - NMAIN, fresh_warp() - 4); }
      if (threadIdx.x == 128) { PT(9); GT(13); }
    }
  }
}

typedef CUresult (*EncodeTiledFn)(CUtensorMap*, CUtensorMapDataType, cuuint32_t, void*, const cuuint64_t*, const cuuint64_t*,
                                  const cuuint32_t*, const cuuint32_t*, CUtensorMapInterleave, CUtensorMapSwizzle,
                                  CUtensorMapL2promotion, CUtensorMapFloatOOBfill);

void make_map(EncodeTiledFn enc, CUtensorMap* m, const void* ptr, int rank, const uint64_t* dims, const uint64_t* strides, const uint32_t* box) {
  cuuint64_t d[3], s[2]; cuuint32_t b[3], e[3] = {1, 1, 1};
  for (int i = 0; i < rank; i++) { d[i] = dims[i]; b[i] = box[i]; if (i) s[i - 1] = strides[i - 1]; }
  enc(m, CU_TENSOR_MAP_DATA_TYPE_BFLOAT16, rank, const_cast<void*>(ptr), d, s, b, e, CU_TENSOR_MAP_INTERLEAVE_NONE,
      CU_TENSOR_MAP_SWIZZLE_128B, CU_TENSOR_MAP_L2_PROMOTION_L2_256B, CU_TENSOR_MAP_FLOAT_OOB_FILL_NONE);
}
void map2(EncodeTiledFn enc, CUtensorMap* m, const void* ptr, uint64_t cols, uint64_t rows, uint32_t bc, uint32_t br) {
  const uint64_t dims[2] = {cols, rows}, st[1] = {cols * 2}; const uint32_t box[2] = {bc, br};
  make_map(enc, m, ptr, 2, dims, st, box);
}
void map2_plain(EncodeTiledFn enc, CUtensorMap* m, const void* ptr, uint64_t cols, uint64_t rows, uint32_t bc, uint32_t br) {
  cuuint64_t d[2] = {cols, rows}, st[1] = {cols * 2}; cuuint32_t b[2] = {bc, br}, e[2] = {1, 1};
  enc(m, CU_TENSOR_MAP_DATA_TYPE_BFLOAT16, 2, const_cast<void*>(ptr), d, st, b, e, CU_TENSOR_MAP_INTERLEAVE_NONE,
      CU_TENSOR_MAP_SWIZZLE_NONE, CU_TENSOR_MAP_L2_PROMOTION_L2_128B, CU_TENSOR_MAP_FLOAT_OOB_FILL_NONE);
}
void map3(EncodeTiledFn enc, CUtensorMap* m, const void* ptr, uint64_t rows, uint32_t nblk) {
  const uint64_t dims[3] = {64, rows, 64}, st[2] = {8192, 128}; const uint32_t box[3] = {64, 64, nblk};
  make_map(enc, m, ptr, 3, dims, st, box);
}

}

extern "C" void kernel_launch(void* const* d_in, const int* in_sizes, int n_in, void* d_out, int out_size) {
  (void)in_sizes; (void)n_in; (void)out_size;
  static EncodeTiledFn enc = nullptr;
  static void *kv_ptr = nullptr, *acc_ptr = nullptr, *xs_ptr = nullptr;
  if (!enc) {
    void* fn = nullptr; cudaDriverEntryPointQueryResult qr;
    cudaGetDriverEntryPoint("cuTensorMapEncodeTiled", &fn, cudaEnableDefault, &qr);
    enc = (EncodeTiledFn)fn;
    cudaGetSymbolAddress(&kv_ptr, g_kv);
    cudaGetSymbolAddress(&acc_ptr, g_ctx);
    cudaGetSymbolAddress(&xs_ptr, g_xs);
    cudaFuncSetAttribute(concat_heads__ssm_conv_h3__compressed_kv_cla__prompt_kernel, cudaFuncAttributeMaxDynamicSharedMemorySize, SMEM_BYTES);
  }
  Params p;
  p.a_q = (const bf16*)d_in[0]; p.a_k = (const bf16*)d_in[1]; p.a_v = (const bf16*)d_in[2];
  map2_plain(enc, &p.aq, d_in[0], DA, SEQ, 8, 256);
  map2_plain(enc, &p.ak, d_in[1], DA, SEQ, 8, 256);
  map2_plain(enc, &p.ak8, d_in[1], DA, SEQ, 8, 8);
  map2_plain(enc, &p.av, d_in[2], DA, SEQ, 8, 256);
  map2_plain(enc, &p.ao, d_out, OUTW, SEQ, 8, 256);
  p.a_shift = (const bf16*)d_in[3]; p.a_ssmk = (const bf16*)d_in[4]; p.a_D = (const bf16*)d_in[5];
  p.out = (bf16*)d_out; p.b_x = (const bf16*)d_in[6]; p.b_wo = (const bf16*)d_in[11];
  map2(enc, &p.x, d_in[6], DM, SEQ, 64, 128);
  map2(enc, &p.ckv, d_in[7], DC, SEQ, 64, 128);
  map3(enc, &p.wq, d_in[8], DM, 4);
  map2_plain(enc, &p.wqp, d_in[8], NH * HD, DM, 256, 4);
  map3(enc, &p.wuk, d_in[9], DC, 4);
  map3(enc, &p.wuv, d_in[10], DC, 4);
  map2(enc, &p.wo, d_in[11], DM, NH * HD, 64, 128);
  {
    const uint64_t dims[3] = {64, 2 * NH * SEQ, 4}, st[2] = {HD * 2, 128}; const uint32_t box[3] = {64, 64, 2};
    make_map(enc, &p.kv, kv_ptr, 3, dims, st, box);
    const uint32_t box1[3] = {64, KV_TMA ? KV_TMA : 64, 1};
    make_map(enc, &p.kvs, kv_ptr, 3, dims, st, box1);
  }
  map2(enc, &p.part, d_out, OUTW, SEQ, 64, 64);
  {
    const uint64_t dims[3] = {64, NMAIN * 128, 4}, st[2] = {HD * 2, 128}; const uint32_t box[3] = {64, 64, 4};
    make_map(enc, &p.ctx, acc_ptr, 3, dims, st, box);
    const uint32_t box1[3] = {64, 64, 1};
    make_map(enc, &p.ctxs, acc_ptr, 3, dims, st, box1);
  }
  concat_heads__ssm_conv_h3__compressed_kv_cla__prompt_kernel<<<NCTA, NTHREADS, SMEM_BYTES>>>((uint8_t*)xs_ptr, 1u, p);
}
```

```cpp
#include <cuda_runtime.h>
#include <cuda_bf16.h>
#include <cuda.h>
#include <stdint.h>

namespace {

typedef __nv_bfloat16 bf16;

constexpr int SEQ  = 2048;
constexpr int DA   = 448;
constexpr int NH   = 16;
constexpr int HD   = 256;
constexpr int DM   = 448;
constexpr int DC   = 1024;
constexpr int OUTW = DA + DM;
constexpr int NMAIN = 128;
constexpr int NCONV = 4;
constexpr int NCTA  = NMAIN + NCONV;
constexpr int NTHREADS = 384;
constexpr int D_SPARE = 320;

__device__ __align__(1024) bf16 g_kv[2ull * SEQ * NH * HD];
__device__ __align__(1024) bf16 g_ctx[(size_t)NMAIN * 128 * HD];
constexpr uint32_t CV_HE = 272 * 16, CV_HCOPY = 4160, CV_D = CV_HE + 4144, CV_BYTES = CV_HE + 2 * CV_HCOPY;
__device__ __align__(128) uint8_t g_xs[NMAIN * CV_BYTES];
struct alignas(128) Flag { unsigned v; unsigned pad[31]; };
struct Flags {
  Flag kv_ready[3 * NH];
  Flag ctx_ready[NMAIN * 2];
  Flag out_ready[16 * 2];
  Flag xs_ready[NH];
  Flag zs_ready[NH];
  alignas(128) unsigned long long done;
};
__device__ Flags g_flags;
#define TS(i)
#define TSG(i)
#define GT(i)
#define PT(i)
#define WHICH_TS 0
#define PCLK(var)
#define PACC(acc, t0)
#define PDECL
#define PDUMP()

#define ST(i)
#define STG_(i)
#define TR_DECL
#define TR(tag)
#define TR_END()
#define TRG(tag)

struct alignas(64) Params {
  CUtensorMap ckv;
  CUtensorMap wuk;
  CUtensorMap wuv;
  CUtensorMap x;
  CUtensorMap wq;
  CUtensorMap wqp;
  CUtensorMap part;
  CUtensorMap wo;
  CUtensorMap ak, ak8, av, aq, ao;
  const bf16 *a_q, *a_k, *a_v, *a_shift, *a_ssmk, *a_D, *b_x, *b_wo;
  bf16* out;
  uint8_t *kv, *ctx;
};

constexpr uint32_t P1_STAGE = 49152;
constexpr uint32_t P1_STG   = 196608;
constexpr uint32_t SLOT     = 32768;
constexpr int      NSLOT    = 5;
constexpr uint32_t QREG     = 163840;
constexpr uint32_t CV_X = 4 * SLOT + 16384, CV_R = 3 * SLOT;
static_assert(CV_BYTES <= 16384 && CV_BYTES % 128 == 0, "SSM operands");
constexpr uint32_t BARS     = 229376;
constexpr uint32_t SMEM_BYTES = BARS + 512 + 1024;
enum : uint32_t {
  B_P1_FULL = 0, B_P1_EMPTY = 4, B_RG_FULL = 8, B_RG_EMPTY = 13, B_ST_FULL = 18, B_ST_EMPTY = 20,
  B_XS = 22, B_S2_FULL = 28, B_S2_EMPTY = 32, B_QFREE = 36, B_CTXF = 38, B_KV = 40, B_GATE = 43, B_CTXS = 44, B_GFREE = 52, B_CONV = 53, B_COUNT = 54
};

__device__ __forceinline__ uint32_t smem_u32(const void* p) { return (uint32_t)__cvta_generic_to_shared(p); }
__device__ __forceinline__ void mbar_init(uint32_t bar, uint32_t cnt) {
  asm volatile("mbarrier.init.shared::cta.b64 [%0], %1;" :: "r"(bar), "r"(cnt) : "memory");
}
__device__ __forceinline__ void mbar_expect_tx(uint32_t bar, uint32_t bytes) {
  asm volatile("mbarrier.arrive.expect_tx.shared::cta.b64 _, [%0], %1;" :: "r"(bar), "r"(bytes) : "memory");
}
__device__ __forceinline__ void mbar_arrive(uint32_t bar) {
  asm volatile("mbarrier.arrive.shared::cta.b64 _, [%0];" :: "r"(bar) : "memory");
}
__device__ __forceinline__ void mbar_arrive_n(uint32_t bar, uint32_t n) {
  asm volatile("mbarrier.arrive.shared::cta.b64 _, [%0], %1;" :: "r"(bar), "r"(n) : "memory");
}
__device__ __forceinline__ void lane0_arrive(uint32_t bar, uint32_t n, int lane) {
  asm volatile("{\n.reg .pred p;\nsetp.eq.s32 p, %2, 0;\n@p mbarrier.arrive.shared::cta.b64 _, [%0], %1;\n}" :: "r"(bar), "r"(n), "r"(lane) : "memory");
}
__device__ __forceinline__ bool mbar_try(uint32_t bar, uint32_t parity) {
  uint32_t ok;
  asm volatile("{\n.reg .pred p;\nmbarrier.try_wait.parity.shared::cta.b64 p, [%1], %2;\nselp.u32 %0, 1, 0, p;\n}"
               : "=r"(ok) : "r"(bar), "r"(parity) : "memory");
  return ok;
}
#define FLAG_NS 100
#define NAP_NS 100
constexpr uint32_t SPIN_LIMIT = 1u << 24;
__device__ __forceinline__ void mbar_wait(uint32_t bar, uint32_t parity) {
  if (mbar_try(bar, parity)) return;
  uint32_t n = 0;
  while (!mbar_try(bar, parity)) { if (++n > SPIN_LIMIT) __trap(); }
}
__device__ __forceinline__ void mbar_wait_nap(uint32_t bar, uint32_t parity) {
  uint32_t n = 0;
  while (!mbar_try(bar, parity)) { if (++n > (SPIN_LIMIT >> 2)) __trap(); __nanosleep(NAP_NS); }
}
__device__ __forceinline__ void mbar_wait_slow(uint32_t bar, uint32_t parity) {
  uint32_t n = 0;
  while (!mbar_try(bar, parity)) { if (++n > (SPIN_LIMIT >> 4)) __trap(); __nanosleep(500); }
}
__device__ __forceinline__ unsigned load_epoch() {
  unsigned long long e; asm volatile("ld.relaxed.gpu.global.u64 %0, [%1];" : "=l"(e) : "l"(&g_flags.done) : "memory"); return (unsigned)(e / NMAIN);
}
__device__ __forceinline__ void flag_wait(const unsigned* f, unsigned count, unsigned epoch) {
  const unsigned target = (epoch + 1) * count;
  uint32_t n = 0;
  while (true) {
    unsigned v;
    asm volatile("ld.acquire.gpu.global.u32 %0, [%1];" : "=r"(v) : "l"(f) : "memory");
    if ((int)(v - target) >= 0) break;
    if (++n > SPIN_LIMIT) __trap();
    __nanosleep(FLAG_NS);
  }
}
__device__ __forceinline__ void fence_async_all() { asm volatile("fence.proxy.async;" ::: "memory"); }
__device__ __forceinline__ void flag_signal(unsigned* f) {
  asm volatile("fence.acq_rel.gpu;" ::: "memory");
  asm volatile("red.relaxed.gpu.global.add.u32 [%0], 1;" :: "l"(f) : "memory");
}
__device__ __forceinline__ void flag_signal_after_bulk(unsigned* f) {
  asm volatile("red.relaxed.gpu.global.add.u32 [%0], 1;" :: "l"(f) : "memory");
}
__device__ __forceinline__ void fence_async_smem() { asm volatile("fence.proxy.async.shared::cta;" ::: "memory"); }
__device__ __forceinline__ void tma_ld2(uint32_t dst, const CUtensorMap* m, uint32_t bar, int c0, int c1) {
  asm volatile("cp.async.bulk.tensor.2d.shared::cluster.global.mbarrier::complete_tx::bytes [%0], [%1, {%3, %4}], [%2];"
               :: "r"(dst), "l"(m), "r"(bar), "r"(c0), "r"(c1) : "memory");
}
__device__ __forceinline__ void tma_ld3(uint32_t dst, const CUtensorMap* m, uint32_t bar, int c0, int c1, int c2) {
  asm volatile("cp.async.bulk.tensor.3d.shared::cluster.global.mbarrier::complete_tx::bytes [%0], [%1, {%3, %4, %5}], [%2];"
               :: "r"(dst), "l"(m), "r"(bar), "r"(c0), "r"(c1), "r"(c2) : "memory");
}
__device__ __forceinline__ void bulk_ld(uint32_t dst, const void* src, uint32_t bytes, uint32_t bar) {
  asm volatile("cp.async.bulk.shared::cluster.global.mbarrier::complete_tx::bytes [%0], [%1], %2, [%3];"
               :: "r"(dst), "l"(src), "r"(bytes), "r"(bar) : "memory");
}
__device__ __forceinline__ void bulk_st(void* dst, uint32_t src, uint32_t bytes) {
  asm volatile("cp.async.bulk.global.shared::cta.bulk_group [%0], [%1], %2;" :: "l"(dst), "r"(src), "r"(bytes) : "memory");
}
__device__ __forceinline__ void tma_st2(const CUtensorMap* m, uint32_t src, int c0, int c1) {
  asm volatile("cp.async.bulk.tensor.2d.global.shared::cta.bulk_group [%0, {%2, %3}], [%1];"
               :: "l"(m), "r"(src), "r"(c0), "r"(c1) : "memory");
}
__device__ __forceinline__ void tma_red2(const CUtensorMap* m, uint32_t src, int c0, int c1) {
  asm volatile("cp.reduce.async.bulk.tensor.2d.global.shared::cta.add.tile.bulk_group [%0, {%2, %3}], [%1];"
               :: "l"(m), "r"(src), "r"(c0), "r"(c1) : "memory");
}
__device__ __forceinline__ void tma_pf2(const CUtensorMap* m, int c0, int c1) {
  asm volatile("cp.async.bulk.prefetch.tensor.2d.L2.global.tile [%0, {%1, %2}];" :: "l"(m), "r"(c0), "r"(c1) : "memory");
}
__device__ __forceinline__ void bulk_prefetch(const void* src, uint32_t bytes) {
  asm volatile("cp.async.bulk.prefetch.L2.global [%0], %1;" :: "l"(src), "r"(bytes) : "memory");
}
__device__ __forceinline__ void bulk_commit() { asm volatile("cp.async.bulk.commit_group;" ::: "memory"); }
__device__ __forceinline__ void bulk_wait_read() { asm volatile("cp.async.bulk.wait_group.read 0;" ::: "memory"); }
__device__ __forceinline__ void bulk_wait_all() { asm volatile("cp.async.bulk.wait_group 0;" ::: "memory"); }
__device__ __forceinline__ void prefetch_map(const CUtensorMap* m) { asm volatile("prefetch.tensormap [%0];" :: "l"(m) : "memory"); }
__device__ __forceinline__ void wg_fence() { asm volatile("wgmma.fence.sync.aligned;" ::: "memory"); }
__device__ __forceinline__ void wg_commit() { asm volatile("wgmma.commit_group.sync.aligned;" ::: "memory"); }
template <int N> __device__ __forceinline__ void wg_wait() { asm volatile("wgmma.wait_group.sync.aligned %0;" :: "n"(N) : "memory"); }
template <int N> __device__ __forceinline__ void reg_fence(float (&d)[N]) {
#pragma unroll
  for (int i = 0; i < N; i++) asm volatile("" : "+f"(d[i]) :: "memory");
}
template <int N> __device__ __forceinline__ void reg_fence(uint32_t (&d)[N]) {
#pragma unroll
  for (int i = 0; i < N; i++) asm volatile("" : "+r"(d[i]) :: "memory");
}
__device__ __forceinline__ uint32_t fresh_tid() { uint32_t t; asm volatile("mov.u32 %0, %%tid.x;" : "=r"(t)); return t; }
__device__ __forceinline__ uint32_t lane_base16() {
  const uint32_t t = fresh_tid(), lane = t & 31, wq = (t >> 5) & 3;
  return (16 * wq + (lane & 7) + 8 * ((lane >> 3) & 1)) * 128 + (((lane >> 4) ^ (lane & 7)) << 4);
}
__device__ __forceinline__ void named_sync(int id, int n) { asm volatile("bar.sync %0, %1;" :: "r"(id), "r"(n) : "memory"); }
__device__ __forceinline__ void named_arrive(int id, int n) { asm volatile("bar.arrive %0, %1;" :: "r"(id), "r"(n) : "memory"); }
__device__ __forceinline__ uint32_t pack_bf16(float lo, float hi) {
  uint32_t r; asm("cvt.rn.bf16x2.f32 %0, %1, %2;" : "=r"(r) : "f"(hi), "f"(lo)); return r;
}
__device__ __forceinline__ float ex2(float x) { float y; asm("ex2.approx.ftz.f32 %0, %1;" : "=f"(y) : "f"(x)); return y; }
__device__ __forceinline__ void stsm4(uint32_t addr, uint32_t a, uint32_t b, uint32_t c, uint32_t d) {
  asm volatile("stmatrix.sync.aligned.m8n8.x4.shared.b16 [%0], {%1, %2, %3, %4};" :: "r"(addr), "r"(a), "r"(b), "r"(c), "r"(d) : "memory");
}
__device__ __forceinline__ void stsm4t(uint32_t addr, uint32_t a, uint32_t b, uint32_t c, uint32_t d) {
  asm volatile("stmatrix.sync.aligned.m8n8.x4.trans.shared.b16 [%0], {%1, %2, %3, %4};" :: "r"(addr), "r"(a), "r"(b), "r"(c), "r"(d) : "memory");
}
__device__ __forceinline__ uint64_t mk_desc(uint32_t addr, uint32_t lbo, uint32_t sbo) {
  return (uint64_t)(((addr & 0x3FFFF) >> 4) | ((lbo >> 4) << 16)) | ((uint64_t)((sbo >> 4) | (1u << 30)) << 32);
}
__device__ __forceinline__ uint64_t desc_k(uint32_t addr)  { return mk_desc(addr, 16, 1024); }
__device__ __forceinline__ uint64_t desc_mn(uint32_t addr) { return mk_desc(addr, 8192, 1024); }
__device__ __forceinline__ uint64_t desc_add(uint64_t d, uint32_t bytes) { return d + (bytes >> 4); }

__device__ __forceinline__ void wgmma_ss_n256_tb(float (&d)[128], uint64_t da, uint64_t db, int sd) {
  asm volatile("{\n.reg .pred p;\nsetp.ne.b32 p, %130, 0;\n"
    "wgmma.mma_async.sync.aligned.m64n256k16.f32.bf16.bf16 "
    "{%0, %1, %2, %3, %4, %5, %6, %7, %8, %9, %10, %11, %12, %13, %14, %15, "
    "%16, %17, %18, %19, %20, %21, %22, %23, %24, %25, %26, %27, %28, %29, %30, %31, "
    "%32, %33, %34, %35, %36, %37, %38, %39, %40, %41, %42, %43, %44, %45, %46, %47, "
    "%48, %49, %50, %51, %52, %53, %54, %55, %56, %57, %58, %59, %60, %61, %62, %63, "
    "%64, %65, %66, %67, %68, %69, %70, %71, %72, %73, %74, %75, %76, %77, %78, %79, "
    "%80, %81, %82, %83, %84, %85, %86, %87, %88, %89, %90, %91, %92, %93, %94, %95, "
    "%96, %97, %98, %99, %100, %101, %102, %103, %104, %105, %106, %107, %108, %109, %110, %111, "
    "%112, %113, %114, %115, %116, %117, %118, %119, %120, %121, %122, %123, %124, %125, %126, %127}, "
    "%128, %129, p, 1, 1, 0, 1;\n}"
    : "+f"(d[0]), "+f"(d[1]), "+f"(d[2]), "+f"(d[3]), "+f"(d[4]), "+f"(d[5]), "+f"(d[6]), "+f"(d[7]),
      "+f"(d[8]), "+f"(d[9]), "+f"(d[10]), "+f"(d[11]), "+f"(d[12]), "+f"(d[13]), "+f"(d[14]), "+f"(d[15]),
      "+f"(d[16]), "+f"(d[17]), "+f"(d[18]), "+f"(d[19]), "+f"(d[20]), "+f"(d[21]), "+f"(d[22]), "+f"(d[23]),
      "+f"(d[24]), "+f"(d[25]), "+f"(d[26]), "+f"(d[27]), "+f"(d[28]), "+f"(d[29]), "+f"(d[30]), "+f"(d[31]),
      "+f"(d[32]), "+f"(d[33]), "+f"(d[34]), "+f"(d[35]), "+f"(d[36]), "+f"(d[37]), "+f"(d[38]), "+f"(d[39]),
      "+f"(d[40]), "+f"(d[41]), "+f"(d[42]), "+f"(d[43]), "+f"(d[44]), "+f"(d[45]), "+f"(d[46]), "+f"(d[47]),
      "+f"(d[48]), "+f"(d[49]), "+f"(d[50]), "+f"(d[51]), "+f"(d[52]), "+f"(d[53]), "+f"(d[54]), "+f"(d[55]),
      "+f"(d[56]), "+f"(d[57]), "+f"(d[58]), "+f"(d[59]), "+f"(d[60]), "+f"(d[61]), "+f"(d[62]), "+f"(d[63]),
      "+f"(d[64]), "+f"(d[65]), "+f"(d[66]), "+f"(d[67]), "+f"(d[68]), "+f"(d[69]), "+f"(d[70]), "+f"(d[71]),
      "+f"(d[72]), "+f"(d[73]), "+f"(d[74]), "+f"(d[75]), "+f"(d[76]), "+f"(d[77]), "+f"(d[78]), "+f"(d[79]),
      "+f"(d[80]), "+f"(d[81]), "+f"(d[82]), "+f"(d[83]), "+f"(d[84]), "+f"(d[85]), "+f"(d[86]), "+f"(d[87]),
      "+f"(d[88]), "+f"(d[89]), "+f"(d[90]), "+f"(d[91]), "+f"(d[92]), "+f"(d[93]), "+f"(d[94]), "+f"(d[95]),
      "+f"(d[96]), "+f"(d[97]), "+f"(d[98]), "+f"(d[99]), "+f"(d[100]), "+f"(d[101]), "+f"(d[102]), "+f"(d[103]),
      "+f"(d[104]), "+f"(d[105]), "+f"(d[106]), "+f"(d[107]), "+f"(d[108]), "+f"(d[109]), "+f"(d[110]), "+f"(d[111]),
      "+f"(d[112]), "+f"(d[113]), "+f"(d[114]), "+f"(d[115]), "+f"(d[116]), "+f"(d[117]), "+f"(d[118]), "+f"(d[119]),
      "+f"(d[120]), "+f"(d[121]), "+f"(d[122]), "+f"(d[123]), "+f"(d[124]), "+f"(d[125]), "+f"(d[126]), "+f"(d[127])
    : "l"(da), "l"(db), "r"(sd));
}
__device__ __forceinline__ void wgmma_ss_n64(float (&d)[32], uint64_t da, uint64_t db, int sd) {
  asm volatile("{\n.reg .pred p;\nsetp.ne.b32 p, %34, 0;\n"
    "wgmma.mma_async.sync.aligned.m64n64k16.f32.bf16.bf16 "
    "{%0, %1, %2, %3, %4, %5, %6, %7, %8, %9, %10, %11, %12, %13, %14, %15, "
    "%16, %17, %18, %19, %20, %21, %22, %23, %24, %25, %26, %27, %28, %29, %30, %31}, "
    "%32, %33, p, 1, 1, 0, 0;\n}"
    : "+f"(d[0]), "+f"(d[1]), "+f"(d[2]), "+f"(d[3]), "+f"(d[4]), "+f"(d[5]), "+f"(d[6]), "+f"(d[7]),
      "+f"(d[8]), "+f"(d[9]), "+f"(d[10]), "+f"(d[11]), "+f"(d[12]), "+f"(d[13]), "+f"(d[14]), "+f"(d[15]),
      "+f"(d[16]), "+f"(d[17]), "+f"(d[18]), "+f"(d[19]), "+f"(d[20]), "+f"(d[21]), "+f"(d[22]), "+f"(d[23]),
      "+f"(d[24]), "+f"(d[25]), "+f"(d[26]), "+f"(d[27]), "+f"(d[28]), "+f"(d[29]), "+f"(d[30]), "+f"(d[31])
    : "l"(da), "l"(db), "r"(sd));
}
__device__ __forceinline__ void wgmma_rs_n256_tb(float (&d)[128], uint32_t a0, uint32_t a1, uint32_t a2, uint32_t a3, uint64_t db, int sd) {
  asm volatile("{\n.reg .pred p;\nsetp.ne.b32 p, %133, 0;\n"
    "wgmma.mma_async.sync.aligned.m64n256k16.f32.bf16.bf16 "
    "{%0, %1, %2, %3, %4, %5, %6, %7, %8, %9, %10, %11, %12, %13, %14, %15, "
    "%16, %17, %18, %19, %20, %21, %22, %23, %24, %25, %26, %27, %28, %29, %30, %31, "
    "%32, %33, %34, %35, %36, %37, %38, %39, %40, %41, %42, %43, %44, %45, %46, %47, "
    "%48, %49, %50, %51, %52, %53, %54, %55, %56, %57, %58, %59, %60, %61, %62, %63, "
    "%64, %65, %66, %67, %68, %69, %70, %71, %72, %73, %74, %75, %76, %77, %78, %79, "
    "%80, %81, %82, %83, %84, %85, %86, %87, %88, %89, %90, %91, %92, %93, %94, %95, "
    "%96, %97, %98, %99, %100, %101, %102, %103, %104, %105, %106, %107, %108, %109, %110, %111, "
    "%112, %113, %114, %115, %116, %117, %118, %119, %120, %121, %122, %123, %124, %125, %126, %127}, "
    "{%128, %129, %130, %131}, %132, p, 1, 1, 1;\n}"
    : "+f"(d[0]), "+f"(d[1]), "+f"(d[2]), "+f"(d[3]), "+f"(d[4]), "+f"(d[5]), "+f"(d[6]), "+f"(d[7]),
      "+f"(d[8]), "+f"(d[9]), "+f"(d[10]), "+f"(d[11]), "+f"(d[12]), "+f"(d[13]), "+f"(d[14]), "+f"(d[15]),
      "+f"(d[16]), "+f"(d[17]), "+f"(d[18]), "+f"(d[19]), "+f"(d[20]), "+f"(d[21]), "+f"(d[22]), "+f"(d[23]),
      "+f"(d[24]), "+f"(d[25]), "+f"(d[26]), "+f"(d[27]), "+f"(d[28]), "+f"(d[29]), "+f"(d[30]), "+f"(d[31]),
      "+f"(d[32]), "+f"(d[33]), "+f"(d[34]), "+f"(d[35]), "+f"(d[36]), "+f"(d[37]), "+f"(d[38]), "+f"(d[39]),
      "+f"(d[40]), "+f"(d[41]), "+f"(d[42]), "+f"(d[43]), "+f"(d[44]), "+f"(d[45]), "+f"(d[46]), "+f"(d[47]),
      "+f"(d[48]), "+f"(d[49]), "+f"(d[50]), "+f"(d[51]), "+f"(d[52]), "+f"(d[53]), "+f"(d[54]), "+f"(d[55]),
      "+f"(d[56]), "+f"(d[57]), "+f"(d[58]), "+f"(d[59]), "+f"(d[60]), "+f"(d[61]), "+f"(d[62]), "+f"(d[63]),
      "+f"(d[64]), "+f"(d[65]), "+f"(d[66]), "+f"(d[67]), "+f"(d[68]), "+f"(d[69]), "+f"(d[70]), "+f"(d[71]),
      "+f"(d[72]), "+f"(d[73]), "+f"(d[74]), "+f"(d[75]), "+f"(d[76]), "+f"(d[77]), "+f"(d[78]), "+f"(d[79]),
      "+f"(d[80]), "+f"(d[81]), "+f"(d[82]), "+f"(d[83]), "+f"(d[84]), "+f"(d[85]), "+f"(d[86]), "+f"(d[87]),
      "+f"(d[88]), "+f"(d[89]), "+f"(d[90]), "+f"(d[91]), "+f"(d[92]), "+f"(d[93]), "+f"(d[94]), "+f"(d[95]),
      "+f"(d[96]), "+f"(d[97]), "+f"(d[98]), "+f"(d[99]), "+f"(d[100]), "+f"(d[101]), "+f"(d[102]), "+f"(d[103]),
      "+f"(d[104]), "+f"(d[105]), "+f"(d[106]), "+f"(d[107]), "+f"(d[108]), "+f"(d[109]), "+f"(d[110]), "+f"(d[111]),
      "+f"(d[112]), "+f"(d[113]), "+f"(d[114]), "+f"(d[115]), "+f"(d[116]), "+f"(d[117]), "+f"(d[118]), "+f"(d[119]),
      "+f"(d[120]), "+f"(d[121]), "+f"(d[122]), "+f"(d[123]), "+f"(d[124]), "+f"(d[125]), "+f"(d[126]), "+f"(d[127])
    : "r"(a0), "r"(a1), "r"(a2), "r"(a3), "l"(db), "r"(sd));
}
__device__ __forceinline__ void wgmma_rs_n64_tb(float (&d)[32], uint32_t a0, uint32_t a1, uint32_t a2, uint32_t a3, uint64_t db, int sd) {
  asm volatile("{\n.reg .pred p;\nsetp.ne.b32 p, %37, 0;\n"
    "wgmma.mma_async.sync.aligned.m64n64k16.f32.bf16.bf16 "
    "{%0, %1, %2, %3, %4, %5, %6, %7, %8, %9, %10, %11, %12, %13, %14, %15, "
    "%16, %17, %18, %19, %20, %21, %22, %23, %24, %25, %26, %27, %28, %29, %30, %31}, "
    "{%32, %33, %34, %35}, %36, p, 1, 1, 1;\n}"
    : "+f"(d[0]), "+f"(d[1]), "+f"(d[2]), "+f"(d[3]), "+f"(d[4]), "+f"(d[5]), "+f"(d[6]), "+f"(d[7]),
      "+f"(d[8]), "+f"(d[9]), "+f"(d[10]), "+f"(d[11]), "+f"(d[12]), "+f"(d[13]), "+f"(d[14]), "+f"(d[15]),
      "+f"(d[16]), "+f"(d[17]), "+f"(d[18]), "+f"(d[19]), "+f"(d[20]), "+f"(d[21]), "+f"(d[22]), "+f"(d[23]),
      "+f"(d[24]), "+f"(d[25]), "+f"(d[26]), "+f"(d[27]), "+f"(d[28]), "+f"(d[29]), "+f"(d[30]), "+f"(d[31])
    : "r"(a0), "r"(a1), "r"(a2), "r"(a3), "l"(db), "r"(sd));
}
__device__ __forceinline__ void wgmma_rs_n64(float (&d)[32], uint32_t a0, uint32_t a1, uint32_t a2, uint32_t a3, uint64_t db, int sd) {
  asm volatile("{\n.reg .pred p;\nsetp.ne.b32 p, %37, 0;\n"
    "wgmma.mma_async.sync.aligned.m64n64k16.f32.bf16.bf16 "
    "{%0, %1, %2, %3, %4, %5, %6, %7, %8, %9, %10, %11, %12, %13, %14, %15, "
    "%16, %17, %18, %19, %20, %21, %22, %23, %24, %25, %26, %27, %28, %29, %30, %31}, "
    "{%32, %33, %34, %35}, %36, p, 1, 1, 0;\n}"
    : "+f"(d[0]), "+f"(d[1]), "+f"(d[2]), "+f"(d[3]), "+f"(d[4]), "+f"(d[5]), "+f"(d[6]), "+f"(d[7]),
      "+f"(d[8]), "+f"(d[9]), "+f"(d[10]), "+f"(d[11]), "+f"(d[12]), "+f"(d[13]), "+f"(d[14]), "+f"(d[15]),
      "+f"(d[16]), "+f"(d[17]), "+f"(d[18]), "+f"(d[19]), "+f"(d[20]), "+f"(d[21]), "+f"(d[22]), "+f"(d[23]),
      "+f"(d[24]), "+f"(d[25]), "+f"(d[26]), "+f"(d[27]), "+f"(d[28]), "+f"(d[29]), "+f"(d[30]), "+f"(d[31])
    : "r"(a0), "r"(a1), "r"(a2), "r"(a3), "l"(db), "r"(sd));
}

__device__ __forceinline__ uint4 lds16(uint32_t a) {
  uint4 v; asm volatile("ld.shared.v4.u32 {%0, %1, %2, %3}, [%4];" : "=r"(v.x), "=r"(v.y), "=r"(v.z), "=r"(v.w) : "r"(a) : "memory"); return v;
}
__device__ __forceinline__ void sts16(uint32_t a, uint32_t x, uint32_t y, uint32_t z, uint32_t w) {
  asm volatile("st.shared.v4.u32 [%0], {%1, %2, %3, %4};" :: "r"(a), "r"(x), "r"(y), "r"(z), "r"(w) : "memory");
}
__device__ __forceinline__ uint32_t lds4(uint32_t a) { uint32_t v; asm volatile("ld.shared.u32 %0, [%1];" : "=r"(v) : "r"(a) : "memory"); return v; }
__device__ __forceinline__ uint32_t lds4v(uint32_t a) { uint32_t v; asm volatile("ld.volatile.shared.u32 %0, [%1];" : "=r"(v) : "r"(a) : "memory"); return v; }
__device__ __forceinline__ uint32_t bmul(uint32_t a, uint32_t b) { uint32_t r; asm("mul.rn.bf16x2 %0, %1, %2;" : "=r"(r) : "r"(a), "r"(b)); return r; }
__device__ __forceinline__ uint32_t bfma(uint32_t a, uint32_t b, uint32_t c) { uint32_t r; asm("fma.rn.bf16x2 %0, %1, %2, %3;" : "=r"(r) : "r"(a), "r"(b), "r"(c)); return r; }
__device__ __forceinline__ uint32_t badd(uint32_t a, uint32_t b) { uint32_t r; asm("add.rn.bf16x2 %0, %1, %2;" : "=r"(r) : "r"(a), "r"(b)); return r; }

__device__ __forceinline__ void ldsm4(uint32_t (&r)[4], uint32_t a) {
  asm volatile("ldmatrix.sync.aligned.m8n8.x4.shared.b16 {%0, %1, %2, %3}, [%4];" : "=r"(r[0]), "=r"(r[1]), "=r"(r[2]), "=r"(r[3]) : "r"(a) : "memory");
}
__device__ __forceinline__ void ldsm4t(uint32_t (&r)[4], uint32_t a) {
  asm volatile("ldmatrix.sync.aligned.m8n8.x4.trans.shared.b16 {%0, %1, %2, %3}, [%4];" : "=r"(r[0]), "=r"(r[1]), "=r"(r[2]), "=r"(r[3]) : "r"(a) : "memory");
}
__device__ __forceinline__ uint32_t transpose8(uint32_t a) { uint32_t d; asm volatile("movmatrix.sync.aligned.m8n8.trans.b16 %0, %1;" : "=r"(d) : "r"(a)); return d; }

__device__ __forceinline__ void mma16816(float (&d)[4], const uint32_t (&a)[4], uint32_t b0, uint32_t b1) {
  asm volatile("mma.sync.aligned.m16n8k16.row.col.f32.bf16.bf16.f32 {%0, %1, %2, %3}, {%4, %5, %6, %7}, {%8, %9}, {%0, %1, %2, %3};"
               : "+f"(d[0]), "+f"(d[1]), "+f"(d[2]), "+f"(d[3]) : "r"(a[0]), "r"(a[1]), "r"(a[2]), "r"(a[3]), "r"(b0), "r"(b1));
}

#define STG_K1 2
#define STG_K2 10
#define STG_Q1 1
#define STG_Q2 5
#define PACE_A 400
#define PACE_B 100
#define PF_QA 48
#define PF_CV 64
#define PF_X 8
#define PF_WO 11
#define Q_PRE 2
#define ARRIVE_KK 12
#define SIDE_DELAY_NS 4000
#define HEAD_MAP 1
#define EARLY_LD 2
#define HI_ORDER 9
constexpr int PP_BAR = 3;
template <int V> struct Int { static constexpr int value = V; };
struct Ring {
  uint32_t slot, phase;
  __device__ __forceinline__ void next() { if (++slot == NSLOT) { slot = 0; phase ^= 1; } }
};
__device__ __forceinline__ uint32_t bar_addr(uint32_t sb, uint32_t i) { return sb + BARS + 8 * i; }
__device__ __forceinline__ uint32_t q_region(uint32_t sb, int w) { return sb + QREG + (w ^ 1) * 32768; }

struct Role { int h, j; };
__device__ __forceinline__ Role get_role() {
  int cta; asm volatile("mov.u32 %0, %%ctaid.x;" : "=r"(cta));
  const int c = cta >> 1;
  int h, u;
  const int a = c - 4, b = c - 36, q = (b * 37) >> 8;
  h = a < 0 ? 15 : b < 0 ? a & 7 : 8 + b - 7 * q;
  u = a < 0 ? c : b < 0 ? a >> 3 : q;
  return Role{h, 2 * u + (cta & 1)};
}
__device__ __forceinline__ int fresh_warp() { return __shfl_sync(0xffffffffu, fresh_tid() >> 5, 0); }

__device__ __forceinline__ int q_tile(int h, int j, int which) { return ((h < 8) == (which == 0)) ? 15 - j : j; }

__device__ __forceinline__ int o_chunk(int h, int c) { const int x = c + (h & 7); return x % 7; }

__device__ __forceinline__ int kv_block(int j, int t) { return j + 8 * ((HI_ORDER >> t) & 1); }
__device__ __forceinline__ uint8_t* kv_tile(const Params& p, int v, int h, int tile) { return p.kv + (size_t)((v * NH + h) * 32 + tile) * 32768; }

__device__ __forceinline__ void ring_acquire(uint32_t sb, Ring& r, uint32_t bytes) {
  mbar_wait(bar_addr(sb, B_RG_EMPTY + r.slot), r.phase ^ 1);
  mbar_expect_tx(bar_addr(sb, B_RG_FULL + r.slot), bytes);
}
__device__ __forceinline__ void producer_main(const Params& p, uint32_t sb) {
  const Role ro = get_role();
  const int h = ro.h, j = ro.j;
  TR_DECL;
  ST(11);
  for (int it = EARLY_LD; it < 71; it++) {
    const int t = it >> 4, k = it & 15, s = it & 3;
    mbar_wait(bar_addr(sb, B_P1_EMPTY + s), ((it >> 2) & 1) ^ 1);
    const uint32_t full = bar_addr(sb, B_P1_FULL + s), dst = sb + s * P1_STAGE;
    mbar_expect_tx(full, P1_STAGE);
    if ((it & 7) == 4) TRG(it);
    if (t < 4) {
      tma_ld2(dst, &p.ckv, full, k * 64, kv_block(j, t) * 128);
      tma_ld3(dst + 16384, (t >> 1) ? &p.wuv : &p.wuk, full, 0, k * 64, h * 4);
    } else {
      tma_ld2(dst, &p.x, full, k * 64, q_tile(h, j, 0) * 128);
      tma_ld3(dst + 16384, &p.wq, full, 0, k * 64, h * 4);
    }
    if (it >= PF_QA && it < PF_QA + 14) {
      const int i = it - PF_QA;
      bulk_prefetch(p.b_x + (size_t)(q_tile(h, j, 0) * 128 + (h & 7) * 16) * DM + i * 512, 1024);
      tma_pf2(&p.wqp, h * HD, (i * 8 + j) * 4);
    }
    if (it >= PF_CV && it < PF_CV + 3) {
      mbar_wait(bar_addr(sb, B_XS), 0);
      bulk_prefetch(g_xs + (size_t)(h * 8 + j) * CV_BYTES + (it - PF_CV) * (CV_BYTES / 3), CV_BYTES / 3);
    }
  }
  mbar_wait(bar_addr(sb, B_P1_EMPTY + 3), 0);
  mbar_wait(bar_addr(sb, B_XS), 0);
  mbar_expect_tx(bar_addr(sb, B_RG_FULL + 4), CV_BYTES);
  bulk_ld(sb + CV_X, g_xs + (size_t)(h * 8 + j) * CV_BYTES, CV_BYTES, bar_addr(sb, B_RG_FULL + 4));
  Ring r{0, 1};
  auto prefetch_wo = [&](int left) {
    const int i = PF_WO - left;
    if (PF_WO && i >= 0 && i < 8) bulk_prefetch(p.b_wo + (size_t)(h * HD + j * 32 + 4 * i) * DM, 4 * DM * 2);
  };
  mbar_wait(bar_addr(sb, B_KV), 0);
  for (int which = 0; which < 2; which++) {
    const int qt = q_tile(h, j, which);
    if (which == 1) {
      for (int kc = 0; kc < 7; kc++) {
        prefetch_wo(4 * qt + 4 + 7 - kc);
        ring_acquire(sb, r, 32768);
        tma_ld3(sb + r.slot * SLOT, &p.wq, bar_addr(sb, B_RG_FULL + r.slot), 0, kc * 64, h * 4);
        r.next();
        if (kc == 0 || (kc & 1)) {
          ring_acquire(sb, r, kc == 0 ? 16384 : 32768);
          const uint32_t full = bar_addr(sb, B_RG_FULL + r.slot), dst = sb + r.slot * SLOT;
          tma_ld2(dst, &p.x, full, kc * 64, qt * 128);
          if (kc > 0) tma_ld2(dst + 16384, &p.x, full, kc * 64 + 64, qt * 128);
          r.next();
        }
      }
    }
    const int n = 2 * qt + 2;
    for (int f = 0; f < 2 * n; f++) {
      if (which == 0) {
        const int i = f - max(2 * n - PF_X, 0);
        if (PF_X && i >= 0 && i < 4) bulk_prefetch(p.b_x + (size_t)((15 - qt) * 128 + (h & 7) * 16 + 4 * i) * DM, 4 * DM * 2);
      } else prefetch_wo(2 * n - f);
      const bool isK = (f == 0) || ((f & 1) && f < 2 * n - 1);
      const int i = isK ? (f + 1) >> 1 : (f == 2 * n - 1 ? n - 1 : (f >> 1) - 1);
      const int tile = which ? n - 1 - i : i;
      if (!isK) mbar_wait(bar_addr(sb, B_KV + 1 + ((tile >> 4) ^ ((HI_ORDER >> 2) & 1))), 0);
      if (which == 0 && f < 2) mbar_wait(bar_addr(sb, B_P1_EMPTY + f), 1);
      ring_acquire(sb, r, 32768);
      if (isK && (tile & 3) == 0) TRG(100 + 50 * which + tile);
      bulk_ld(sb + r.slot * SLOT, kv_tile(p, !isK, h, tile), 32768, bar_addr(sb, B_RG_FULL + r.slot));
      r.next();
    }
  }
  for (int i = 0; i < 14; i++) {
    ring_acquire(sb, r, 32768);
    if ((i & 3) == 0) TRG(200 + i);
    if (i == 13) TR_END();
    tma_ld2(sb + r.slot * SLOT, &p.wo, bar_addr(sb, B_RG_FULL + r.slot), o_chunk(h, i >> 1) * 64, ((i & 1) ? h ^ 8 : h) * HD);
    r.next();
  }
}

__device__ __forceinline__ void storer_main(const Params& p, uint32_t sb) {
  const Role ro = get_role();
  const int h = ro.h, j = ro.j, w = fresh_warp() - 1;
  const uint32_t full = bar_addr(sb, B_ST_FULL + w), empty = bar_addr(sb, B_ST_EMPTY + w);
  const int lane = threadIdx.x & 31;
  const unsigned epoch = load_epoch();
  if (lane == 0) {
    for (int job = 0; job < 8; job++) {
      const int t = job >> 1;
      uint8_t* dst = kv_tile(p, t >> 1, h, 2 * kv_block(j, t) + w) + (job & 1) * 16384;
      mbar_wait_nap(full, job & 1);
      for (int i = 0; i < 8; i++) {
        if (i) __nanosleep(job < 6 ? PACE_A : PACE_B);
        bulk_st(dst + i * 2048, sb + P1_STG + w * 16384 + i * 2048, 2048);
      }
      bulk_commit();
      bulk_wait_read();
      mbar_arrive(empty);
      if (job >= 3 && (job & 1)) { bulk_wait_all(); flag_signal(&g_flags.kv_ready[3 * h + t - 1].v); }
    }
  }
  __syncwarp();
  const int cta = h * 8 + j, qt = q_tile(h, j, 1);
  const uint32_t qreg = q_region(sb, w);
  {
    mbar_wait_nap(bar_addr(sb, B_CTXS + 4 * w), 0);
    uint4* z = reinterpret_cast<uint4*>(p.out + (size_t)(qt * 128 + w * 64 + (h & 7) * 8 + (lane >> 2)) * OUTW + DA) + (lane & 3);
#pragma unroll
    for (int i = 0; i < 14; i++) z[4 * i] = make_uint4(0, 0, 0, 0);
    __syncwarp();
    if (lane != 0) return;
    for (int b = 0; b < 4; b++) {
      mbar_wait(bar_addr(sb, B_CTXS + 4 * w + b), 0);
      bulk_st(p.ctx + (size_t)(cta * 2 + w) * 32768 + b * 8192, qreg + b * 8192, 8192);
      bulk_commit();
    }
    bulk_wait_read();
    mbar_arrive(empty);
    bulk_wait_all();
    flag_signal(&g_flags.ctx_ready[cta * 2 + w].v);
    flag_signal_after_bulk(&g_flags.out_ready[qt * 2 + w].v);
  }
  {
    const int wx = w ^ 1;
    flag_wait(&g_flags.ctx_ready[(cta ^ 64) * 2 + wx].v, 1, epoch);
    flag_wait(&g_flags.out_ready[qt * 2 + wx].v, 8, epoch);
    fence_async_all();
    mbar_wait_nap(bar_addr(sb, B_QFREE + w), 0);
    mbar_expect_tx(bar_addr(sb, B_CTXF + w), 32768);
    bulk_ld(qreg, p.ctx + (size_t)((cta ^ 64) * 2 + wx) * 32768, 32768, bar_addr(sb, B_CTXF + w));
    for (int ch = 0; ch < 7; ch++) {
      const int b = ch & 1;
      mbar_wait(bar_addr(sb, B_S2_FULL + w * 2 + b), (ch >> 1) & 1);
      tma_red2(&p.part, qreg + b * 8192, DA + o_chunk(h, ch) * 64, qt * 128 + wx * 64);
      bulk_commit();
      if (ch == 0 && w == 1) mbar_arrive(bar_addr(sb, B_GFREE));
      bulk_wait_read();
      mbar_arrive(bar_addr(sb, B_S2_EMPTY + w * 2 + b));
    }
    GT(48 + w);
    bulk_wait_all();
    GT(50 + w); GT(52 + w); GT(56);
    if (w == 0) { ST(12); STG_(13); }
  }
}

template <int OFF, int NB, int NREG>
__device__ __forceinline__ void store_blocks(uint32_t base, uint32_t lanebase, const uint32_t (&pk)[NREG]) {
#pragma unroll
  for (int J = 0; J < NB * 8; J += 2) {
    const uint32_t a = base + (J >> 3) * 8192 + (lanebase ^ ((J & 7) << 4));
    stsm4(a, pk[OFF + 2 * J], pk[OFF + 2 * J + 1], pk[OFF + 2 * J + 2], pk[OFF + 2 * J + 3]);
  }
}
__device__ __forceinline__ void warp_arrive(uint32_t bar, int lane) { __syncwarp(); if (lane == 0) mbar_arrive(bar); }
__device__ __forceinline__ void release(uint32_t bar, int lane) { lane0_arrive(bar, 1, lane); }

template <int W> __device__ __forceinline__ constexpr int cv_tile(int u) { return 2 * u + ((u ^ W) & 1); }
__device__ __forceinline__ uint32_t cv_x_lane(uint32_t lane) { return (16 + (lane & 15) - (lane >> 4)) * 16; }
__device__ __forceinline__ uint32_t cv_h_lane(uint32_t lane, uint32_t hE, uint32_t hO) {
  const uint32_t g = lane >> 2, c = lane & 3;
  return (g & 1) ? hO + (15 + 2 * c - g) * 2 : hE + (16 + 2 * c - g) * 2;
}
template <int W>
__device__ __forceinline__ void conv_mma(float (&ca)[8][4], uint32_t xa, uint32_t ha, uint32_t sb, uint32_t lb, const uint32_t (&pk)[64]) {
  constexpr int N = 16 - W;
  uint32_t fx[N][4], fh[N][2];
  auto ld_h = [&](int i, int rr) { fh[i][0] = lds4(ha + i * 256 + rr * 32); fh[i][1] = lds4(ha + i * 256 + rr * 32 + 16); };
  ldsm4(fx[0], xa);
#pragma unroll
  for (int u = 0; u < 8; u++) ld_h(cv_tile<W>(u), 0);
  ldsm4(fx[1], xa + 256);
#pragma unroll
  for (int u = 0; u < 8; u++) if (cv_tile<W ^ 1>(u) < N) ld_h(cv_tile<W ^ 1>(u), 0);
#pragma unroll
  for (int i = 2; i < N; i++) ldsm4(fx[i], xa + i * 256);
#pragma unroll
  for (int sx = 0; sx < N; sx++) {
#pragma unroll
    for (int u = 0; u < 8; u++) {
      const int jj = cv_tile<W>(u) - sx;
      if (jj >= 0) mma16816(ca[u], fx[sx], fh[jj < 0 ? 0 : jj][0], fh[jj < 0 ? 0 : jj][1]);
    }
    ldsm4(fx[sx], xa + sx * 256 - 32);
    ld_h(N - 1 - sx, 1);
  }
  mbar_wait(bar_addr(sb, B_P1_EMPTY + 2), 1);
  if (W == 0) { mbar_wait(bar_addr(sb, B_ST_EMPTY), 1); mbar_wait(bar_addr(sb, B_ST_EMPTY + 1), 1); }
#pragma unroll
  for (int jj = 15; jj >= 0; jj--) {
    stsm4(q_region(sb, W) + (jj >> 2) * 8192 + (lb ^ ((jj & 3) << 5)), pk[4 * jj], pk[4 * jj + 1], pk[4 * jj + 2], pk[4 * jj + 3]);
#pragma unroll
    for (int u = 0; u < 8; u++) {
      const int sx = cv_tile<W>(u) - jj;
      if (sx >= 0) mma16816(ca[u], fx[sx < 0 ? 0 : sx], fh[jj < N ? jj : 0][0], fh[jj < N ? jj : 0][1]);
    }
  }
}

__device__ __forceinline__ void consumer_main(const Params& p, uint32_t sb, uint8_t* xs_base, uint32_t one) {
  const int lane = fresh_tid() & 31, w = (fresh_warp() >> 2) - 1;
  const uint32_t lb = lane_base16();
  int qt, cc;
  { const Role ro = get_role(); qt = q_tile(ro.h, ro.j, 0); cc = ro.h * 8 + ro.j; }
  const uint32_t st_full = bar_addr(sb, B_ST_FULL + w), st_empty = bar_addr(sb, B_ST_EMPTY + w);
  const uint32_t stg = sb + P1_STG + w * 16384;

  auto turn_begin = [&]() { named_sync(PP_BAR + w, 256); };
  auto turn_end = [&]() { named_arrive(PP_BAR + (w ^ 1), 256); };
  float acc[128];
#pragma unroll
  for (int i = 0; i < 128; i++) acc[i] = 0.f;
  uint32_t pk[64];
#pragma unroll
  for (int i = 0; i < 64; i++) pk[i] = 0;
  if (fresh_warp() != 4) named_sync(0, NTHREADS);
  PDECL;
  TR_DECL;
  TR(0);
  TSG(0); TS(1);
  const uint32_t qreg = q_region(sb, w);
  for (int t = 0; t < 5; t++) {
    const int nk = t < 4 ? 16 : 7;
#pragma unroll 1
    for (int k = 0; k < nk; k++) {
      const int it = t * 16 + k, s = k & 3;
      if (it == 0 && threadIdx.x == 256) ST(6);
      mbar_wait(bar_addr(sb, B_P1_FULL + s), (it >> 2) & 1);
      if (it < 3 && threadIdx.x == 256) ST(7 + it);
      TR(1);
      const uint64_t da = desc_k(sb + s * P1_STAGE + w * 8192), db = desc_mn(sb + s * P1_STAGE + 16384);
      turn_begin();
      wg_fence();
#pragma unroll
      for (int kk = 0; kk < 4; kk++) wgmma_ss_n256_tb(acc, desc_add(da, kk * 32), desc_add(db, kk * 2048), (k | kk) != 0);
      wg_commit();
      turn_end();
      TR(3);
      wg_wait<1>();
      if (k > 0) release(bar_addr(sb, B_P1_EMPTY + ((k - 1) & 3)), lane);
      const int k1 = t < 4 ? STG_K1 : STG_Q1, k2 = t < 4 ? STG_K2 : STG_Q2;
      if (t > 0 && (k == k1 || k == k2)) {
        const int job = 2 * (t - 1) + (k != k1);
        if (job > 0) mbar_wait(st_empty, (job - 1) & 1);
        if (k == k1) store_blocks<0, 2>(stg, lb, pk); else store_blocks<32, 2>(stg, lb, pk);
      }
      if (t > 0 && (k == k1 + 1 || k == k2 + 1)) { fence_async_smem(); warp_arrive(st_full, lane); }
      TR(5);
    }
    wg_wait<0>();
    TR(6);
    reg_fence(acc);
    release(bar_addr(sb, B_P1_EMPTY + ((nk - 1) & 3)), lane);
#pragma unroll
    for (int i = 0; i < 64; i++) pk[i] = pack_bf16(acc[2 * i], acc[2 * i + 1]);
    TS(t < 4 ? 2 + t : 60);
  }
  TS(6);
  {
    const uint32_t wq = lb >> 11, ln = lane, cx = sb + CV_X;
    float ca[8][4];
#pragma unroll
    for (int i = 0; i < 8; i++) { ca[i][0] = 0.f; ca[i][1] = 0.f; ca[i][2] = 0.f; ca[i][3] = 0.f; }
    const uint32_t xa = cx + cv_x_lane(ln) - wq * 64, ha = cv_h_lane(ln, cx + CV_HE, cx + CV_HE + CV_HCOPY) + wq * 64;
    mbar_wait(bar_addr(sb, B_RG_FULL + 4), 0);
    TR(7); TS(19); TS(20);
    if (w) conv_mma<1>(ca, xa, ha, sb, lb, pk); else conv_mma<0>(ca, xa, ha, sb, lb, pk);
    TR(8); TS(21);
    const uint32_t ex = sb + CV_R + w * 16384 + ln * 16;
#pragma unroll
    for (int u = 0; u < 8; u++)
      sts16(ex + (wq * 8 + u) * 512, __float_as_uint(ca[u][0]), __float_as_uint(ca[u][1]), __float_as_uint(ca[u][2]), __float_as_uint(ca[u][3]));
  }
  auto conv_finish = [&]() {
    const uint32_t wq = lb >> 11, cx = sb + CV_X, ex = sb + CV_R + w * 16384 + lane * 16;
    uint8_t* gz = xs_base + (size_t)cc * CV_BYTES;
    const uint32_t Dd = lds4(cx + CV_D);
    uint32_t z[2][2];
#pragma unroll
    for (int e = 0; e < 2; e++) {
      const uint32_t u = 2 * wq + e, nt = 2 * u + ((e ^ w) & 1);
      float y[4] = {0.f, 0.f, 0.f, 0.f};
#pragma unroll
      for (int v = 0; v < 4; v++) {
        const uint4 t = lds16(ex + (v * 8 + u) * 512);
        y[0] += __uint_as_float(t.x); y[1] += __uint_as_float(t.y); y[2] += __uint_as_float(t.z); y[3] += __uint_as_float(t.w);
      }
      const uint32_t o = (16 + 16 * nt) * 16 + lane * 4;
      *reinterpret_cast<uint32_t*>(gz + o)       = badd(pack_bf16(y[0], y[1]), bmul(lds4(cx + o), Dd));
      *reinterpret_cast<uint32_t*>(gz + o + 128) = badd(pack_bf16(y[2], y[3]), bmul(lds4(cx + o + 128), Dd));
    }
    __syncwarp();
    release(bar_addr(sb, B_RG_EMPTY + 3), lane);
    release(bar_addr(sb, B_RG_EMPTY + 4), lane);
    if (lane == 0) mbar_arrive(bar_addr(sb, B_CONV));
  };
  TS(15);
  TR(10);
  Ring r{0, 1};
  auto take = [&]() { const uint32_t sl = r.slot; mbar_wait(bar_addr(sb, B_RG_FULL + sl), r.phase); r.next(); return sl; };
  constexpr float SC = 0.0625f * 1.4426950408889634f;
  uint32_t ws;
#pragma unroll 1
  for (int which = 0;; which++) {
    float s[32];
#pragma unroll
    for (int i = 0; i < 32; i++) s[i] = 0.f;
    uint32_t pa[16];
    float b0, b1, l0, l1;
    const uint64_t dq = desc_k(qreg);
    uint64_t dk = 0, dqq = 0, dv = 0;
    auto prep_qk = [&](uint32_t kaddr) { dk = desc_k(kaddr); dqq = dq + (kaddr >> 31); asm volatile("" : "+l"(dk), "+l"(dqq)); };
    auto prep_pv = [&](uint32_t vaddr) { dv = desc_mn(vaddr); asm volatile("" : "+l"(dv)); };
    auto issue_qk = [&]() {
#pragma unroll
      for (int kk = 0; kk < 16; kk++)
        wgmma_ss_n64(s, desc_add(dqq, (kk >> 2) * 8192 + (kk & 3) * 32), desc_add(dk, (kk >> 2) * 8192 + (kk & 3) * 32), kk != 0);
    };
    auto issue_pv = [&](int accumulate) {
#pragma unroll
      for (int kk = 0; kk < 4; kk++)
        wgmma_rs_n256_tb(acc, pa[4 * kk], pa[4 * kk + 1], pa[4 * kk + 2], pa[4 * kk + 3], desc_add(dv, kk * 2048), accumulate | kk);
    };
    auto mask_diag = [&]() {
      const int d = (int)((lb >> 11) << 4) + (lane >> 2) - 2 * (lane & 3);
#pragma unroll
      for (int jj = 0; jj < 8; jj++) {
        if (8 * jj > d)     s[4 * jj]     = -INFINITY;
        if (8 * jj + 1 > d) s[4 * jj + 1] = -INFINITY;
        if (8 * jj - 8 > d) s[4 * jj + 2] = -INFINITY;
        if (8 * jj - 7 > d) s[4 * jj + 3] = -INFINITY;
      }
    };
    auto row_max = [&](float& x0, float& x1) {
      x0 = fmaxf(s[0], s[1]); x1 = fmaxf(s[2], s[3]);
#pragma unroll
      for (int jj = 1; jj < 8; jj++) {
        x0 = fmaxf(x0, fmaxf(s[4 * jj], s[4 * jj + 1]));
        x1 = fmaxf(x1, fmaxf(s[4 * jj + 2], s[4 * jj + 3]));
      }
      x0 = fmaxf(x0, __shfl_xor_sync(0xffffffffu, x0, 1));
      x1 = fmaxf(x1, __shfl_xor_sync(0xffffffffu, x1, 1));
      x0 = fmaxf(x0, __shfl_xor_sync(0xffffffffu, x0, 2));
      x1 = fmaxf(x1, __shfl_xor_sync(0xffffffffu, x1, 2));
    };
    auto exps = [&](uint32_t (&pp)[16], float& r0, float& r1) {
      float t0, t1, t2, t3;
#pragma unroll
      for (int jj = 0; jj < 8; jj++) {
        const float e0 = ex2(fmaf(s[4 * jj], SC, b0)), e1 = ex2(fmaf(s[4 * jj + 1], SC, b0));
        const float e2 = ex2(fmaf(s[4 * jj + 2], SC, b1)), e3 = ex2(fmaf(s[4 * jj + 3], SC, b1));
        if (jj == 0) { t0 = e0; t1 = e1; t2 = e2; t3 = e3; } else { t0 += e0; t1 += e1; t2 += e2; t3 += e3; }
        pp[2 * jj] = pack_bf16(e0, e1); pp[2 * jj + 1] = pack_bf16(e2, e3);
      }
      r0 = t0 + t1; r1 = t2 + t3;
    };

    const bool up = w == which;
    const int n = 2 * qt + 2, nw = n - up;
    int fd = which ? 0 : 2 * n - 1;
    const int dir = which ? 1 : -1;
    auto skip = [&]() { r.next(); fd += dir; };
    auto give = [&](uint32_t sl, int d) {
      lane0_arrive(bar_addr(sb, B_RG_EMPTY + sl), (d & ~2) == 0 ? 2 : 1, lane);
    };
    if (which && up) skip();
    uint32_t ks = take();
    TS(62 + which);
    TR(20);
    prep_qk(sb + ks * SLOT);
    turn_begin();
    wg_fence();
#pragma unroll
    for (int kk = 0; kk < 16; kk++)
      wgmma_rs_n64(s, pk[4 * kk], pk[4 * kk + 1], pk[4 * kk + 2], pk[4 * kk + 3], desc_add(dk, (kk >> 2) * 8192 + (kk & 3) * 32), kk != 0);
    wg_commit();
    turn_end();
    TR(21);
    if (!which) conv_finish();
    TR(23);
    if (which) mbar_wait(st_empty, 0);
    if (which && !up) store_blocks<0, Q_PRE>(qreg, lb, pk);
    TR(24);
    wg_wait<0>();
    TR(22);
    reg_fence(s);
    reg_fence(pk);
    give(ks, fd);
    fd += dir;
    if (which && up) { skip(); store_blocks<0, 4>(qreg, lb, pk); }
    if (which || nw == 1) mask_diag();
    row_max(b0, b1);
    if (which && !up) store_blocks<16 * Q_PRE, 4 - Q_PRE>(qreg + Q_PRE * 8192, lb, pk);
    b0 *= -SC; b1 *= -SC;
#pragma unroll
    for (int i = 0; i < 128; i++) acc[i] = 0.f;
    exps(pa, l0, l1);
    if (which && nw == 1) { fence_async_smem(); warp_arrive(bar_addr(sb, B_QFREE + w), lane); }
#pragma unroll 1
    for (int jj = 1; jj < nw; jj++) {
      ks = take();
      const uint32_t vs = take();
      if (jj == 1) fence_async_smem();
      TR(30);
#pragma unroll
      for (int i = 0; i < 32; i++) s[i] = 0.f;
      prep_qk(sb + ks * SLOT);
      prep_pv(sb + vs * SLOT);
      turn_begin();
      wg_fence();
      issue_qk();
      wg_commit();
      issue_pv(1);
      wg_commit();
      turn_end();
      TR(31);
      wg_wait<1>();
      TR(32);
      reg_fence(s);
      give(ks, fd);
      if (jj == nw - 1) {
        if (!which) mask_diag();
        else if (lane == 0) mbar_arrive(bar_addr(sb, B_QFREE + w));
      }
      uint32_t pn[16];
      float t0, t1, a0 = 1.f, a1 = 1.f;
      exps(pn, t0, t1);
      const bool redo = __any_sync(0xffffffffu, !(t0 + t1 <= 65536.f));
      if (redo) {
        row_max(a0, a1);
        const float c0 = fminf(b0, -SC * a0), c1 = fminf(b1, -SC * a1);
        a0 = ex2(c0 - b0); a1 = ex2(c1 - b1);
        b0 = c0; b1 = c1;
        l0 *= a0; l1 *= a1;
        exps(pn, t0, t1);
      }
      l0 += t0; l1 += t1;
      wg_wait<0>();
      reg_fence(acc);
      reg_fence(pa);
      give(vs, fd + dir);
      fd += 2 * dir;
      if (redo) {
#pragma unroll
        for (int i = 0; i < 32; i++) { acc[4 * i] *= a0; acc[4 * i + 1] *= a0; acc[4 * i + 2] *= a1; acc[4 * i + 3] *= a1; }
      }
#pragma unroll
      for (int i = 0; i < 16; i++) pa[i] = (i & 1) ? pn[i] ^ (one - 1) : pn[i] * one;
    }
    if (!which && up) skip();
    const uint32_t vs = take();
    TR(40);
    prep_pv(sb + vs * SLOT);
    turn_begin();
    wg_fence();
    issue_pv(1);
    wg_commit();
    turn_end();
    TR(41);
    if (!which && up) r.next();
    ws = take();
    l0 += __shfl_xor_sync(0xffffffffu, l0, 1); l1 += __shfl_xor_sync(0xffffffffu, l1, 1);
    l0 += __shfl_xor_sync(0xffffffffu, l0, 2); l1 += __shfl_xor_sync(0xffffffffu, l1, 2);
    float i0, i1;
    asm volatile("rcp.approx.ftz.f32 %0, %1;" : "=f"(i0) : "f"(l0));
    asm volatile("rcp.approx.ftz.f32 %0, %1;" : "=f"(i1) : "f"(l1));
    uint32_t xs = 0;
    if (!which) xs = take();
    wg_wait<0>();
    TR(42);
    reg_fence(acc);
    reg_fence(pa);
    give(vs, fd);
    TS(7 + 3 * which);
#pragma unroll
    for (int i = 0; i < 32; i++) {
      pk[2 * i]     = pack_bf16(acc[4 * i] * i0, acc[4 * i + 1] * i0);
      pk[2 * i + 1] = pack_bf16(acc[4 * i + 2] * i1, acc[4 * i + 3] * i1);
    }
    TS(8 + 3 * which); TR(46);
    if (which) break;
    TS(31);
    uint32_t xaddr = sb + xs * SLOT + (w ^ 1) * 8192;
#pragma unroll 1
    for (int kc = 0;; kc++) {
      TR(11);
      const uint64_t da = desc_k(xaddr), db = desc_mn(sb + ws * SLOT);
      turn_begin();
      wg_fence();
#pragma unroll
      for (int kk = 0; kk < 4; kk++) wgmma_ss_n256_tb(acc, desc_add(da, kk * 32), desc_add(db, kk * 2048), (kc | kk) != 0);
      wg_commit();
      turn_end();
      TR(13);
      const int cb = kc;
      if (cb >= 1 && cb <= 4) { fence_async_smem(); warp_arrive(bar_addr(sb, B_CTXS + 4 * w + cb - 1), lane); }
      if ((unsigned)cb < 4) {
        if (cb & 2) { if (cb & 1) store_blocks<48, 1>(qreg + 24576, lb, pk); else store_blocks<32, 1>(qreg + 16384, lb, pk); }
        else        { if (cb & 1) store_blocks<16, 1>(qreg + 8192, lb, pk);  else store_blocks<0, 1>(qreg, lb, pk); }
      }
      TR(15);
      wg_wait<0>();
      release(bar_addr(sb, B_RG_EMPTY + ws), lane);
      if (!(kc & 1)) release(bar_addr(sb, B_RG_EMPTY + xs), lane);
      if (kc == 6) break;
      ws = take();
      if (!(kc & 1)) { xs = take(); xaddr = sb + xs * SLOT + (w ^ 1) * 8192; } else xaddr += 16384;
    }
    reg_fence(acc);
    TS(61); TR(16);
#pragma unroll
    for (int i = 0; i < 64; i++) pk[i] = pack_bf16(acc[2 * i], acc[2 * i + 1]);
    TS(9); TR(19);
    qt = 15 - qt;
  }

  {
    float oa[32], ob[32];
#pragma unroll
    for (int i = 0; i < 32; i++) { oa[i] = 0.f; ob[i] = 0.f; }
    auto stage_o = [&](float (&o)[32], int ch) {
      reg_fence(o);
      uint32_t q[16];
#pragma unroll
      for (int i = 0; i < 16; i++) q[i] = pack_bf16(o[2 * i], o[2 * i + 1]);
      if (ch >= 2) mbar_wait(bar_addr(sb, B_S2_EMPTY + w * 2 + (ch & 1)), ((ch >> 1) - 1) & 1);
      store_blocks<0, 1>(qreg + (ch & 1) * 8192, lb, q);
    };
    auto hand_over = [&](int ch) {
      fence_async_smem();
      warp_arrive(bar_addr(sb, B_S2_FULL + w * 2 + (ch & 1)), lane);
    };
    uint32_t pk2[64];
    uint32_t p2 = 0;
    auto chunk = [&](int ch, auto first, float (&o)[32], float (&oprev)[32]) {
      constexpr bool FIRST = decltype(first)::value;
      const uint32_t s1 = FIRST ? ws : take();
      TR(50);
      const uint64_t d1 = desc_mn(sb + s1 * SLOT);
      turn_begin();
      wg_fence();
#pragma unroll
      for (int kk = 0; kk < 16; kk++) {
        wgmma_rs_n64_tb(o, pk[4 * kk], pk[4 * kk + 1], pk[4 * kk + 2], pk[4 * kk + 3], desc_add(d1, kk * 2048), kk != 0);
        if (kk == ARRIVE_KK) turn_end();
      }
      wg_commit();
      TR(51);
      if constexpr (!FIRST) {
        wg_wait<1>();
        release(bar_addr(sb, B_RG_EMPTY + p2), lane);
        stage_o(oprev, ch - 1);
      } else {
        mbar_wait(bar_addr(sb, B_CTXF + w), 0);
#pragma unroll
        for (int kk = 0; kk < 16; kk++) {
          uint32_t f[4];
          ldsm4(f, qreg + (kk >> 2) * 8192 + (lb ^ ((kk & 3) << 5)));
          pk2[4 * kk] = f[0]; pk2[4 * kk + 1] = f[1]; pk2[4 * kk + 2] = f[2]; pk2[4 * kk + 3] = f[3];
        }
      }
      const uint32_t s2 = take();
      TR(53);
      const uint64_t d2 = desc_mn(sb + s2 * SLOT);
      turn_begin();
      wg_fence();
#pragma unroll
      for (int kk = 0; kk < 16; kk++) {
        wgmma_rs_n64_tb(o, pk2[4 * kk], pk2[4 * kk + 1], pk2[4 * kk + 2], pk2[4 * kk + 3], desc_add(d2, kk * 2048), 1);
        if (kk == ARRIVE_KK && (ch < 6 || w == 1)) turn_end();
      }
      wg_commit();
      TR(54);
      if (!FIRST) hand_over(ch - 1);
      wg_wait<1>();
      TR(55);
      release(bar_addr(sb, B_RG_EMPTY + s1), lane);
      p2 = s2;
    };
    chunk(0, Int<1>(), oa, ob);
#pragma unroll 1
    for (int ch = 1; ch < 7; ch += 2) { chunk(ch, Int<0>(), ob, oa); chunk(ch + 1, Int<0>(), oa, ob); }
    wg_wait<0>();
    TR(58);
    reg_fence(pk);
    reg_fence(pk2);
    stage_o(oa, 6);
    hand_over(6);
  }
  TS(12); TR(59);
  if (threadIdx.x == 128) ST(14);
  if ((threadIdx.x & 127) == 0) GT(54 + w);

  TS(16); TS(18); TS(17);
  TR(99); TR_END();
  TS(13); TSG(14);
}

#define CONV_STAGGER_NS 1200
namespace ssm {
#define CONV_GROUPS (D_SPARE / 8 / NCONV)
constexpr int GROUPS = CONV_GROUPS;
constexpr uint32_t ZROWS = 16;
constexpr uint32_t CHAN = (ZROWS + 256 + 1) * 16;
constexpr uint32_t XBUF = 8 * CHAN;
constexpr uint32_t OFF_X = 0;
constexpr uint32_t HCOPY = 4160;
constexpr uint32_t OFF_H = 2 * XBUF;
constexpr uint32_t HWARP = 3 * HCOPY;
constexpr uint32_t IO_K = 128, IO_V = IO_K + 4096, IO_Q = IO_V + 4096, IOBUF = IO_Q + 4096;
constexpr uint32_t OFF_IO = (OFF_H + 8 * HWARP + 127) / 128 * 128;
constexpr uint32_t END = OFF_IO + 4 * IOBUF;
static_assert(IOBUF % 128 == 0 && OFF_H % 16 == 0, "TMA destination alignment");
static_assert(END <= BARS, "smem");
enum : uint32_t { B_XREADY = 0, B_ZDONE = 2, B_KV = 4, B_Q = 8, B_HRAW = 12, B_QLAST = 20 };
constexpr int CW_BAR = 4;

__device__ __forceinline__ int group_d0(int cidx, int grp) { return (grp * NCONV + cidx) * 8; }
__device__ __forceinline__ uint32_t x_lane(int lane) { return (lane & 7) * CHAN + (ZROWS + (lane >> 3)) * 16; }
__device__ __forceinline__ uint32_t t_lane(int lane) { return (uint32_t)(8 * (lane >> 3) + 7 - (lane & 7)) * 16; }
struct Taps { uint32_t s[4]; };
__device__ __forceinline__ Taps load_taps(const Params& p, int d0, int c) {
  const uint2 s0 = __ldg(reinterpret_cast<const uint2*>(p.a_shift + (d0 + 2 * c) * 4)), s1 = __ldg(reinterpret_cast<const uint2*>(p.a_shift + (d0 + 2 * c + 1) * 4));
  return Taps{{__byte_perm(s0.x, s1.x, 0x5410), __byte_perm(s0.x, s1.x, 0x7632), __byte_perm(s0.y, s1.y, 0x5410), __byte_perm(s0.y, s1.y, 0x7632)}};
}
__device__ __forceinline__ uint32_t short_conv(const Taps& t, uint32_t k0, uint32_t k1, uint32_t k2, uint32_t k3, uint32_t v) {
  return bmul(bfma(k3, t.s[0], bfma(k2, t.s[1], bfma(k1, t.s[2], bmul(k0, t.s[3])))), v);
}
__device__ __forceinline__ void gate_chunk(uint32_t xa, uint32_t qa) {
#pragma unroll 4
  for (int i = 0; i < 8; i++) {
    uint32_t zz[4], qq[4];
    ldsm4t(zz, xa + i * 64);
    ldsm4(qq, qa + i * 512);
    stsm4(qa + i * 512, bmul(qq[0], zz[0]), bmul(qq[1], zz[1]), bmul(qq[2], zz[2]), bmul(qq[3], zz[3]));
  }
}

__device__ __forceinline__ void io_warp(const Params& p, uint32_t sb, int cidx, int wq) {
  const int lane = threadIdx.x & 31;
  const uint32_t io = sb + OFF_IO + wq * IOBUF, bkv = bar_addr(sb, B_KV + wq), bq = bar_addr(sb, B_Q + wq);
  auto load_kv = [&](int e) {
    __syncwarp();
    if (lane != 0) return;
    const int d0 = group_d0(cidx, e >> 1), row = (2 * wq + (e & 1)) * 256;
    if (e < 2 * GROUPS) {
      mbar_expect_tx(bkv, IO_Q);
      tma_ld2(io, &p.ak8, bkv, d0, row - 8);
      tma_ld2(io + IO_K, &p.ak, bkv, d0, row);
      tma_ld2(io + IO_V, &p.av, bkv, d0, row);
    } else {
      const uint32_t bar = bar_addr(sb, B_QLAST + 2 * wq + 1);
      mbar_expect_tx(bar, 4096);
      tma_ld2(io + IO_K, &p.aq, bar, group_d0(cidx, GROUPS - 1), row + 256);
    }
  };
  auto load_q = [&](int e) {
    __syncwarp();
    if (lane != 0) return;
    const uint32_t bar = e < 2 * GROUPS - 2 ? bq : bar_addr(sb, B_QLAST + 2 * wq);
    mbar_expect_tx(bar, 4096);
    tma_ld2(io + IO_Q, &p.aq, bar, group_d0(cidx, e >> 1), (2 * wq + (e & 1)) * 256);
  };
  TR_DECL;
  TR(0);
  load_kv(0);
  const uint32_t xl = sb + OFF_X + x_lane(lane) + wq * 1024, tl = io + t_lane(lane);
#pragma unroll 1
  for (int grp = -2; grp + 1 < GROUPS; grp++) {
    const bool more = grp + 2 < GROUPS;
    const Taps taps = load_taps(p, group_d0(cidx, more ? grp + 2 : 0), lane & 3);
    PCLK(c0);
    if (grp >= 0) mbar_wait_nap(bar_addr(sb, B_ZDONE + (grp & 1)), (grp >> 1) & 1);
    PACC(tp, c0);
    PCLK(c1);
    TR(80);
#pragma unroll 1
    for (int i = 0; i < 2; i++) {
      const uint32_t xa = xl + (grp & 1) * XBUF + i * 512;
      if (grp >= 0) {
        mbar_wait_nap(bq, i);
        TR(81);
        gate_chunk(xa, tl + IO_Q);
      }
      if (more) {
        TR(82);
        mbar_wait_nap(bkv, i);
        TR(83);
#pragma unroll 2
        for (int u = 0; u < 8; u++) {
          const uint32_t ka = tl + IO_K + u * 512;
          uint32_t k0[4], k1[4], k2[4], k3[4], vv[4];
          ldsm4(k0, ka - 48); ldsm4(k1, ka - 32); ldsm4(k2, ka - 16); ldsm4(k3, ka); ldsm4(vv, ka + 4096);
          stsm4t(xa + u * 64, short_conv(taps, k0[0], k1[0], k2[0], k3[0], vv[0]), short_conv(taps, k0[1], k1[1], k2[1], k3[1], vv[1]),
                 short_conv(taps, k0[2], k1[2], k2[2], k3[2], vv[2]), short_conv(taps, k0[3], k1[3], k2[3], k3[3], vv[3]));
        }
        load_kv(2 * (grp + 2) + i + 1);
        TR(84);
        if (i == 1) warp_arrive(bar_addr(sb, B_XREADY + (grp & 1)), lane);
      }
      if (grp >= 0) {
        fence_async_smem();
        __syncwarp();
        if (lane == 0) {
          tma_st2(&p.ao, io + IO_Q, group_d0(cidx, grp), (2 * wq + i) * 256);
          bulk_commit();
          bulk_wait_read();
        }
      }
      if (2 * grp + i + 1 >= 0) load_q(2 * grp + i + 1);
      TR(85);
    }
    PACC(te, c1);
  }
  if (lane == 0) bulk_wait_all();
  TR(99); TR_END();
}

__device__ __forceinline__ void conv_warp(const Params& p, uint32_t sb, int cidx, int ch) {
  const int lane = threadIdx.x & 31;
  const uint32_t hE0 = sb + OFF_H + ch * HWARP, hO = hE0 + HCOPY;
  const uint32_t hbar = bar_addr(sb, B_HRAW + ch);
  auto fetch_h = [&](int grp) {
    if (lane == 0) {
      mbar_expect_tx(hbar, 4096);
      asm volatile("cp.async.bulk.shared::cluster.global.mbarrier::complete_tx::bytes [%0], [%1], %2, [%3];"
                   :: "r"(hE0 + (grp & 1) * 2 * HCOPY + 32), "l"(p.a_ssmk + (size_t)(group_d0(cidx, grp) + ch) * SEQ), "r"(4096), "r"(hbar) : "memory");
    }
  };
  TR_DECL;
  TR(0);
  fetch_h(0);
#pragma unroll 1
  for (int grp = 0; grp < GROUPS; grp++) {
    const uint32_t xc = sb + OFF_X + (grp & 1) * XBUF + ch * CHAN;
    const uint32_t Dd = (uint32_t)__ldg(reinterpret_cast<const unsigned short*>(p.a_D + group_d0(cidx, grp) + ch)) * 0x10001u;
    PCLK(k0);
    mbar_wait(hbar, grp & 1);
    const uint32_t hE = hE0 + (grp & 1) * 2 * HCOPY;
    if (grp + 1 < GROUPS) fetch_h(grp + 1);
#pragma unroll
    for (int i = 0; i < 8; i++) {
      const uint32_t o = 32 + (i * 32 + lane) * 16;
      const uint4 w = lds16(hE + o);
      const uint32_t nx = lds4(hE + o + 16);
      sts16(hO + o, __byte_perm(w.x, w.y, 0x5432), __byte_perm(w.y, w.z, 0x5432), __byte_perm(w.z, w.w, 0x5432), __byte_perm(w.w, nx, 0x5432));
      if (o == 32) asm volatile("st.shared.u32 [%0], %1;" :: "r"(hO + 28), "r"(w.x << 16) : "memory");
    }
    __syncwarp();
    const uint32_t ha = cv_h_lane(lane, hE, hO), xa = xc + cv_x_lane(lane);
    TR(71);
    mbar_wait(bar_addr(sb, B_XREADY + (grp & 1)), (grp >> 1) & 1);
    TR(72);
    if (grp == 0 && ch >= 4) __nanosleep(CONV_STAGGER_NS);
    PACC(tw, k0);
    PCLK(k1);
    float acc[16][4];
#pragma unroll
    for (int i = 0; i < 16; i++) { acc[i][0] = 0.f; acc[i][1] = 0.f; acc[i][2] = 0.f; acc[i][3] = 0.f; }
#pragma unroll 1
    for (int r = 0; r < 8; r++) {
      uint32_t fx[16][4], fh[16][2];
#pragma unroll
      for (int i = 0; i < 16; i++) { fh[i][0] = lds4(ha + i * 256 + r * 32); fh[i][1] = lds4(ha + i * 256 + r * 32 + 16); }
#pragma unroll
      for (int i = 0; i < 16; i++) ldsm4(fx[i], xa + i * 256 - r * 32);
#pragma unroll
      for (int sx = 0; sx < 16; sx++)
#pragma unroll
        for (int jj = 0; jj < 16 - sx; jj++) mma16816(acc[jj + sx], fx[sx], fh[jj][0], fh[jj][1]);
    }
    PACC(tm, k1);
    PCLK(k2);
    TR(73);
#pragma unroll
    for (int i = 0; i < 8; i++) {
      uint32_t x[4];
      const uint32_t ad = xc + (ZROWS + lane) * 16 + i * 512;
      ldsm4(x, ad);
      stsm4(ad, badd(pack_bf16(acc[2 * i][0], acc[2 * i][1]), bmul(x[0], Dd)), badd(pack_bf16(acc[2 * i][2], acc[2 * i][3]), bmul(x[1], Dd)),
            badd(pack_bf16(acc[2 * i + 1][0], acc[2 * i + 1][1]), bmul(x[2], Dd)), badd(pack_bf16(acc[2 * i + 1][2], acc[2 * i + 1][3]), bmul(x[3], Dd)));
    }
    if (grp + 1 < GROUPS) warp_arrive(bar_addr(sb, B_ZDONE + (grp & 1)), lane);
    PACC(tr, k2);
    TR(74);
  }
  {
    mbar_wait(bar_addr(sb, B_QLAST + ch), 0);
    named_sync(CW_BAR, 256);
    TR(75);
    const uint32_t qb = sb + OFF_IO + (ch >> 1) * IOBUF + ((ch & 1) ? IO_K : IO_Q);
    gate_chunk(sb + OFF_X + ((GROUPS - 1) & 1) * XBUF + x_lane(lane) + ch * 512, qb + t_lane(lane));
    fence_async_smem();
    __syncwarp();
    if (lane == 0) { tma_st2(&p.ao, qb, group_d0(cidx, GROUPS - 1), ch * 256); bulk_commit(); bulk_wait_all(); }
    TR(99); TR_END();
  }
}

__device__ __forceinline__ void init(uint32_t sb) {
  if (threadIdx.x < 16 * ZROWS) sts16(sb + OFF_X + (threadIdx.x >> 4) * CHAN + (threadIdx.x & 15) * 16, 0, 0, 0, 0);
  if (threadIdx.x < 96) sts16(sb + OFF_H + (threadIdx.x >> 2) * HCOPY + (threadIdx.x & 1) * 16 + ((threadIdx.x & 2) ? 4128 : 0), 0, 0, 0, 0);
  if (threadIdx.x == 0) {
    for (int i = 0; i < 2; i++) { mbar_init(bar_addr(sb, B_XREADY + i), 4); mbar_init(bar_addr(sb, B_ZDONE + i), 8); }
    for (int i = 0; i < 4; i++) { mbar_init(bar_addr(sb, B_KV + i), 1); mbar_init(bar_addr(sb, B_Q + i), 1); }
    for (int i = 0; i < 8; i++) { mbar_init(bar_addr(sb, B_HRAW + i), 1); mbar_init(bar_addr(sb, B_QLAST + i), 1); }
    fence_async_smem();
  }
  named_sync(0, NTHREADS);
}
}

__device__ __forceinline__ void ssm_side_work(const Params& p, uint32_t sb, unsigned epoch) {
  const Role ro = get_role();
  const int h = ro.h, j = ro.j;
  const int lane = threadIdx.x & 31, g = lane >> 2, c = lane & 3;
  const int d0 = D_SPARE + 8 * h;
  uint8_t* xs = g_xs + (size_t)(h * 8 + g) * CV_BYTES + c * 4;
  auto xrow = [&](int beta) { return xs + (16 + beta) * 16; };
  {
    const uint4* hp = reinterpret_cast<const uint4*>(p.a_ssmk + (size_t)(d0 + j) * SEQ) + lane;
    uint8_t* he = g_xs + (size_t)(h * 8 + j) * CV_BYTES + CV_HE;
#pragma unroll 2
    for (int i = 0; i < 8; i++) {
      const uint4 wv = __ldg(hp + i * 32);
      const uint32_t nx = i * 32 + lane < 255 ? __ldg(reinterpret_cast<const uint32_t*>(hp + i * 32 + 1)) : 0u;
      const uint32_t o = 32 + (i * 32 + lane) * 16;
      *reinterpret_cast<uint4*>(he + o) = wv;
      *reinterpret_cast<uint4*>(he + CV_HCOPY + o) =
          make_uint4(__byte_perm(wv.x, wv.y, 0x5432), __byte_perm(wv.y, wv.z, 0x5432), __byte_perm(wv.z, wv.w, 0x5432), __byte_perm(wv.w, nx, 0x5432));
      if (o == 32) *reinterpret_cast<uint32_t*>(he + CV_HCOPY + 28) = wv.x << 16;
    }
    if (lane == 0) *reinterpret_cast<uint32_t*>(he + CV_D - CV_HE) = (uint32_t)__ldg(reinterpret_cast<const unsigned short*>(p.a_D + d0 + j)) * 0x10001u;
  }
  {
    const ssm::Taps taps = ssm::load_taps(p, d0, c);
    const uint32_t* kp = reinterpret_cast<const uint32_t*>(p.a_k + (size_t)(256 * j + 7 - g) * DA + d0) + c;
    const uint32_t* vp = reinterpret_cast<const uint32_t*>(p.a_v + (size_t)(256 * j + 7 - g) * DA + d0) + c;
    uint32_t kprev = j > 0 ? __ldg(kp - 8 * (DA / 2)) : 0u;
#pragma unroll 1
    for (int i0 = 0; i0 < 32; i0 += 8) {
      uint32_t kk[8], vv[8];
#pragma unroll
      for (int i = 0; i < 8; i++) { kk[i] = __ldg(kp + (i0 + i) * 8 * (DA / 2)); vv[i] = __ldg(vp + (i0 + i) * 8 * (DA / 2)); }
#pragma unroll
      for (int i = 0; i < 8; i++) {
        const uint32_t k2 = __shfl_sync(0xffffffffu, g < 1 ? kprev : kk[i], (lane + 4) & 31);
        const uint32_t k1 = __shfl_sync(0xffffffffu, g < 2 ? kprev : kk[i], (lane + 8) & 31);
        const uint32_t k0 = __shfl_sync(0xffffffffu, g < 3 ? kprev : kk[i], (lane + 12) & 31);
        *reinterpret_cast<uint32_t*>(xrow(32 * j + i0 + i)) = transpose8(ssm::short_conv(taps, k0, k1, k2, kk[i], vv[i]));
        kprev = kk[i];
      }
    }
    __syncwarp();
    if (lane == 0) {
      flag_signal(&g_flags.xs_ready[h].v);
      flag_wait(&g_flags.xs_ready[h].v, 8, epoch);
      fence_async_all();
      mbar_arrive(bar_addr(sb, B_XS));
    }
  }
  if (lane == 0) {
    for (int i = 0; i < 3; i++) {
      flag_wait(&g_flags.kv_ready[3 * h + i].v, 16, epoch);
      fence_async_all();
      mbar_arrive(bar_addr(sb, B_KV + i));
    }
    mbar_wait_nap(bar_addr(sb, B_CONV), 0);
    flag_signal(&g_flags.zs_ready[h].v);
    flag_wait(&g_flags.zs_ready[h].v, 8, epoch);
    asm volatile("red.relaxed.gpu.global.add.u64 [%0], 1;" :: "l"(&g_flags.done) : "memory");
  }
  __syncwarp();
  fence_async_all();
  const uint32_t qb = q_region(sb, 1) + 16384, zb = qb + 4096, bar = bar_addr(sb, B_GATE);
  constexpr uint32_t ZCH = 528;
  mbar_wait_slow(bar_addr(sb, B_GFREE), 0);
  if (lane == 0) { mbar_expect_tx(bar, 8192); tma_ld2(qb, &p.aq, bar, d0, 256 * j); }
  __syncwarp();
  if (lane < 8) bulk_ld(zb + lane * ZCH, g_xs + (size_t)(h * 8 + lane) * CV_BYTES + (16 + 32 * j) * 16, 512, bar);
  mbar_wait(bar, 0);
  ssm::gate_chunk(zb + (lane & 7) * ZCH + (lane >> 3) * 16, qb + ssm::t_lane(lane));
  fence_async_smem();
  __syncwarp();
  if (lane == 0) { tma_st2(&p.ao, qb, d0, 256 * j); bulk_commit(); bulk_wait_all(); }
}

__global__ void __cluster_dims__(2, 1, 1) __launch_bounds__(NTHREADS, 1)
concat_heads__ssm_conv_h3__compressed_kv_cla__prompt_kernel(uint8_t* xs, uint32_t one, const __grid_constant__ Params p) {
  if (threadIdx.x == 0) { prefetch_map(&p.wuk); prefetch_map(&p.ckv); }
  extern __shared__ uint8_t smem_raw[];
  if (threadIdx.x == 96) { ST(0); STG_(10); }
  const uint32_t sb = (smem_u32(smem_raw) + 1023) & ~1023u;
  const int warp = __shfl_sync(0xffffffffu, threadIdx.x >> 5, 0);
  const int wg = warp >> 2;
  const int cta = blockIdx.x;
  const bool attn = cta < NMAIN;
  if (attn && (threadIdx.x >> 5) == 4) {
    const Role ro = get_role();
    auto load = [&](int k) {
      const uint32_t full = bar_addr(sb, B_P1_FULL + k), dst = sb + k * P1_STAGE;
      mbar_expect_tx(full, P1_STAGE);
      tma_ld2(dst, &p.ckv, full, k * 64, kv_block(ro.j, 0) * 128);
      tma_ld3(dst + 16384, &p.wuk, full, 0, k * 64, ro.h * 4);
    };
    if (threadIdx.x == 128) {
      for (int i = 0; i < 4; i++) mbar_init(bar_addr(sb, B_P1_FULL + i), 1);
      asm volatile("fence.mbarrier_init.release.cluster;" ::: "memory");
      ST(1);
      load(0);
    }
    __syncwarp();
    named_arrive(0, NTHREADS);
    if (threadIdx.x == 128) {
      for (int k = 1; k < EARLY_LD; k++) load(k);
      ST(2);
    }
    __syncwarp();
  }
  const int lane = threadIdx.x & 31;
  if (wg == 0) {
    if (!attn) {
      asm volatile("setmaxnreg.dec.sync.aligned.u32 72;");
      if (threadIdx.x == 0) GT(0);
      if (one) { ssm::init(sb); ssm::io_warp(p, sb, cta - NMAIN, fresh_warp()); }
      if (threadIdx.x == 0) GT(14);
      return;
    }
    asm volatile("setmaxnreg.dec.sync.aligned.u32 40;");
    named_arrive(PP_BAR + 1, 256);
    if (warp == 2) {
      if (lane == 0) {
        for (int i = 0; i < 4; i++) mbar_init(bar_addr(sb, B_P1_EMPTY + i), 8);
        for (int i = 0; i < NSLOT; i++) {
          mbar_init(bar_addr(sb, B_RG_FULL + i), 1); mbar_init(bar_addr(sb, B_RG_EMPTY + i), 8);
        }
        for (int i = 0; i < 2; i++) { mbar_init(bar_addr(sb, B_ST_FULL + i), 4); mbar_init(bar_addr(sb, B_ST_EMPTY + i), 1); }
        mbar_init(bar_addr(sb, B_XS), 1); mbar_init(bar_addr(sb, B_CONV), 8); mbar_init(bar_addr(sb, B_GATE), 1); mbar_init(bar_addr(sb, B_GFREE), 1);
        for (int i = 0; i < 3; i++) mbar_init(bar_addr(sb, B_KV + i), 1);
        for (int i = 0; i < 8; i++) mbar_init(bar_addr(sb, B_CTXS + i), 4);
        for (int i = 0; i < 4; i++) { mbar_arrive(bar_addr(sb, B_RG_FULL + i)); if (i < 3) mbar_arrive_n(bar_addr(sb, B_RG_EMPTY + i), 8); }
        for (int i = 0; i < 4; i++) { mbar_init(bar_addr(sb, B_S2_FULL + i), 4); mbar_init(bar_addr(sb, B_S2_EMPTY + i), 1); }
        for (int i = 0; i < 2; i++) { mbar_init(bar_addr(sb, B_QFREE + i), 4); mbar_init(bar_addr(sb, B_CTXF + i), 1); }
        asm volatile("fence.mbarrier_init.release.cluster;" ::: "memory");
        ST(3);
      }
      __syncwarp();
      named_arrive(0, NTHREADS);
    } else {
      named_sync(0, NTHREADS);
    }
    if (threadIdx.x == 96) ST(4);
    if (warp == 0) {
      if (lane == 0) producer_main(p, sb);
    } else if (warp < 3) {
      storer_main(p, sb);
    } else {
      const unsigned epoch = load_epoch();
      mbar_wait(bar_addr(sb, B_P1_FULL + 3), 0);
      __nanosleep(SIDE_DELAY_NS);
      ssm_side_work(p, sb, epoch);
    }
  } else {
    if (attn) {
      asm volatile("setmaxnreg.inc.sync.aligned.u32 232;");
      if (threadIdx.x == 256) ST(5);
      if (one) consumer_main(p, sb, xs, one);
    } else {
      asm volatile("setmaxnreg.inc.sync.aligned.u32 216;");
      if (threadIdx.x == 128) { GT(12); PT(10); }
      if (one) { ssm::init(sb); ssm::conv_warp(p, sb, cta - NMAIN, fresh_warp() - 4); }
      if (threadIdx.x == 128) { PT(9); GT(13); }
    }
  }
}

typedef CUresult (*EncodeTiledFn)(CUtensorMap*, CUtensorMapDataType, cuuint32_t, void*, const cuuint64_t*, const cuuint64_t*,
                                  const cuuint32_t*, const cuuint32_t*, CUtensorMapInterleave, CUtensorMapSwizzle,
                                  CUtensorMapL2promotion, CUtensorMapFloatOOBfill);

void make_map(EncodeTiledFn enc, CUtensorMap* m, const void* ptr, int rank, const uint64_t* dims, const uint64_t* strides, const uint32_t* box) {
  cuuint64_t d[3], s[2]; cuuint32_t b[3], e[3] = {1, 1, 1};
  for (int i = 0; i < rank; i++) { d[i] = dims[i]; b[i] = box[i]; if (i) s[i - 1] = strides[i - 1]; }
  enc(m, CU_TENSOR_MAP_DATA_TYPE_BFLOAT16, rank, const_cast<void*>(ptr), d, s, b, e, CU_TENSOR_MAP_INTERLEAVE_NONE,
      CU_TENSOR_MAP_SWIZZLE_128B, CU_TENSOR_MAP_L2_PROMOTION_L2_256B, CU_TENSOR_MAP_FLOAT_OOB_FILL_NONE);
}
void map2(EncodeTiledFn enc, CUtensorMap* m, const void* ptr, uint64_t cols, uint64_t rows, uint32_t bc, uint32_t br) {
  const uint64_t dims[2] = {cols, rows}, st[1] = {cols * 2}; const uint32_t box[2] = {bc, br};
  make_map(enc, m, ptr, 2, dims, st, box);
}
void map2_plain(EncodeTiledFn enc, CUtensorMap* m, const void* ptr, uint64_t cols, uint64_t rows, uint32_t bc, uint32_t br) {
  cuuint64_t d[2] = {cols, rows}, st[1] = {cols * 2}; cuuint32_t b[2] = {bc, br}, e[2] = {1, 1};
  enc(m, CU_TENSOR_MAP_DATA_TYPE_BFLOAT16, 2, const_cast<void*>(ptr), d, st, b, e, CU_TENSOR_MAP_INTERLEAVE_NONE,
      CU_TENSOR_MAP_SWIZZLE_NONE, CU_TENSOR_MAP_L2_PROMOTION_L2_128B, CU_TENSOR_MAP_FLOAT_OOB_FILL_NONE);
}
void map3(EncodeTiledFn enc, CUtensorMap* m, const void* ptr, uint64_t rows, uint32_t nblk) {
  const uint64_t dims[3] = {64, rows, 64}, st[2] = {8192, 128}; const uint32_t box[3] = {64, 64, nblk};
  make_map(enc, m, ptr, 3, dims, st, box);
}

}

extern "C" void kernel_launch(void* const* d_in, const int* in_sizes, int n_in, void* d_out, int out_size) {
  (void)in_sizes; (void)n_in; (void)out_size;
  static EncodeTiledFn enc = nullptr;
  static void *kv_ptr = nullptr, *acc_ptr = nullptr, *xs_ptr = nullptr;
  if (!enc) {
    void* fn = nullptr; cudaDriverEntryPointQueryResult qr;
    cudaGetDriverEntryPoint("cuTensorMapEncodeTiled", &fn, cudaEnableDefault, &qr);
    enc = (EncodeTiledFn)fn;
    cudaGetSymbolAddress(&kv_ptr, g_kv);
    cudaGetSymbolAddress(&acc_ptr, g_ctx);
    cudaGetSymbolAddress(&xs_ptr, g_xs);
    cudaFuncSetAttribute(concat_heads__ssm_conv_h3__compressed_kv_cla__prompt_kernel, cudaFuncAttributeMaxDynamicSharedMemorySize, SMEM_BYTES);
  }
  Params p;
  p.a_q = (const bf16*)d_in[0]; p.a_k = (const bf16*)d_in[1]; p.a_v = (const bf16*)d_in[2];
  map2_plain(enc, &p.aq, d_in[0], DA, SEQ, 8, 256);
  map2_plain(enc, &p.ak, d_in[1], DA, SEQ, 8, 256);
  map2_plain(enc, &p.ak8, d_in[1], DA, SEQ, 8, 8);
  map2_plain(enc, &p.av, d_in[2], DA, SEQ, 8, 256);
  map2_plain(enc, &p.ao, d_out, OUTW, SEQ, 8, 256);
  p.a_shift = (const bf16*)d_in[3]; p.a_ssmk = (const bf16*)d_in[4]; p.a_D = (const bf16*)d_in[5];
  p.out = (bf16*)d_out; p.b_x = (const bf16*)d_in[6]; p.b_wo = (const bf16*)d_in[11];
  map2(enc, &p.x, d_in[6], DM, SEQ, 64, 128);
  map2(enc, &p.ckv, d_in[7], DC, SEQ, 64, 128);
  map3(enc, &p.wq, d_in[8], DM, 4);
  map2_plain(enc, &p.wqp, d_in[8], NH * HD, DM, 256, 4);
  map3(enc, &p.wuk, d_in[9], DC, 4);
  map3(enc, &p.wuv, d_in[10], DC, 4);
  map2(enc, &p.wo, d_in[11], DM, NH * HD, 64, 256);
  map2(enc, &p.part, d_out, OUTW, SEQ, 64, 64);
  p.kv = (uint8_t*)kv_ptr; p.ctx = (uint8_t*)acc_ptr;
  concat_heads__ssm_conv_h3__compressed_kv_cla__prompt_kernel<<<NCTA, NTHREADS, SMEM_BYTES>>>((uint8_t*)xs_ptr, 1u, p);
}
```

```cpp
#include <cuda_runtime.h>
#include <cuda_bf16.h>
#include <cuda.h>
#include <stdint.h>

namespace {

typedef __nv_bfloat16 bf16;

constexpr int SEQ  = 2048;
constexpr int DA   = 448;
constexpr int NH   = 16;
constexpr int HD   = 256;
constexpr int DM   = 448;
constexpr int DC   = 1024;
constexpr int OUTW = DA + DM;
constexpr int NMAIN = 128;
constexpr int NCONV = 4;
constexpr int NCTA  = NMAIN + NCONV;
constexpr int NTHREADS = 384;
constexpr int D_SPARE = 320;

__device__ __align__(1024) bf16 g_kv[2ull * SEQ * NH * HD];
__device__ __align__(1024) bf16 g_ctx[(size_t)NMAIN * 128 * HD];
constexpr uint32_t CV_HE = 272 * 16, CV_HCOPY = 4160, CV_D = CV_HE + 4144, CV_BYTES = CV_HE + 2 * CV_HCOPY;
__device__ __align__(128) uint8_t g_xs[NMAIN * CV_BYTES];
struct alignas(128) Flag { unsigned v; unsigned pad[31]; };
struct Flags {
  Flag kv_ready[3 * NH];
  Flag ctx_ready[NMAIN * 2];
  Flag out_ready[16 * 2];
  Flag xs_ready[NH];
  Flag zs_ready[NH];
  alignas(128) unsigned long long done;
};
__device__ Flags g_flags;
#define TS(i)
#define TSG(i)
#define GT(i)
#define PT(i)
#define WHICH_TS 0
#define PCLK(var)
#define PACC(acc, t0)
#define PDECL
#define PDUMP()

#define ST(i)
#define STG_(i)
#define TR_DECL
#define TR(tag)
#define TR_END()
#define TRG(tag)

struct alignas(64) Params {
  CUtensorMap ckv;
  CUtensorMap wuk;
  CUtensorMap wuv;
  CUtensorMap x;
  CUtensorMap wq;
  CUtensorMap wqp;
  CUtensorMap part;
  CUtensorMap wo;
  CUtensorMap ak, ak8, av, aq, ao;
  const bf16 *a_q, *a_k, *a_v, *a_shift, *a_ssmk, *a_D, *b_x, *b_wo;
  bf16* out;
  uint8_t *kv, *ctx;
};

constexpr uint32_t P1_STAGE = 49152;
constexpr uint32_t P1_STG   = 196608;
constexpr uint32_t SLOT     = 32768;
constexpr int      NSLOT    = 5;
constexpr uint32_t QREG     = 163840;
constexpr uint32_t CV_X = 4 * SLOT + 16384, CV_R = 3 * SLOT;
static_assert(CV_BYTES <= 16384 && CV_BYTES % 128 == 0, "SSM operands");
constexpr uint32_t BARS     = 229376;
constexpr uint32_t SMEM_BYTES = BARS + 512 + 1024;
enum : uint32_t {
  B_P1_FULL = 0, B_P1_EMPTY = 4, B_RG_FULL = 8, B_RG_EMPTY = 13, B_ST_FULL = 18, B_ST_EMPTY = 20,
  B_XS = 22, B_S2_FULL = 28, B_S2_EMPTY = 32, B_QFREE = 36, B_CTXF = 38, B_KV = 40, B_GATE = 43, B_CTXS = 44, B_GFREE = 52, B_CONV = 53, B_COUNT = 54
};

__device__ __forceinline__ uint32_t smem_u32(const void* p) { return (uint32_t)__cvta_generic_to_shared(p); }
__device__ __forceinline__ void mbar_init(uint32_t bar, uint32_t cnt) {
  asm volatile("mbarrier.init.shared::cta.b64 [%0], %1;" :: "r"(bar), "r"(cnt) : "memory");
}
__device__ __forceinline__ void mbar_expect_tx(uint32_t bar, uint32_t bytes) {
  asm volatile("mbarrier.arrive.expect_tx.shared::cta.b64 _, [%0], %1;" :: "r"(bar), "r"(bytes) : "memory");
}
__device__ __forceinline__ void mbar_arrive(uint32_t bar) {
  asm volatile("mbarrier.arrive.shared::cta.b64 _, [%0];" :: "r"(bar) : "memory");
}
__device__ __forceinline__ void mbar_arrive_n(uint32_t bar, uint32_t n) {
  asm volatile("mbarrier.arrive.shared::cta.b64 _, [%0], %1;" :: "r"(bar), "r"(n) : "memory");
}
__device__ __forceinline__ void lane0_arrive(uint32_t bar, uint32_t n, int lane) {
  asm volatile("{\n.reg .pred p;\nsetp.eq.s32 p, %2, 0;\n@p mbarrier.arrive.shared::cta.b64 _, [%0], %1;\n}" :: "r"(bar), "r"(n), "r"(lane) : "memory");
}
__device__ __forceinline__ bool mbar_try(uint32_t bar, uint32_t parity) {
  uint32_t ok;
  asm volatile("{\n.reg .pred p;\nmbarrier.try_wait.parity.shared::cta.b64 p, [%1], %2;\nselp.u32 %0, 1, 0, p;\n}"
               : "=r"(ok) : "r"(bar), "r"(parity) : "memory");
  return ok;
}
#define FLAG_NS 100
#define NAP_NS 100
constexpr uint32_t SPIN_LIMIT = 1u << 24;
__device__ __forceinline__ void mbar_wait(uint32_t bar, uint32_t parity) {
  if (mbar_try(bar, parity)) return;
  uint32_t n = 0;
  while (!mbar_try(bar, parity)) { if (++n > SPIN_LIMIT) __trap(); }
}
__device__ __forceinline__ void mbar_wait_nap(uint32_t bar, uint32_t parity) {
  uint32_t n = 0;
  while (!mbar_try(bar, parity)) { if (++n > (SPIN_LIMIT >> 2)) __trap(); __nanosleep(NAP_NS); }
}
__device__ __forceinline__ void mbar_wait_slow(uint32_t bar, uint32_t parity) {
  uint32_t n = 0;
  while (!mbar_try(bar, parity)) { if (++n > (SPIN_LIMIT >> 4)) __trap(); __nanosleep(500); }
}
__device__ __forceinline__ unsigned load_epoch() {
  unsigned long long e; asm volatile("ld.relaxed.gpu.global.u64 %0, [%1];" : "=l"(e) : "l"(&g_flags.done) : "memory"); return (unsigned)(e / NMAIN);
}
__device__ __forceinline__ void flag_wait(const unsigned* f, unsigned count, unsigned epoch) {
  const unsigned target = (epoch + 1) * count;
  uint32_t n = 0;
  while (true) {
    unsigned v;
    asm volatile("ld.acquire.gpu.global.u32 %0, [%1];" : "=r"(v) : "l"(f) : "memory");
    if ((int)(v - target) >= 0) break;
    if (++n > SPIN_LIMIT) __trap();
    __nanosleep(FLAG_NS);
  }
}
__device__ __forceinline__ void fence_async_all() { asm volatile("fence.proxy.async;" ::: "memory"); }
__device__ __forceinline__ void flag_signal(unsigned* f) {
  asm volatile("fence.acq_rel.gpu;" ::: "memory");
  asm volatile("red.relaxed.gpu.global.add.u32 [%0], 1;" :: "l"(f) : "memory");
}
__device__ __forceinline__ void flag_signal_after_bulk(unsigned* f) {
  asm volatile("red.relaxed.gpu.global.add.u32 [%0], 1;" :: "l"(f) : "memory");
}
__device__ __forceinline__ void fence_async_smem() { asm volatile("fence.proxy.async.shared::cta;" ::: "memory"); }
__device__ __forceinline__ void tma_ld2(uint32_t dst, const CUtensorMap* m, uint32_t bar, int c0, int c1) {
  asm volatile("cp.async.bulk.tensor.2d.shared::cluster.global.mbarrier::complete_tx::bytes [%0], [%1, {%3, %4}], [%2];"
               :: "r"(dst), "l"(m), "r"(bar), "r"(c0), "r"(c1) : "memory");
}
__device__ __forceinline__ void tma_ld3(uint32_t dst, const CUtensorMap* m, uint32_t bar, int c0, int c1, int c2) {
  asm volatile("cp.async.bulk.tensor.3d.shared::cluster.global.mbarrier::complete_tx::bytes [%0], [%1, {%3, %4, %5}], [%2];"
               :: "r"(dst), "l"(m), "r"(bar), "r"(c0), "r"(c1), "r"(c2) : "memory");
}
__device__ __forceinline__ void bulk_ld(uint32_t dst, const void* src, uint32_t bytes, uint32_t bar) {
  asm volatile("cp.async.bulk.shared::cluster.global.mbarrier::complete_tx::bytes [%0], [%1], %2, [%3];"
               :: "r"(dst), "l"(src), "r"(bytes), "r"(bar) : "memory");
}
__device__ __forceinline__ void bulk_st(void* dst, uint32_t src, uint32_t bytes) {
  asm volatile("cp.async.bulk.global.shared::cta.bulk_group [%0], [%1], %2;" :: "l"(dst), "r"(src), "r"(bytes) : "memory");
}
__device__ __forceinline__ void tma_st2(const CUtensorMap* m, uint32_t src, int c0, int c1) {
  asm volatile("cp.async.bulk.tensor.2d.global.shared::cta.bulk_group [%0, {%2, %3}], [%1];"
               :: "l"(m), "r"(src), "r"(c0), "r"(c1) : "memory");
}
__device__ __forceinline__ void tma_red2(const CUtensorMap* m, uint32_t src, int c0, int c1) {
  asm volatile("cp.reduce.async.bulk.tensor.2d.global.shared::cta.add.tile.bulk_group [%0, {%2, %3}], [%1];"
               :: "l"(m), "r"(src), "r"(c0), "r"(c1) : "memory");
}
__device__ __forceinline__ void tma_pf2(const CUtensorMap* m, int c0, int c1) {
  asm volatile("cp.async.bulk.prefetch.tensor.2d.L2.global.tile [%0, {%1, %2}];" :: "l"(m), "r"(c0), "r"(c1) : "memory");
}
__device__ __forceinline__ void bulk_prefetch(const void* src, uint32_t bytes) {
  asm volatile("cp.async.bulk.prefetch.L2.global [%0], %1;" :: "l"(src), "r"(bytes) : "memory");
}
__device__ __forceinline__ void bulk_commit() { asm volatile("cp.async.bulk.commit_group;" ::: "memory"); }
__device__ __forceinline__ void bulk_wait_read() { asm volatile("cp.async.bulk.wait_group.read 0;" ::: "memory"); }
__device__ __forceinline__ void bulk_wait_all() { asm volatile("cp.async.bulk.wait_group 0;" ::: "memory"); }
__device__ __forceinline__ void prefetch_map(const CUtensorMap* m) { asm volatile("prefetch.tensormap [%0];" :: "l"(m) : "memory"); }
__device__ __forceinline__ void wg_fence() { asm volatile("wgmma.fence.sync.aligned;" ::: "memory"); }
__device__ __forceinline__ void wg_commit() { asm volatile("wgmma.commit_group.sync.aligned;" ::: "memory"); }
template <int N> __device__ __forceinline__ void wg_wait() { asm volatile("wgmma.wait_group.sync.aligned %0;" :: "n"(N) : "memory"); }
template <int N> __device__ __forceinline__ void reg_fence(float (&d)[N]) {
#pragma unroll
  for (int i = 0; i < N; i++) asm volatile("" : "+f"(d[i]) :: "memory");
}
template <int N> __device__ __forceinline__ void reg_fence(uint32_t (&d)[N]) {
#pragma unroll
  for (int i = 0; i < N; i++) asm volatile("" : "+r"(d[i]) :: "memory");
}
__device__ __forceinline__ uint32_t fresh_tid() { uint32_t t; asm volatile("mov.u32 %0, %%tid.x;" : "=r"(t)); return t; }
__device__ __forceinline__ uint32_t lane_base16() {
  const uint32_t t = fresh_tid(), lane = t & 31, wq = (t >> 5) & 3;
  return (16 * wq + (lane & 7) + 8 * ((lane >> 3) & 1)) * 128 + (((lane >> 4) ^ (lane & 7)) << 4);
}
__device__ __forceinline__ void named_sync(int id, int n) { asm volatile("bar.sync %0, %1;" :: "r"(id), "r"(n) : "memory"); }
__device__ __forceinline__ void named_arrive(int id, int n) { asm volatile("bar.arrive %0, %1;" :: "r"(id), "r"(n) : "memory"); }
__device__ __forceinline__ uint32_t pack_bf16(float lo, float hi) {
  uint32_t r; asm("cvt.rn.bf16x2.f32 %0, %1, %2;" : "=r"(r) : "f"(hi), "f"(lo)); return r;
}
__device__ __forceinline__ float ex2(float x) { float y; asm("ex2.approx.ftz.f32 %0, %1;" : "=f"(y) : "f"(x)); return y; }
__device__ __forceinline__ void stsm4(uint32_t addr, uint32_t a, uint32_t b, uint32_t c, uint32_t d) {
  asm volatile("stmatrix.sync.aligned.m8n8.x4.shared.b16 [%0], {%1, %2, %3, %4};" :: "r"(addr), "r"(a), "r"(b), "r"(c), "r"(d) : "memory");
}
__device__ __forceinline__ void stsm4t(uint32_t addr, uint32_t a, uint32_t b, uint32_t c, uint32_t d) {
  asm volatile("stmatrix.sync.aligned.m8n8.x4.trans.shared.b16 [%0], {%1, %2, %3, %4};" :: "r"(addr), "r"(a), "r"(b), "r"(c), "r"(d) : "memory");
}
__device__ __forceinline__ uint64_t mk_desc(uint32_t addr, uint32_t lbo, uint32_t sbo) {
  return (uint64_t)(((addr & 0x3FFFF) >> 4) | ((lbo >> 4) << 16)) | ((uint64_t)((sbo >> 4) | (1u << 30)) << 32);
}
__device__ __forceinline__ uint64_t desc_k(uint32_t addr)  { return mk_desc(addr, 16, 1024); }
__device__ __forceinline__ uint64_t desc_mn(uint32_t addr) { return mk_desc(addr, 8192, 1024); }
__device__ __forceinline__ uint64_t desc_add(uint64_t d, uint32_t bytes) { return d + (bytes >> 4); }

__device__ __forceinline__ void wgmma_ss_n256_tb(float (&d)[128], uint64_t da, uint64_t db, int sd) {
  asm volatile("{\n.reg .pred p;\nsetp.ne.b32 p, %130, 0;\n"
    "wgmma.mma_async.sync.aligned.m64n256k16.f32.bf16.bf16 "
    "{%0, %1, %2, %3, %4, %5, %6, %7, %8, %9, %10, %11, %12, %13, %14, %15, "
    "%16, %17, %18, %19, %20, %21, %22, %23, %24, %25, %26, %27, %28, %29, %30, %31, "
    "%32, %33, %34, %35, %36, %37, %38, %39, %40, %41, %42, %43, %44, %45, %46, %47, "
    "%48, %49, %50, %51, %52, %53, %54, %55, %56, %57, %58, %59, %60, %61, %62, %63, "
    "%64, %65, %66, %67, %68, %69, %70, %71, %72, %73, %74, %75, %76, %77, %78, %79, "
    "%80, %81, %82, %83, %84, %85, %86, %87, %88, %89, %90, %91, %92, %93, %94, %95, "
    "%96, %97, %98, %99, %100, %101, %102, %103, %104, %105, %106, %107, %108, %109, %110, %111, "
    "%112, %113, %114, %115, %116, %117, %118, %119, %120, %121, %122, %123, %124, %125, %126, %127}, "
    "%128, %129, p, 1, 1, 0, 1;\n}"
    : "+f"(d[0]), "+f"(d[1]), "+f"(d[2]), "+f"(d[3]), "+f"(d[4]), "+f"(d[5]), "+f"(d[6]), "+f"(d[7]),
      "+f"(d[8]), "+f"(d[9]), "+f"(d[10]), "+f"(d[11]), "+f"(d[12]), "+f"(d[13]), "+f"(d[14]), "+f"(d[15]),
      "+f"(d[16]), "+f"(d[17]), "+f"(d[18]), "+f"(d[19]), "+f"(d[20]), "+f"(d[21]), "+f"(d[22]), "+f"(d[23]),
      "+f"(d[24]), "+f"(d[25]), "+f"(d[26]), "+f"(d[27]), "+f"(d[28]), "+f"(d[29]), "+f"(d[30]), "+f"(d[31]),
      "+f"(d[32]), "+f"(d[33]), "+f"(d[34]), "+f"(d[35]), "+f"(d[36]), "+f"(d[37]), "+f"(d[38]), "+f"(d[39]),
      "+f"(d[40]), "+f"(d[41]), "+f"(d[42]), "+f"(d[43]), "+f"(d[44]), "+f"(d[45]), "+f"(d[46]), "+f"(d[47]),
      "+f"(d[48]), "+f"(d[49]), "+f"(d[50]), "+f"(d[51]), "+f"(d[52]), "+f"(d[53]), "+f"(d[54]), "+f"(d[55]),
      "+f"(d[56]), "+f"(d[57]), "+f"(d[58]), "+f"(d[59]), "+f"(d[60]), "+f"(d[61]), "+f"(d[62]), "+f"(d[63]),
      "+f"(d[64]), "+f"(d[65]), "+f"(d[66]), "+f"(d[67]), "+f"(d[68]), "+f"(d[69]), "+f"(d[70]), "+f"(d[71]),
      "+f"(d[72]), "+f"(d[73]), "+f"(d[74]), "+f"(d[75]), "+f"(d[76]), "+f"(d[77]), "+f"(d[78]), "+f"(d[79]),
      "+f"(d[80]), "+f"(d[81]), "+f"(d[82]), "+f"(d[83]), "+f"(d[84]), "+f"(d[85]), "+f"(d[86]), "+f"(d[87]),
      "+f"(d[88]), "+f"(d[89]), "+f"(d[90]), "+f"(d[91]), "+f"(d[92]), "+f"(d[93]), "+f"(d[94]), "+f"(d[95]),
      "+f"(d[96]), "+f"(d[97]), "+f"(d[98]), "+f"(d[99]), "+f"(d[100]), "+f"(d[101]), "+f"(d[102]), "+f"(d[103]),
      "+f"(d[104]), "+f"(d[105]), "+f"(d[106]), "+f"(d[107]), "+f"(d[108]), "+f"(d[109]), "+f"(d[110]), "+f"(d[111]),
      "+f"(d[112]), "+f"(d[113]), "+f"(d[114]), "+f"(d[115]), "+f"(d[116]), "+f"(d[117]), "+f"(d[118]), "+f"(d[119]),
      "+f"(d[120]), "+f"(d[121]), "+f"(d[122]), "+f"(d[123]), "+f"(d[124]), "+f"(d[125]), "+f"(d[126]), "+f"(d[127])
    : "l"(da), "l"(db), "r"(sd));
}
__device__ __forceinline__ void wgmma_ss_n64(float (&d)[32], uint64_t da, uint64_t db, int sd) {
  asm volatile("{\n.reg .pred p;\nsetp.ne.b32 p, %34, 0;\n"
    "wgmma.mma_async.sync.aligned.m64n64k16.f32.bf16.bf16 "
    "{%0, %1, %2, %3, %4, %5, %6, %7, %8, %9, %10, %11, %12, %13, %14, %15, "
    "%16, %17, %18, %19, %20, %21, %22, %23, %24, %25, %26, %27, %28, %29, %30, %31}, "
    "%32, %33, p, 1, 1, 0, 0;\n}"
    : "+f"(d[0]), "+f"(d[1]), "+f"(d[2]), "+f"(d[3]), "+f"(d[4]), "+f"(d[5]), "+f"(d[6]), "+f"(d[7]),
      "+f"(d[8]), "+f"(d[9]), "+f"(d[10]), "+f"(d[11]), "+f"(d[12]), "+f"(d[13]), "+f"(d[14]), "+f"(d[15]),
      "+f"(d[16]), "+f"(d[17]), "+f"(d[18]), "+f"(d[19]), "+f"(d[20]), "+f"(d[21]), "+f"(d[22]), "+f"(d[23]),
      "+f"(d[24]), "+f"(d[25]), "+f"(d[26]), "+f"(d[27]), "+f"(d[28]), "+f"(d[29]), "+f"(d[30]), "+f"(d[31])
    : "l"(da), "l"(db), "r"(sd));
}
__device__ __forceinline__ void wgmma_rs_n256_tb(float (&d)[128], uint32_t a0, uint32_t a1, uint32_t a2, uint32_t a3, uint64_t db, int sd) {
  asm volatile("{\n.reg .pred p;\nsetp.ne.b32 p, %133, 0;\n"
    "wgmma.mma_async.sync.aligned.m64n256k16.f32.bf16.bf16 "
    "{%0, %1, %2, %3, %4, %5, %6, %7, %8, %9, %10, %11, %12, %13, %14, %15, "
    "%16, %17, %18, %19, %20, %21, %22, %23, %24, %25, %26, %27, %28, %29, %30, %31, "
    "%32, %33, %34, %35, %36, %37, %38, %39, %40, %41, %42, %43, %44, %45, %46, %47, "
    "%48, %49, %50, %51, %52, %53, %54, %55, %56, %57, %58, %59, %60, %61, %62, %63, "
    "%64, %65, %66, %67, %68, %69, %70, %71, %72, %73, %74, %75, %76, %77, %78, %79, "
    "%80, %81, %82, %83, %84, %85, %86, %87, %88, %89, %90, %91, %92, %93, %94, %95, "
    "%96, %97, %98, %99, %100, %101, %102, %103, %104, %105, %106, %107, %108, %109, %110, %111, "
    "%112, %113, %114, %115, %116, %117, %118, %119, %120, %121, %122, %123, %124, %125, %126, %127}, "
    "{%128, %129, %130, %131}, %132, p, 1, 1, 1;\n}"
    : "+f"(d[0]), "+f"(d[1]), "+f"(d[2]), "+f"(d[3]), "+f"(d[4]), "+f"(d[5]), "+f"(d[6]), "+f"(d[7]),
      "+f"(d[8]), "+f"(d[9]), "+f"(d[10]), "+f"(d[11]), "+f"(d[12]), "+f"(d[13]), "+f"(d[14]), "+f"(d[15]),
      "+f"(d[16]), "+f"(d[17]), "+f"(d[18]), "+f"(d[19]), "+f"(d[20]), "+f"(d[21]), "+f"(d[22]), "+f"(d[23]),
      "+f"(d[24]), "+f"(d[25]), "+f"(d[26]), "+f"(d[27]), "+f"(d[28]), "+f"(d[29]), "+f"(d[30]), "+f"(d[31]),
      "+f"(d[32]), "+f"(d[33]), "+f"(d[34]), "+f"(d[35]), "+f"(d[36]), "+f"(d[37]), "+f"(d[38]), "+f"(d[39]),
      "+f"(d[40]), "+f"(d[41]), "+f"(d[42]), "+f"(d[43]), "+f"(d[44]), "+f"(d[45]), "+f"(d[46]), "+f"(d[47]),
      "+f"(d[48]), "+f"(d[49]), "+f"(d[50]), "+f"(d[51]), "+f"(d[52]), "+f"(d[53]), "+f"(d[54]), "+f"(d[55]),
      "+f"(d[56]), "+f"(d[57]), "+f"(d[58]), "+f"(d[59]), "+f"(d[60]), "+f"(d[61]), "+f"(d[62]), "+f"(d[63]),
      "+f"(d[64]), "+f"(d[65]), "+f"(d[66]), "+f"(d[67]), "+f"(d[68]), "+f"(d[69]), "+f"(d[70]), "+f"(d[71]),
      "+f"(d[72]), "+f"(d[73]), "+f"(d[74]), "+f"(d[75]), "+f"(d[76]), "+f"(d[77]), "+f"(d[78]), "+f"(d[79]),
      "+f"(d[80]), "+f"(d[81]), "+f"(d[82]), "+f"(d[83]), "+f"(d[84]), "+f"(d[85]), "+f"(d[86]), "+f"(d[87]),
      "+f"(d[88]), "+f"(d[89]), "+f"(d[90]), "+f"(d[91]), "+f"(d[92]), "+f"(d[93]), "+f"(d[94]), "+f"(d[95]),
      "+f"(d[96]), "+f"(d[97]), "+f"(d[98]), "+f"(d[99]), "+f"(d[100]), "+f"(d[101]), "+f"(d[102]), "+f"(d[103]),
      "+f"(d[104]), "+f"(d[105]), "+f"(d[106]), "+f"(d[107]), "+f"(d[108]), "+f"(d[109]), "+f"(d[110]), "+f"(d[111]),
      "+f"(d[112]), "+f"(d[113]), "+f"(d[114]), "+f"(d[115]), "+f"(d[116]), "+f"(d[117]), "+f"(d[118]), "+f"(d[119]),
      "+f"(d[120]), "+f"(d[121]), "+f"(d[122]), "+f"(d[123]), "+f"(d[124]), "+f"(d[125]), "+f"(d[126]), "+f"(d[127])
    : "r"(a0), "r"(a1), "r"(a2), "r"(a3), "l"(db), "r"(sd));
}
__device__ __forceinline__ void wgmma_rs_n64_tb(float (&d)[32], uint32_t a0, uint32_t a1, uint32_t a2, uint32_t a3, uint64_t db, int sd) {
  asm volatile("{\n.reg .pred p;\nsetp.ne.b32 p, %37, 0;\n"
    "wgmma.mma_async.sync.aligned.m64n64k16.f32.bf16.bf16 "
    "{%0, %1, %2, %3, %4, %5, %6, %7, %8, %9, %10, %11, %12, %13, %14, %15, "
    "%16, %17, %18, %19, %20, %21, %22, %23, %24, %25, %26, %27, %28, %29, %30, %31}, "
    "{%32, %33, %34, %35}, %36, p, 1, 1, 1;\n}"
    : "+f"(d[0]), "+f"(d[1]), "+f"(d[2]), "+f"(d[3]), "+f"(d[4]), "+f"(d[5]), "+f"(d[6]), "+f"(d[7]),
      "+f"(d[8]), "+f"(d[9]), "+f"(d[10]), "+f"(d[11]), "+f"(d[12]), "+f"(d[13]), "+f"(d[14]), "+f"(d[15]),
      "+f"(d[16]), "+f"(d[17]), "+f"(d[18]), "+f"(d[19]), "+f"(d[20]), "+f"(d[21]), "+f"(d[22]), "+f"(d[23]),
      "+f"(d[24]), "+f"(d[25]), "+f"(d[26]), "+f"(d[27]), "+f"(d[28]), "+f"(d[29]), "+f"(d[30]), "+f"(d[31])
    : "r"(a0), "r"(a1), "r"(a2), "r"(a3), "l"(db), "r"(sd));
}
__device__ __forceinline__ void wgmma_rs_n64(float (&d)[32], uint32_t a0, uint32_t a1, uint32_t a2, uint32_t a3, uint64_t db, int sd) {
  asm volatile("{\n.reg .pred p;\nsetp.ne.b32 p, %37, 0;\n"
    "wgmma.mma_async.sync.aligned.m64n64k16.f32.bf16.bf16 "
    "{%0, %1, %2, %3, %4, %5, %6, %7, %8, %9, %10, %11, %12, %13, %14, %15, "
    "%16, %17, %18, %19, %20, %21, %22, %23, %24, %25, %26, %27, %28, %29, %30, %31}, "
    "{%32, %33, %34, %35}, %36, p, 1, 1, 0;\n}"
    : "+f"(d[0]), "+f"(d[1]), "+f"(d[2]), "+f"(d[3]), "+f"(d[4]), "+f"(d[5]), "+f"(d[6]), "+f"(d[7]),
      "+f"(d[8]), "+f"(d[9]), "+f"(d[10]), "+f"(d[11]), "+f"(d[12]), "+f"(d[13]), "+f"(d[14]), "+f"(d[15]),
      "+f"(d[16]), "+f"(d[17]), "+f"(d[18]), "+f"(d[19]), "+f"(d[20]), "+f"(d[21]), "+f"(d[22]), "+f"(d[23]),
      "+f"(d[24]), "+f"(d[25]), "+f"(d[26]), "+f"(d[27]), "+f"(d[28]), "+f"(d[29]), "+f"(d[30]), "+f"(d[31])
    : "r"(a0), "r"(a1), "r"(a2), "r"(a3), "l"(db), "r"(sd));
}

__device__ __forceinline__ uint4 lds16(uint32_t a) {
  uint4 v; asm volatile("ld.shared.v4.u32 {%0, %1, %2, %3}, [%4];" : "=r"(v.x), "=r"(v.y), "=r"(v.z), "=r"(v.w) : "r"(a) : "memory"); return v;
}
__device__ __forceinline__ void sts16(uint32_t a, uint32_t x, uint32_t y, uint32_t z, uint32_t w) {
  asm volatile("st.shared.v4.u32 [%0], {%1, %2, %3, %4};" :: "r"(a), "r"(x), "r"(y), "r"(z), "r"(w) : "memory");
}
__device__ __forceinline__ uint32_t lds4(uint32_t a) { uint32_t v; asm volatile("ld.shared.u32 %0, [%1];" : "=r"(v) : "r"(a) : "memory"); return v; }
__device__ __forceinline__ uint32_t lds4v(uint32_t a) { uint32_t v; asm volatile("ld.volatile.shared.u32 %0, [%1];" : "=r"(v) : "r"(a) : "memory"); return v; }
__device__ __forceinline__ uint32_t bmul(uint32_t a, uint32_t b) { uint32_t r; asm("mul.rn.bf16x2 %0, %1, %2;" : "=r"(r) : "r"(a), "r"(b)); return r; }
__device__ __forceinline__ uint32_t bfma(uint32_t a, uint32_t b, uint32_t c) { uint32_t r; asm("fma.rn.bf16x2 %0, %1, %2, %3;" : "=r"(r) : "r"(a), "r"(b), "r"(c)); return r; }
__device__ __forceinline__ uint32_t badd(uint32_t a, uint32_t b) { uint32_t r; asm("add.rn.bf16x2 %0, %1, %2;" : "=r"(r) : "r"(a), "r"(b)); return r; }

__device__ __forceinline__ void ldsm4(uint32_t (&r)[4], uint32_t a) {
  asm volatile("ldmatrix.sync.aligned.m8n8.x4.shared.b16 {%0, %1, %2, %3}, [%4];" : "=r"(r[0]), "=r"(r[1]), "=r"(r[2]), "=r"(r[3]) : "r"(a) : "memory");
}
__device__ __forceinline__ void ldsm4t(uint32_t (&r)[4], uint32_t a) {
  asm volatile("ldmatrix.sync.aligned.m8n8.x4.trans.shared.b16 {%0, %1, %2, %3}, [%4];" : "=r"(r[0]), "=r"(r[1]), "=r"(r[2]), "=r"(r[3]) : "r"(a) : "memory");
}
__device__ __forceinline__ uint32_t transpose8(uint32_t a) { uint32_t d; asm volatile("movmatrix.sync.aligned.m8n8.trans.b16 %0, %1;" : "=r"(d) : "r"(a)); return d; }

__device__ __forceinline__ void mma16816(float (&d)[4], const uint32_t (&a)[4], uint32_t b0, uint32_t b1) {
  asm volatile("mma.sync.aligned.m16n8k16.row.col.f32.bf16.bf16.f32 {%0, %1, %2, %3}, {%4, %5, %6, %7}, {%8, %9}, {%0, %1, %2, %3};"
               : "+f"(d[0]), "+f"(d[1]), "+f"(d[2]), "+f"(d[3]) : "r"(a[0]), "r"(a[1]), "r"(a[2]), "r"(a[3]), "r"(b0), "r"(b1));
}

#define STG_K1 2
#define STG_K2 10
#define STG_Q1 1
#define STG_Q2 5
#define PACE_A 400
#define PACE_B 100
#define PF_QA 48
#define PF_CV 64
#define PF_X 8
#define PF_WO 11
#define Q_PRE 2
#define CV_SER -1
#define CV_QX 0
#define CV_FX 1
#define ARRIVE_KK 12
#define SIDE_DELAY_NS 4000
#define HEAD_MAP 1
#define EARLY_LD 2
#define HI_ORDER 9
constexpr int CV_BAR = 5;
constexpr int PP_BAR = 3;
template <int V> struct Int { static constexpr int value = V; };
struct Ring {
  uint32_t slot, phase;
  __device__ __forceinline__ void next() { if (++slot == NSLOT) { slot = 0; phase ^= 1; } }
};
__device__ __forceinline__ uint32_t bar_addr(uint32_t sb, uint32_t i) { return sb + BARS + 8 * i; }
__device__ __forceinline__ uint32_t q_region(uint32_t sb, int w) { return sb + QREG + (w ^ 1) * 32768; }

struct Role { int h, j; };
__device__ __forceinline__ Role get_role() {
  int cta; asm volatile("mov.u32 %0, %%ctaid.x;" : "=r"(cta));
  const int c = cta >> 1;
  int h, u;
  const int a = c - 4, b = c - 36, q = (b * 37) >> 8;
  h = a < 0 ? 15 : b < 0 ? a & 7 : 8 + b - 7 * q;
  u = a < 0 ? c : b < 0 ? a >> 3 : q;
  return Role{h, 2 * u + (cta & 1)};
}
__device__ __forceinline__ int fresh_warp() { return __shfl_sync(0xffffffffu, fresh_tid() >> 5, 0); }

__device__ __forceinline__ int q_tile(int h, int j, int which) { return ((h < 8) == (which == 0)) ? 15 - j : j; }

__device__ __forceinline__ int o_chunk(int h, int c) { const int x = c + (h & 7); return x % 7; }

__device__ __forceinline__ int kv_block(int j, int t) { return j + 8 * ((HI_ORDER >> t) & 1); }
__device__ __forceinline__ uint8_t* kv_tile(const Params& p, int v, int h, int tile) { return p.kv + (size_t)((v * NH + h) * 32 + tile) * 32768; }

__device__ __forceinline__ void ring_acquire(uint32_t sb, Ring& r, uint32_t bytes) {
  mbar_wait(bar_addr(sb, B_RG_EMPTY + r.slot), r.phase ^ 1);
  mbar_expect_tx(bar_addr(sb, B_RG_FULL + r.slot), bytes);
}
__device__ __forceinline__ void producer_main(const Params& p, uint32_t sb) {
  const Role ro = get_role();
  const int h = ro.h, j = ro.j;
  TR_DECL;
  ST(11);
  for (int it = EARLY_LD; it < 71; it++) {
    const int t = it >> 4, k = it & 15, s = it & 3;
    mbar_wait(bar_addr(sb, B_P1_EMPTY + s), ((it >> 2) & 1) ^ 1);
    const uint32_t full = bar_addr(sb, B_P1_FULL + s), dst = sb + s * P1_STAGE;
    mbar_expect_tx(full, P1_STAGE);
    if ((it & 7) == 4) TRG(it);
    if (t < 4) {
      tma_ld2(dst, &p.ckv, full, k * 64, kv_block(j, t) * 128);
      tma_ld3(dst + 16384, (t >> 1) ? &p.wuv : &p.wuk, full, 0, k * 64, h * 4);
    } else {
      tma_ld2(dst, &p.x, full, k * 64, q_tile(h, j, 0) * 128);
      tma_ld3(dst + 16384, &p.wq, full, 0, k * 64, h * 4);
    }
    if (it >= PF_QA && it < PF_QA + 14) {
      const int i = it - PF_QA;
      bulk_prefetch(p.b_x + (size_t)(q_tile(h, j, 0) * 128 + (h & 7) * 16) * DM + i * 512, 1024);
      tma_pf2(&p.wqp, h * HD, (i * 8 + j) * 4);
    }
    if (it >= PF_CV && it < PF_CV + 3) {
      mbar_wait(bar_addr(sb, B_XS), 0);
      bulk_prefetch(g_xs + (size_t)(h * 8 + j) * CV_BYTES + (it - PF_CV) * (CV_BYTES / 3), CV_BYTES / 3);
    }
  }
  mbar_wait(bar_addr(sb, B_P1_EMPTY + 3), 0);
  mbar_wait(bar_addr(sb, B_XS), 0);
  mbar_expect_tx(bar_addr(sb, B_RG_FULL + 4), CV_BYTES);
  bulk_ld(sb + CV_X, g_xs + (size_t)(h * 8 + j) * CV_BYTES, CV_BYTES, bar_addr(sb, B_RG_FULL + 4));
  Ring r{0, 1};
  auto prefetch_wo = [&](int left) {
    const int i = PF_WO - left;
    if (PF_WO && i >= 0 && i < 8) bulk_prefetch(p.b_wo + (size_t)(h * HD + j * 32 + 4 * i) * DM, 4 * DM * 2);
  };
  mbar_wait(bar_addr(sb, B_KV), 0);
  for (int which = 0; which < 2; which++) {
    const int qt = q_tile(h, j, which);
    if (which == 1) {
      for (int kc = 0; kc < 7; kc++) {
        prefetch_wo(4 * qt + 4 + 7 - kc);
        ring_acquire(sb, r, 32768);
        tma_ld3(sb + r.slot * SLOT, &p.wq, bar_addr(sb, B_RG_FULL + r.slot), 0, kc * 64, h * 4);
        r.next();
        if (kc == 0 || (kc & 1)) {
          ring_acquire(sb, r, kc == 0 ? 16384 : 32768);
          const uint32_t full = bar_addr(sb, B_RG_FULL + r.slot), dst = sb + r.slot * SLOT;
          tma_ld2(dst, &p.x, full, kc * 64, qt * 128);
          if (kc > 0) tma_ld2(dst + 16384, &p.x, full, kc * 64 + 64, qt * 128);
          r.next();
        }
      }
    }
    const int n = 2 * qt + 2;
    for (int f = 0; f < 2 * n; f++) {
      if (which == 0) {
        const int i = f - max(2 * n - PF_X, 0);
        if (PF_X && i >= 0 && i < 4) bulk_prefetch(p.b_x + (size_t)((15 - qt) * 128 + (h & 7) * 16 + 4 * i) * DM, 4 * DM * 2);
      } else prefetch_wo(2 * n - f);
      const bool isK = (f == 0) || ((f & 1) && f < 2 * n - 1);
      const int i = isK ? (f + 1) >> 1 : (f == 2 * n - 1 ? n - 1 : (f >> 1) - 1);
      const int tile = which ? n - 1 - i : i;
      if (!isK) mbar_wait(bar_addr(sb, B_KV + 1 + ((tile >> 4) ^ ((HI_ORDER >> 2) & 1))), 0);
      if (which == 0 && f < 2) mbar_wait(bar_addr(sb, B_P1_EMPTY + f), 1);
      ring_acquire(sb, r, 32768);
      if (isK && (tile & 3) == 0) TRG(100 + 50 * which + tile);
      bulk_ld(sb + r.slot * SLOT, kv_tile(p, !isK, h, tile), 32768, bar_addr(sb, B_RG_FULL + r.slot));
      r.next();
    }
  }
  for (int i = 0; i < 14; i++) {
    ring_acquire(sb, r, 32768);
    if ((i & 3) == 0) TRG(200 + i);
    if (i == 13) TR_END();
    tma_ld2(sb + r.slot * SLOT, &p.wo, bar_addr(sb, B_RG_FULL + r.slot), o_chunk(h, i >> 1) * 64, ((i & 1) ? h ^ 8 : h) * HD);
    r.next();
  }
}

__device__ __forceinline__ void storer_main(const Params& p, uint32_t sb) {
  const Role ro = get_role();
  const int h = ro.h, j = ro.j, w = fresh_warp() - 1;
  const uint32_t full = bar_addr(sb, B_ST_FULL + w), empty = bar_addr(sb, B_ST_EMPTY + w);
  const int lane = threadIdx.x & 31;
  const unsigned epoch = load_epoch();
  if (lane == 0) {
    for (int job = 0; job < 8; job++) {
      const int t = job >> 1;
      uint8_t* dst = kv_tile(p, t >> 1, h, 2 * kv_block(j, t) + w) + (job & 1) * 16384;
      mbar_wait_nap(full, job & 1);
      for (int i = 0; i < 8; i++) {
        if (i) __nanosleep(job < 6 ? PACE_A : PACE_B);
        bulk_st(dst + i * 2048, sb + P1_STG + w * 16384 + i * 2048, 2048);
      }
      bulk_commit();
      bulk_wait_read();
      mbar_arrive(empty);
      if (job >= 3 && (job & 1)) { bulk_wait_all(); flag_signal(&g_flags.kv_ready[3 * h + t - 1].v); }
    }
  }
  __syncwarp();
  const int cta = h * 8 + j, qt = q_tile(h, j, 1);
  const uint32_t qreg = q_region(sb, w);
  {
    mbar_wait_nap(bar_addr(sb, B_CTXS + 4 * w), 0);
    uint4* z = reinterpret_cast<uint4*>(p.out + (size_t)(qt * 128 + w * 64 + (h & 7) * 8 + (lane >> 2)) * OUTW + DA) + (lane & 3);
#pragma unroll
    for (int i = 0; i < 14; i++) z[4 * i] = make_uint4(0, 0, 0, 0);
    __syncwarp();
    if (lane != 0) return;
    for (int b = 0; b < 4; b++) {
      mbar_wait(bar_addr(sb, B_CTXS + 4 * w + b), 0);
      bulk_st(p.ctx + (size_t)(cta * 2 + w) * 32768 + b * 8192, qreg + b * 8192, 8192);
      bulk_commit();
    }
    bulk_wait_read();
    mbar_arrive(empty);
    bulk_wait_all();
    flag_signal(&g_flags.ctx_ready[cta * 2 + w].v);
    flag_signal_after_bulk(&g_flags.out_ready[qt * 2 + w].v);
  }
  {
    const int wx = w ^ 1;
    flag_wait(&g_flags.ctx_ready[(cta ^ 64) * 2 + wx].v, 1, epoch);
    flag_wait(&g_flags.out_ready[qt * 2 + wx].v, 8, epoch);
    fence_async_all();
    mbar_wait_nap(bar_addr(sb, B_QFREE + w), 0);
    mbar_expect_tx(bar_addr(sb, B_CTXF + w), 32768);
    bulk_ld(qreg, p.ctx + (size_t)((cta ^ 64) * 2 + wx) * 32768, 32768, bar_addr(sb, B_CTXF + w));
    for (int ch = 0; ch < 7; ch++) {
      const int b = ch & 1;
      mbar_wait(bar_addr(sb, B_S2_FULL + w * 2 + b), (ch >> 1) & 1);
      tma_red2(&p.part, qreg + b * 8192, DA + o_chunk(h, ch) * 64, qt * 128 + wx * 64);
      bulk_commit();
      if (ch == 0 && w == 1) mbar_arrive(bar_addr(sb, B_GFREE));
      bulk_wait_read();
      mbar_arrive(bar_addr(sb, B_S2_EMPTY + w * 2 + b));
    }
    GT(48 + w);
    bulk_wait_all();
    GT(50 + w); GT(52 + w); GT(56);
    if (w == 0) { ST(12); STG_(13); }
  }
}

template <int OFF, int NB, int NREG>
__device__ __forceinline__ void store_blocks(uint32_t base, uint32_t lanebase, const uint32_t (&pk)[NREG]) {
#pragma unroll
  for (int J = 0; J < NB * 8; J += 2) {
    const uint32_t a = base + (J >> 3) * 8192 + (lanebase ^ ((J & 7) << 4));
    stsm4(a, pk[OFF + 2 * J], pk[OFF + 2 * J + 1], pk[OFF + 2 * J + 2], pk[OFF + 2 * J + 3]);
  }
}
__device__ __forceinline__ void warp_arrive(uint32_t bar, int lane) { __syncwarp(); if (lane == 0) mbar_arrive(bar); }
__device__ __forceinline__ void release(uint32_t bar, int lane) { lane0_arrive(bar, 1, lane); }

template <int W> __device__ __forceinline__ constexpr int cv_tile(int u) { return 2 * u + ((u ^ W) & 1); }
__device__ __forceinline__ uint32_t cv_x_lane(uint32_t lane) { return (16 + (lane & 15) - (lane >> 4)) * 16; }
__device__ __forceinline__ uint32_t cv_h_lane(uint32_t lane, uint32_t hE, uint32_t hO) {
  const uint32_t g = lane >> 2, c = lane & 3;
  return (g & 1) ? hO + (15 + 2 * c - g) * 2 : hE + (16 + 2 * c - g) * 2;
}
template <int W>
__device__ __forceinline__ void conv_mma(float (&ca)[8][4], uint32_t xa, uint32_t ha, uint32_t sb, uint32_t lb, const uint32_t (&pk)[64]) {
  constexpr int N = 16 - W;
  uint32_t fx[N][4], fh[N][2];
  auto ld_h = [&](int i, int rr) { fh[i][0] = lds4(ha + i * 256 + rr * 32); fh[i][1] = lds4(ha + i * 256 + rr * 32 + 16); };
  if (CV_SER >= 0 && W == 0) named_sync(CV_BAR, 256);
  ldsm4(fx[0], xa);
#pragma unroll
  for (int u = 0; u < 8; u++) ld_h(cv_tile<W>(u), 0);
  ldsm4(fx[1], xa + 256);
#pragma unroll
  for (int u = 0; u < 8; u++) if (cv_tile<W ^ 1>(u) < N) ld_h(cv_tile<W ^ 1>(u), 0);
#pragma unroll
  for (int i = 2; i < N; i++) ldsm4(fx[i], xa + i * 256);
#pragma unroll
  for (int sx = 0; sx < N; sx++) {
#pragma unroll
    for (int u = 0; u < 8; u++) {
      const int jj = cv_tile<W>(u) - sx;
      if (jj >= 0) mma16816(ca[u], fx[sx], fh[jj < 0 ? 0 : jj][0], fh[jj < 0 ? 0 : jj][1]);
    }
    ldsm4(fx[sx], xa + sx * 256 - 32);
    ld_h(N - 1 - sx, 1);
    if (W == 1 && sx == CV_SER) named_arrive(CV_BAR, 256);
  }
  mbar_wait(bar_addr(sb, B_P1_EMPTY + 2), 1);
  if (W == 0) { mbar_wait(bar_addr(sb, B_ST_EMPTY), 1); mbar_wait(bar_addr(sb, B_ST_EMPTY + 1), 1); }
#pragma unroll
  for (int jj = 15; jj >= 0; jj--) {
    if (W == 0 || CV_QX) stsm4(q_region(sb, W) + (jj >> 2) * 8192 + (lb ^ ((jj & 3) << 5)), pk[4 * jj], pk[4 * jj + 1], pk[4 * jj + 2], pk[4 * jj + 3]);
#pragma unroll
    for (int u = 0; u < 8; u++) {
      const int sx = cv_tile<W>(u) - jj;
      if (sx >= 0) mma16816(ca[u], fx[sx < 0 ? 0 : sx], fh[jj < N ? jj : 0][0], fh[jj < N ? jj : 0][1]);
    }
  }
}

__device__ __forceinline__ void consumer_main(const Params& p, uint32_t sb, uint8_t* xs_base, uint32_t one) {
  const int lane = fresh_tid() & 31, w = (fresh_warp() >> 2) - 1;
  const uint32_t lb = lane_base16();
  int qt, cc;
  { const Role ro = get_role(); qt = q_tile(ro.h, ro.j, 0); cc = ro.h * 8 + ro.j; }
  const uint32_t st_full = bar_addr(sb, B_ST_FULL + w), st_empty = bar_addr(sb, B_ST_EMPTY + w);
  const uint32_t stg = sb + P1_STG + w * 16384;

  auto turn_begin = [&]() { named_sync(PP_BAR + w, 256); };
  auto turn_end = [&]() { named_arrive(PP_BAR + (w ^ 1), 256); };
  float acc[128];
#pragma unroll
  for (int i = 0; i < 128; i++) acc[i] = 0.f;
  uint32_t pk[64];
#pragma unroll
  for (int i = 0; i < 64; i++) pk[i] = 0;
  if (fresh_warp() != 4) named_sync(0, NTHREADS);
  PDECL;
  TR_DECL;
  TR(0);
  TSG(0); TS(1);
  const uint32_t qreg = q_region(sb, w);
  for (int t = 0; t < 5; t++) {
    const int nk = t < 4 ? 16 : 7;
#pragma unroll 1
    for (int k = 0; k < nk; k++) {
      const int it = t * 16 + k, s = k & 3;
      if (it == 0 && threadIdx.x == 256) ST(6);
      mbar_wait(bar_addr(sb, B_P1_FULL + s), (it >> 2) & 1);
      if (it < 3 && threadIdx.x == 256) ST(7 + it);
      TR(1);
      const uint64_t da = desc_k(sb + s * P1_STAGE + w * 8192), db = desc_mn(sb + s * P1_STAGE + 16384);
      turn_begin();
      wg_fence();
#pragma unroll
      for (int kk = 0; kk < 4; kk++) wgmma_ss_n256_tb(acc, desc_add(da, kk * 32), desc_add(db, kk * 2048), (k | kk) != 0);
      wg_commit();
      turn_end();
      TR(3);
      wg_wait<1>();
      if (k > 0) release(bar_addr(sb, B_P1_EMPTY + ((k - 1) & 3)), lane);
      const int k1 = t < 4 ? STG_K1 : STG_Q1, k2 = t < 4 ? STG_K2 : STG_Q2;
      if (t > 0 && (k == k1 || k == k2)) {
        const int job = 2 * (t - 1) + (k != k1);
        if (job > 0) mbar_wait(st_empty, (job - 1) & 1);
        if (k == k1) store_blocks<0, 2>(stg, lb, pk); else store_blocks<32, 2>(stg, lb, pk);
      }
      if (t > 0 && (k == k1 + 1 || k == k2 + 1)) { fence_async_smem(); warp_arrive(st_full, lane); }
      TR(5);
    }
    wg_wait<0>();
    TR(6);
    reg_fence(acc);
    release(bar_addr(sb, B_P1_EMPTY + ((nk - 1) & 3)), lane);
#pragma unroll
    for (int i = 0; i < 64; i++) pk[i] = pack_bf16(acc[2 * i], acc[2 * i + 1]);
    TS(t < 4 ? 2 + t : 60);
  }
  TS(6);
  {
    const uint32_t wq = lb >> 11, ln = lane, cx = sb + CV_X;
    float ca[8][4];
#pragma unroll
    for (int i = 0; i < 8; i++) { ca[i][0] = 0.f; ca[i][1] = 0.f; ca[i][2] = 0.f; ca[i][3] = 0.f; }
    const uint32_t xa = cx + cv_x_lane(ln) - wq * 64, ha = cv_h_lane(ln, cx + CV_HE, cx + CV_HE + CV_HCOPY) + wq * 64;
    mbar_wait(bar_addr(sb, B_RG_FULL + 4), 0);
    TR(7); TS(19); TS(20);
    if (w) conv_mma<1>(ca, xa, ha, sb, lb, pk); else conv_mma<0>(ca, xa, ha, sb, lb, pk);
    TR(8); TS(21);
    const uint32_t ex = sb + CV_R + w * 16384 + ln * 16;
#pragma unroll
    for (int u = 0; u < 8; u++)
      sts16(ex + (wq * 8 + u) * 512, __float_as_uint(ca[u][0]), __float_as_uint(ca[u][1]), __float_as_uint(ca[u][2]), __float_as_uint(ca[u][3]));
  }
  auto conv_finish = [&]() {
    const uint32_t wq = lb >> 11, cx = sb + CV_X, ex = sb + CV_R + w * 16384 + lane * 16;
    uint8_t* gz = xs_base + (size_t)cc * CV_BYTES;
    const uint32_t Dd = lds4(cx + CV_D);
    uint32_t z[2][2];
#pragma unroll
    for (int e = 0; e < 2; e++) {
      const uint32_t u = 2 * wq + e, nt = 2 * u + ((e ^ w) & 1);
      float y[4] = {0.f, 0.f, 0.f, 0.f};
#pragma unroll
      for (int v = 0; v < 4; v++) {
        const uint4 t = lds16(ex + (v * 8 + u) * 512);
        y[0] += __uint_as_float(t.x); y[1] += __uint_as_float(t.y); y[2] += __uint_as_float(t.z); y[3] += __uint_as_float(t.w);
      }
      const uint32_t o = (16 + 16 * nt) * 16 + lane * 4;
      *reinterpret_cast<uint32_t*>(gz + o)       = badd(pack_bf16(y[0], y[1]), bmul(lds4(cx + o), Dd));
      *reinterpret_cast<uint32_t*>(gz + o + 128) = badd(pack_bf16(y[2], y[3]), bmul(lds4(cx + o + 128), Dd));
    }
    __syncwarp();
    release(bar_addr(sb, B_RG_EMPTY + 3), lane);
    release(bar_addr(sb, B_RG_EMPTY + 4), lane);
    if (lane == 0) mbar_arrive(bar_addr(sb, B_CONV));
  };
  TS(15);
  TR(10);
  Ring r{0, 1};
  auto take = [&]() { const uint32_t sl = r.slot; mbar_wait(bar_addr(sb, B_RG_FULL + sl), r.phase); r.next(); return sl; };
  constexpr float SC = 0.0625f * 1.4426950408889634f;
  uint32_t ws;
#pragma unroll 1
  for (int which = 0;; which++) {
    float s[32];
#pragma unroll
    for (int i = 0; i < 32; i++) s[i] = 0.f;
    uint32_t pa[16];
    float b0, b1, l0, l1;
    const uint64_t dq = desc_k(qreg);
    uint64_t dk = 0, dqq = 0, dv = 0;
    auto prep_qk = [&](uint32_t kaddr) { dk = desc_k(kaddr); dqq = dq + (kaddr >> 31); asm volatile("" : "+l"(dk), "+l"(dqq)); };
    auto prep_pv = [&](uint32_t vaddr) { dv = desc_mn(vaddr); asm volatile("" : "+l"(dv)); };
    auto issue_qk = [&]() {
#pragma unroll
      for (int kk = 0; kk < 16; kk++)
        wgmma_ss_n64(s, desc_add(dqq, (kk >> 2) * 8192 + (kk & 3) * 32), desc_add(dk, (kk >> 2) * 8192 + (kk & 3) * 32), kk != 0);
    };
    auto issue_pv = [&](int accumulate) {
#pragma unroll
      for (int kk = 0; kk < 4; kk++)
        wgmma_rs_n256_tb(acc, pa[4 * kk], pa[4 * kk + 1], pa[4 * kk + 2], pa[4 * kk + 3], desc_add(dv, kk * 2048), accumulate | kk);
    };
    auto mask_diag = [&]() {
      const int d = (int)((lb >> 11) << 4) + (lane >> 2) - 2 * (lane & 3);
#pragma unroll
      for (int jj = 0; jj < 8; jj++) {
        if (8 * jj > d)     s[4 * jj]     = -INFINITY;
        if (8 * jj + 1 > d) s[4 * jj + 1] = -INFINITY;
        if (8 * jj - 8 > d) s[4 * jj + 2] = -INFINITY;
        if (8 * jj - 7 > d) s[4 * jj + 3] = -INFINITY;
      }
    };
    auto row_max = [&](float& x0, float& x1) {
      x0 = fmaxf(s[0], s[1]); x1 = fmaxf(s[2], s[3]);
#pragma unroll
      for (int jj = 1; jj < 8; jj++) {
        x0 = fmaxf(x0, fmaxf(s[4 * jj], s[4 * jj + 1]));
        x1 = fmaxf(x1, fmaxf(s[4 * jj + 2], s[4 * jj + 3]));
      }
      x0 = fmaxf(x0, __shfl_xor_sync(0xffffffffu, x0, 1));
      x1 = fmaxf(x1, __shfl_xor_sync(0xffffffffu, x1, 1));
      x0 = fmaxf(x0, __shfl_xor_sync(0xffffffffu, x0, 2));
      x1 = fmaxf(x1, __shfl_xor_sync(0xffffffffu, x1, 2));
    };
    auto exps = [&](uint32_t (&pp)[16], float& r0, float& r1) {
      float t0, t1, t2, t3;
#pragma unroll
      for (int jj = 0; jj < 8; jj++) {
        const float e0 = ex2(fmaf(s[4 * jj], SC, b0)), e1 = ex2(fmaf(s[4 * jj + 1], SC, b0));
        const float e2 = ex2(fmaf(s[4 * jj + 2], SC, b1)), e3 = ex2(fmaf(s[4 * jj + 3], SC, b1));
        if (jj == 0) { t0 = e0; t1 = e1; t2 = e2; t3 = e3; } else { t0 += e0; t1 += e1; t2 += e2; t3 += e3; }
        pp[2 * jj] = pack_bf16(e0, e1); pp[2 * jj + 1] = pack_bf16(e2, e3);
      }
      r0 = t0 + t1; r1 = t2 + t3;
    };

    const bool up = w == which;
    const int n = 2 * qt + 2, nw = n - up;
    int fd = which ? 0 : 2 * n - 1;
    const int dir = which ? 1 : -1;
    auto skip = [&]() { r.next(); fd += dir; };
    auto give = [&](uint32_t sl, int d) {
      lane0_arrive(bar_addr(sb, B_RG_EMPTY + sl), (d & ~2) == 0 ? 2 : 1, lane);
    };
    if (which && up) skip();
    uint32_t ks = take();
    TS(62 + which);
    TR(20);
    prep_qk(sb + ks * SLOT);
    turn_begin();
    wg_fence();
#pragma unroll
    for (int kk = 0; kk < 16; kk++)
      wgmma_rs_n64(s, pk[4 * kk], pk[4 * kk + 1], pk[4 * kk + 2], pk[4 * kk + 3], desc_add(dk, (kk >> 2) * 8192 + (kk & 3) * 32), kk != 0);
    wg_commit();
    turn_end();
    TR(21);
    if (!which && (up || !CV_FX)) conv_finish();
    TR(23);
    if (which) mbar_wait(st_empty, 0);
    if ((which || !CV_QX) && !up) store_blocks<0, Q_PRE>(qreg, lb, pk);
    TR(24);
    wg_wait<0>();
    TR(22);
    reg_fence(s);
    reg_fence(pk);
    give(ks, fd);
    fd += dir;
    if (which && up) { skip(); store_blocks<0, 4>(qreg, lb, pk); }
    if (which || nw == 1) mask_diag();
    row_max(b0, b1);
    if ((which || !CV_QX) && !up) store_blocks<16 * Q_PRE, 4 - Q_PRE>(qreg + Q_PRE * 8192, lb, pk);
    b0 *= -SC; b1 *= -SC;
#pragma unroll
    for (int i = 0; i < 128; i++) acc[i] = 0.f;
    exps(pa, l0, l1);
    if (CV_FX && !which && !up) conv_finish();
    if (which && nw == 1) { fence_async_smem(); warp_arrive(bar_addr(sb, B_QFREE + w), lane); }
#pragma unroll 1
    for (int jj = 1; jj < nw; jj++) {
      ks = take();
      const uint32_t vs = take();
      if (jj == 1) fence_async_smem();
      TR(30);
#pragma unroll
      for (int i = 0; i < 32; i++) s[i] = 0.f;
      prep_qk(sb + ks * SLOT);
      prep_pv(sb + vs * SLOT);
      turn_begin();
      wg_fence();
      issue_qk();
      wg_commit();
      issue_pv(1);
      wg_commit();
      turn_end();
      TR(31);
      wg_wait<1>();
      TR(32);
      reg_fence(s);
      give(ks, fd);
      if (jj == nw - 1) {
        if (!which) mask_diag();
        else if (lane == 0) mbar_arrive(bar_addr(sb, B_QFREE + w));
      }
      uint32_t pn[16];
      float t0, t1, a0 = 1.f, a1 = 1.f;
      exps(pn, t0, t1);
      const bool redo = __any_sync(0xffffffffu, !(t0 + t1 <= 65536.f));
      if (redo) {
        row_max(a0, a1);
        const float c0 = fminf(b0, -SC * a0), c1 = fminf(b1, -SC * a1);
        a0 = ex2(c0 - b0); a1 = ex2(c1 - b1);
        b0 = c0; b1 = c1;
        l0 *= a0; l1 *= a1;
        exps(pn, t0, t1);
      }
      l0 += t0; l1 += t1;
      wg_wait<0>();
      reg_fence(acc);
      reg_fence(pa);
      give(vs, fd + dir);
      fd += 2 * dir;
      if (redo) {
#pragma unroll
        for (int i = 0; i < 32; i++) { acc[4 * i] *= a0; acc[4 * i + 1] *= a0; acc[4 * i + 2] *= a1; acc[4 * i + 3] *= a1; }
      }
#pragma unroll
      for (int i = 0; i < 16; i++) pa[i] = (i & 1) ? pn[i] ^ (one - 1) : pn[i] * one;
    }
    if (!which && up) skip();
    const uint32_t vs = take();
    TR(40);
    prep_pv(sb + vs * SLOT);
    turn_begin();
    wg_fence();
    issue_pv(1);
    wg_commit();
    turn_end();
    TR(41);
    if (!which && up) r.next();
    ws = take();
    l0 += __shfl_xor_sync(0xffffffffu, l0, 1); l1 += __shfl_xor_sync(0xffffffffu, l1, 1);
    l0 += __shfl_xor_sync(0xffffffffu, l0, 2); l1 += __shfl_xor_sync(0xffffffffu, l1, 2);
    float i0, i1;
    asm volatile("rcp.approx.ftz.f32 %0, %1;" : "=f"(i0) : "f"(l0));
    asm volatile("rcp.approx.ftz.f32 %0, %1;" : "=f"(i1) : "f"(l1));
    uint32_t xs = 0;
    if (!which) xs = take();
    wg_wait<0>();
    TR(42);
    reg_fence(acc);
    reg_fence(pa);
    give(vs, fd);
    TS(7 + 3 * which);
#pragma unroll
    for (int i = 0; i < 32; i++) {
      pk[2 * i]     = pack_bf16(acc[4 * i] * i0, acc[4 * i + 1] * i0);
      pk[2 * i + 1] = pack_bf16(acc[4 * i + 2] * i1, acc[4 * i + 3] * i1);
    }
    TS(8 + 3 * which); TR(46);
    if (which) break;
    TS(31);
    uint32_t xaddr = sb + xs * SLOT + (w ^ 1) * 8192;
#pragma unroll 1
    for (int kc = 0;; kc++) {
      TR(11);
      const uint64_t da = desc_k(xaddr), db = desc_mn(sb + ws * SLOT);
      turn_begin();
      wg_fence();
#pragma unroll
      for (int kk = 0; kk < 4; kk++) wgmma_ss_n256_tb(acc, desc_add(da, kk * 32), desc_add(db, kk * 2048), (kc | kk) != 0);
      wg_commit();
      turn_end();
      TR(13);
      const int cb = kc;
      if (cb >= 1 && cb <= 4) { fence_async_smem(); warp_arrive(bar_addr(sb, B_CTXS + 4 * w + cb - 1), lane); }
      if ((unsigned)cb < 4) {
        if (cb & 2) { if (cb & 1) store_blocks<48, 1>(qreg + 24576, lb, pk); else store_blocks<32, 1>(qreg + 16384, lb, pk); }
        else        { if (cb & 1) store_blocks<16, 1>(qreg + 8192, lb, pk);  else store_blocks<0, 1>(qreg, lb, pk); }
      }
      TR(15);
      wg_wait<0>();
      release(bar_addr(sb, B_RG_EMPTY + ws), lane);
      if (!(kc & 1)) release(bar_addr(sb, B_RG_EMPTY + xs), lane);
      if (kc == 6) break;
      ws = take();
      if (!(kc & 1)) { xs = take(); xaddr = sb + xs * SLOT + (w ^ 1) * 8192; } else xaddr += 16384;
    }
    reg_fence(acc);
    TS(61); TR(16);
#pragma unroll
    for (int i = 0; i < 64; i++) pk[i] = pack_bf16(acc[2 * i], acc[2 * i + 1]);
    TS(9); TR(19);
    qt = 15 - qt;
  }

  {
    float oa[32], ob[32];
#pragma unroll
    for (int i = 0; i < 32; i++) { oa[i] = 0.f; ob[i] = 0.f; }
    auto stage_o = [&](float (&o)[32], int ch) {
      reg_fence(o);
      uint32_t q[16];
#pragma unroll
      for (int i = 0; i < 16; i++) q[i] = pack_bf16(o[2 * i], o[2 * i + 1]);
      if (ch >= 2) mbar_wait(bar_addr(sb, B_S2_EMPTY + w * 2 + (ch & 1)), ((ch >> 1) - 1) & 1);
      store_blocks<0, 1>(qreg + (ch & 1) * 8192, lb, q);
    };
    auto hand_over = [&](int ch) {
      fence_async_smem();
      warp_arrive(bar_addr(sb, B_S2_FULL + w * 2 + (ch & 1)), lane);
    };
    uint32_t pk2[64];
    uint32_t p2 = 0;
    auto chunk = [&](int ch, auto first, float (&o)[32], float (&oprev)[32]) {
      constexpr bool FIRST = decltype(first)::value;
      const uint32_t s1 = FIRST ? ws : take();
      TR(50);
      const uint64_t d1 = desc_mn(sb + s1 * SLOT);
      turn_begin();
      wg_fence();
#pragma unroll
      for (int kk = 0; kk < 16; kk++) {
        wgmma_rs_n64_tb(o, pk[4 * kk], pk[4 * kk + 1], pk[4 * kk + 2], pk[4 * kk + 3], desc_add(d1, kk * 2048), kk != 0);
        if (kk == ARRIVE_KK) turn_end();
      }
      wg_commit();
      TR(51);
      if constexpr (!FIRST) {
        wg_wait<1>();
        release(bar_addr(sb, B_RG_EMPTY + p2), lane);
        stage_o(oprev, ch - 1);
      } else {
        mbar_wait(bar_addr(sb, B_CTXF + w), 0);
#pragma unroll
        for (int kk = 0; kk < 16; kk++) {
          uint32_t f[4];
          ldsm4(f, qreg + (kk >> 2) * 8192 + (lb ^ ((kk & 3) << 5)));
          pk2[4 * kk] = f[0]; pk2[4 * kk + 1] = f[1]; pk2[4 * kk + 2] = f[2]; pk2[4 * kk + 3] = f[3];
        }
      }
      const uint32_t s2 = take();
      TR(53);
      const uint64_t d2 = desc_mn(sb + s2 * SLOT);
      turn_begin();
      wg_fence();
#pragma unroll
      for (int kk = 0; kk < 16; kk++) {
        wgmma_rs_n64_tb(o, pk2[4 * kk], pk2[4 * kk + 1], pk2[4 * kk + 2], pk2[4 * kk + 3], desc_add(d2, kk * 2048), 1);
        if (kk == ARRIVE_KK && (ch < 6 || w == 1)) turn_end();
      }
      wg_commit();
      TR(54);
      if (!FIRST) hand_over(ch - 1);
      wg_wait<1>();
      TR(55);
      release(bar_addr(sb, B_RG_EMPTY + s1), lane);
      p2 = s2;
    };
    chunk(0, Int<1>(), oa, ob);
#pragma unroll 1
    for (int ch = 1; ch < 7; ch += 2) { chunk(ch, Int<0>(), ob, oa); chunk(ch + 1, Int<0>(), oa, ob); }
    wg_wait<0>();
    TR(58);
    reg_fence(pk);
    reg_fence(pk2);
    stage_o(oa, 6);
    hand_over(6);
  }
  TS(12); TR(59);
  if (threadIdx.x == 128) ST(14);
  if ((threadIdx.x & 127) == 0) GT(54 + w);

  TS(16); TS(18); TS(17);
  TR(99); TR_END();
  TS(13); TSG(14);
}

#define CONV_STAGGER_NS 1200
namespace ssm {
#define CONV_GROUPS (D_SPARE / 8 / NCONV)
constexpr int GROUPS = CONV_GROUPS;
constexpr uint32_t ZROWS = 16;
constexpr uint32_t CHAN = (ZROWS + 256 + 1) * 16;
constexpr uint32_t XBUF = 8 * CHAN;
constexpr uint32_t OFF_X = 0;
constexpr uint32_t HCOPY = 4160;
constexpr uint32_t OFF_H = 2 * XBUF;
constexpr uint32_t HWARP = 3 * HCOPY;
constexpr uint32_t IO_K = 128, IO_V = IO_K + 4096, IO_Q = IO_V + 4096, IOBUF = IO_Q + 4096;
constexpr uint32_t OFF_IO = (OFF_H + 8 * HWARP + 127) / 128 * 128;
constexpr uint32_t END = OFF_IO + 4 * IOBUF;
static_assert(IOBUF % 128 == 0 && OFF_H % 16 == 0, "TMA destination alignment");
static_assert(END <= BARS, "smem");
enum : uint32_t { B_XREADY = 0, B_ZDONE = 2, B_KV = 4, B_Q = 8, B_HRAW = 12, B_QLAST = 20 };
constexpr int CW_BAR = 4;

__device__ __forceinline__ int group_d0(int cidx, int grp) { return (grp * NCONV + cidx) * 8; }
__device__ __forceinline__ uint32_t x_lane(int lane) { return (lane & 7) * CHAN + (ZROWS + (lane >> 3)) * 16; }
__device__ __forceinline__ uint32_t t_lane(int lane) { return (uint32_t)(8 * (lane >> 3) + 7 - (lane & 7)) * 16; }
struct Taps { uint32_t s[4]; };
__device__ __forceinline__ Taps load_taps(const Params& p, int d0, int c) {
  const uint2 s0 = __ldg(reinterpret_cast<const uint2*>(p.a_shift + (d0 + 2 * c) * 4)), s1 = __ldg(reinterpret_cast<const uint2*>(p.a_shift + (d0 + 2 * c + 1) * 4));
  return Taps{{__byte_perm(s0.x, s1.x, 0x5410), __byte_perm(s0.x, s1.x, 0x7632), __byte_perm(s0.y, s1.y, 0x5410), __byte_perm(s0.y, s1.y, 0x7632)}};
}
__device__ __forceinline__ uint32_t short_conv(const Taps& t, uint32_t k0, uint32_t k1, uint32_t k2, uint32_t k3, uint32_t v) {
  return bmul(bfma(k3, t.s[0], bfma(k2, t.s[1], bfma(k1, t.s[2], bmul(k0, t.s[3])))), v);
}
__device__ __forceinline__ void gate_chunk(uint32_t xa, uint32_t qa) {
#pragma unroll 4
  for (int i = 0; i < 8; i++) {
    uint32_t zz[4], qq[4];
    ldsm4t(zz, xa + i * 64);
    ldsm4(qq, qa + i * 512);
    stsm4(qa + i * 512, bmul(qq[0], zz[0]), bmul(qq[1], zz[1]), bmul(qq[2], zz[2]), bmul(qq[3], zz[3]));
  }
}

__device__ __forceinline__ void io_warp(const Params& p, uint32_t sb, int cidx, int wq) {
  const int lane = threadIdx.x & 31;
  const uint32_t io = sb + OFF_IO + wq * IOBUF, bkv = bar_addr(sb, B_KV + wq), bq = bar_addr(sb, B_Q + wq);
  auto load_kv = [&](int e) {
    __syncwarp();
    if (lane != 0) return;
    const int d0 = group_d0(cidx, e >> 1), row = (2 * wq + (e & 1)) * 256;
    if (e < 2 * GROUPS) {
      mbar_expect_tx(bkv, IO_Q);
      tma_ld2(io, &p.ak8, bkv, d0, row - 8);
      tma_ld2(io + IO_K, &p.ak, bkv, d0, row);
      tma_ld2(io + IO_V, &p.av, bkv, d0, row);
    } else {
      const uint32_t bar = bar_addr(sb, B_QLAST + 2 * wq + 1);
      mbar_expect_tx(bar, 4096);
      tma_ld2(io + IO_K, &p.aq, bar, group_d0(cidx, GROUPS - 1), row + 256);
    }
  };
  auto load_q = [&](int e) {
    __syncwarp();
    if (lane != 0) return;
    const uint32_t bar = e < 2 * GROUPS - 2 ? bq : bar_addr(sb, B_QLAST + 2 * wq);
    mbar_expect_tx(bar, 4096);
    tma_ld2(io + IO_Q, &p.aq, bar, group_d0(cidx, e >> 1), (2 * wq + (e & 1)) * 256);
  };
  TR_DECL;
  TR(0);
  load_kv(0);
  const uint32_t xl = sb + OFF_X + x_lane(lane) + wq * 1024, tl = io + t_lane(lane);
#pragma unroll 1
  for (int grp = -2; grp + 1 < GROUPS; grp++) {
    const bool more = grp + 2 < GROUPS;
    const Taps taps = load_taps(p, group_d0(cidx, more ? grp + 2 : 0), lane & 3);
    PCLK(c0);
    if (grp >= 0) mbar_wait_nap(bar_addr(sb, B_ZDONE + (grp & 1)), (grp >> 1) & 1);
    PACC(tp, c0);
    PCLK(c1);
    TR(80);
#pragma unroll 1
    for (int i = 0; i < 2; i++) {
      const uint32_t xa = xl + (grp & 1) * XBUF + i * 512;
      if (grp >= 0) {
        mbar_wait_nap(bq, i);
        TR(81);
        gate_chunk(xa, tl + IO_Q);
      }
      if (more) {
        TR(82);
        mbar_wait_nap(bkv, i);
        TR(83);
#pragma unroll 2
        for (int u = 0; u < 8; u++) {
          const uint32_t ka = tl + IO_K + u * 512;
          uint32_t k0[4], k1[4], k2[4], k3[4], vv[4];
          ldsm4(k0, ka - 48); ldsm4(k1, ka - 32); ldsm4(k2, ka - 16); ldsm4(k3, ka); ldsm4(vv, ka + 4096);
          stsm4t(xa + u * 64, short_conv(taps, k0[0], k1[0], k2[0], k3[0], vv[0]), short_conv(taps, k0[1], k1[1], k2[1], k3[1], vv[1]),
                 short_conv(taps, k0[2], k1[2], k2[2], k3[2], vv[2]), short_conv(taps, k0[3], k1[3], k2[3], k3[3], vv[3]));
        }
        load_kv(2 * (grp + 2) + i + 1);
        TR(84);
        if (i == 1) warp_arrive(bar_addr(sb, B_XREADY + (grp & 1)), lane);
      }
      if (grp >= 0) {
        fence_async_smem();
        __syncwarp();
        if (lane == 0) {
          tma_st2(&p.ao, io + IO_Q, group_d0(cidx, grp), (2 * wq + i) * 256);
          bulk_commit();
          bulk_wait_read();
        }
      }
      if (2 * grp + i + 1 >= 0) load_q(2 * grp + i + 1);
      TR(85);
    }
    PACC(te, c1);
  }
  if (lane == 0) bulk_wait_all();
  TR(99); TR_END();
}

__device__ __forceinline__ void conv_warp(const Params& p, uint32_t sb, int cidx, int ch) {
  const int lane = threadIdx.x & 31;
  const uint32_t hE0 = sb + OFF_H + ch * HWARP, hO = hE0 + HCOPY;
  const uint32_t hbar = bar_addr(sb, B_HRAW + ch);
  auto fetch_h = [&](int grp) {
    if (lane == 0) {
      mbar_expect_tx(hbar, 4096);
      asm volatile("cp.async.bulk.shared::cluster.global.mbarrier::complete_tx::bytes [%0], [%1], %2, [%3];"
                   :: "r"(hE0 + (grp & 1) * 2 * HCOPY + 32), "l"(p.a_ssmk + (size_t)(group_d0(cidx, grp) + ch) * SEQ), "r"(4096), "r"(hbar) : "memory");
    }
  };
  TR_DECL;
  TR(0);
  fetch_h(0);
#pragma unroll 1
  for (int grp = 0; grp < GROUPS; grp++) {
    const uint32_t xc = sb + OFF_X + (grp & 1) * XBUF + ch * CHAN;
    const uint32_t Dd = (uint32_t)__ldg(reinterpret_cast<const unsigned short*>(p.a_D + group_d0(cidx, grp) + ch)) * 0x10001u;
    PCLK(k0);
    mbar_wait(hbar, grp & 1);
    const uint32_t hE = hE0 + (grp & 1) * 2 * HCOPY;
    if (grp + 1 < GROUPS) fetch_h(grp + 1);
#pragma unroll
    for (int i = 0; i < 8; i++) {
      const uint32_t o = 32 + (i * 32 + lane) * 16;
      const uint4 w = lds16(hE + o);
      const uint32_t nx = lds4(hE + o + 16);
      sts16(hO + o, __byte_perm(w.x, w.y, 0x5432), __byte_perm(w.y, w.z, 0x5432), __byte_perm(w.z, w.w, 0x5432), __byte_perm(w.w, nx, 0x5432));
      if (o == 32) asm volatile("st.shared.u32 [%0], %1;" :: "r"(hO + 28), "r"(w.x << 16) : "memory");
    }
    __syncwarp();
    const uint32_t ha = cv_h_lane(lane, hE, hO), xa = xc + cv_x_lane(lane);
    TR(71);
    mbar_wait(bar_addr(sb, B_XREADY + (grp & 1)), (grp >> 1) & 1);
    TR(72);
    if (grp == 0 && ch >= 4) __nanosleep(CONV_STAGGER_NS);
    PACC(tw, k0);
    PCLK(k1);
    float acc[16][4];
#pragma unroll
    for (int i = 0; i < 16; i++) { acc[i][0] = 0.f; acc[i][1] = 0.f; acc[i][2] = 0.f; acc[i][3] = 0.f; }
#pragma unroll 1
    for (int r = 0; r < 8; r++) {
      uint32_t fx[16][4], fh[16][2];
#pragma unroll
      for (int i = 0; i < 16; i++) { fh[i][0] = lds4(ha + i * 256 + r * 32); fh[i][1] = lds4(ha + i * 256 + r * 32 + 16); }
#pragma unroll
      for (int i = 0; i < 16; i++) ldsm4(fx[i], xa + i * 256 - r * 32);
#pragma unroll
      for (int sx = 0; sx < 16; sx++)
#pragma unroll
        for (int jj = 0; jj < 16 - sx; jj++) mma16816(acc[jj + sx], fx[sx], fh[jj][0], fh[jj][1]);
    }
    PACC(tm, k1);
    PCLK(k2);
    TR(73);
#pragma unroll
    for (int i = 0; i < 8; i++) {
      uint32_t x[4];
      const uint32_t ad = xc + (ZROWS + lane) * 16 + i * 512;
      ldsm4(x, ad);
      stsm4(ad, badd(pack_bf16(acc[2 * i][0], acc[2 * i][1]), bmul(x[0], Dd)), badd(pack_bf16(acc[2 * i][2], acc[2 * i][3]), bmul(x[1], Dd)),
            badd(pack_bf16(acc[2 * i + 1][0], acc[2 * i + 1][1]), bmul(x[2], Dd)), badd(pack_bf16(acc[2 * i + 1][2], acc[2 * i + 1][3]), bmul(x[3], Dd)));
    }
    if (grp + 1 < GROUPS) warp_arrive(bar_addr(sb, B_ZDONE + (grp & 1)), lane);
    PACC(tr, k2);
    TR(74);
  }
  {
    mbar_wait(bar_addr(sb, B_QLAST + ch), 0);
    named_sync(CW_BAR, 256);
    TR(75);
    const uint32_t qb = sb + OFF_IO + (ch >> 1) * IOBUF + ((ch & 1) ? IO_K : IO_Q);
    gate_chunk(sb + OFF_X + ((GROUPS - 1) & 1) * XBUF + x_lane(lane) + ch * 512, qb + t_lane(lane));
    fence_async_smem();
    __syncwarp();
    if (lane == 0) { tma_st2(&p.ao, qb, group_d0(cidx, GROUPS - 1), ch * 256); bulk_commit(); bulk_wait_all(); }
    TR(99); TR_END();
  }
}

__device__ __forceinline__ void init(uint32_t sb) {
  if (threadIdx.x < 16 * ZROWS) sts16(sb + OFF_X + (threadIdx.x >> 4) * CHAN + (threadIdx.x & 15) * 16, 0, 0, 0, 0);
  if (threadIdx.x < 96) sts16(sb + OFF_H + (threadIdx.x >> 2) * HCOPY + (threadIdx.x & 1) * 16 + ((threadIdx.x & 2) ? 4128 : 0), 0, 0, 0, 0);
  if (threadIdx.x == 0) {
    for (int i = 0; i < 2; i++) { mbar_init(bar_addr(sb, B_XREADY + i), 4); mbar_init(bar_addr(sb, B_ZDONE + i), 8); }
    for (int i = 0; i < 4; i++) { mbar_init(bar_addr(sb, B_KV + i), 1); mbar_init(bar_addr(sb, B_Q + i), 1); }
    for (int i = 0; i < 8; i++) { mbar_init(bar_addr(sb, B_HRAW + i), 1); mbar_init(bar_addr(sb, B_QLAST + i), 1); }
    fence_async_smem();
  }
  named_sync(0, NTHREADS);
}
}

__device__ __forceinline__ void ssm_side_work(const Params& p, uint32_t sb, unsigned epoch) {
  const Role ro = get_role();
  const int h = ro.h, j = ro.j;
  const int lane = threadIdx.x & 31, g = lane >> 2, c = lane & 3;
  const int d0 = D_SPARE + 8 * h;
  uint8_t* xs = g_xs + (size_t)(h * 8 + g) * CV_BYTES + c * 4;
  auto xrow = [&](int beta) { return xs + (16 + beta) * 16; };
  {
    const uint4* hp = reinterpret_cast<const uint4*>(p.a_ssmk + (size_t)(d0 + j) * SEQ) + lane;
    uint8_t* he = g_xs + (size_t)(h * 8 + j) * CV_BYTES + CV_HE;
#pragma unroll 2
    for (int i = 0; i < 8; i++) {
      const uint4 wv = __ldg(hp + i * 32);
      const uint32_t nx = i * 32 + lane < 255 ? __ldg(reinterpret_cast<const uint32_t*>(hp + i * 32 + 1)) : 0u;
      const uint32_t o = 32 + (i * 32 + lane) * 16;
      *reinterpret_cast<uint4*>(he + o) = wv;
      *reinterpret_cast<uint4*>(he + CV_HCOPY + o) =
          make_uint4(__byte_perm(wv.x, wv.y, 0x5432), __byte_perm(wv.y, wv.z, 0x5432), __byte_perm(wv.z, wv.w, 0x5432), __byte_perm(wv.w, nx, 0x5432));
      if (o == 32) *reinterpret_cast<uint32_t*>(he + CV_HCOPY + 28) = wv.x << 16;
    }
    if (lane == 0) *reinterpret_cast<uint32_t*>(he + CV_D - CV_HE) = (uint32_t)__ldg(reinterpret_cast<const unsigned short*>(p.a_D + d0 + j)) * 0x10001u;
  }
  {
    const ssm::Taps taps = ssm::load_taps(p, d0, c);
    const uint32_t* kp = reinterpret_cast<const uint32_t*>(p.a_k + (size_t)(256 * j + 7 - g) * DA + d0) + c;
    const uint32_t* vp = reinterpret_cast<const uint32_t*>(p.a_v + (size_t)(256 * j + 7 - g) * DA + d0) + c;
    uint32_t kprev = j > 0 ? __ldg(kp - 8 * (DA / 2)) : 0u;
#pragma unroll 1
    for (int i0 = 0; i0 < 32; i0 += 8) {
      uint32_t kk[8], vv[8];
#pragma unroll
      for (int i = 0; i < 8; i++) { kk[i] = __ldg(kp + (i0 + i) * 8 * (DA / 2)); vv[i] = __ldg(vp + (i0 + i) * 8 * (DA / 2)); }
#pragma unroll
      for (int i = 0; i < 8; i++) {
        const uint32_t k2 = __shfl_sync(0xffffffffu, g < 1 ? kprev : kk[i], (lane + 4) & 31);
        const uint32_t k1 = __shfl_sync(0xffffffffu, g < 2 ? kprev : kk[i], (lane + 8) & 31);
        const uint32_t k0 = __shfl_sync(0xffffffffu, g < 3 ? kprev : kk[i], (lane + 12) & 31);
        *reinterpret_cast<uint32_t*>(xrow(32 * j + i0 + i)) = transpose8(ssm::short_conv(taps, k0, k1, k2, kk[i], vv[i]));
        kprev = kk[i];
      }
    }
    __syncwarp();
    if (lane == 0) {
      flag_signal(&g_flags.xs_ready[h].v);
      flag_wait(&g_flags.xs_ready[h].v, 8, epoch);
      fence_async_all();
      mbar_arrive(bar_addr(sb, B_XS));
    }
  }
  if (lane == 0) {
    for (int i = 0; i < 3; i++) {
      flag_wait(&g_flags.kv_ready[3 * h + i].v, 16, epoch);
      fence_async_all();
      mbar_arrive(bar_addr(sb, B_KV + i));
    }
    mbar_wait_nap(bar_addr(sb, B_CONV), 0);
    flag_signal(&g_flags.zs_ready[h].v);
    flag_wait(&g_flags.zs_ready[h].v, 8, epoch);
    asm volatile("red.relaxed.gpu.global.add.u64 [%0], 1;" :: "l"(&g_flags.done) : "memory");
  }
  __syncwarp();
  fence_async_all();
  const uint32_t qb = q_region(sb, 1) + 16384, zb = qb + 4096, bar = bar_addr(sb, B_GATE);
  constexpr uint32_t ZCH = 528;
  mbar_wait_slow(bar_addr(sb, B_GFREE), 0);
  if (lane == 0) { mbar_expect_tx(bar, 8192); tma_ld2(qb, &p.aq, bar, d0, 256 * j); }
  __syncwarp();
  if (lane < 8) bulk_ld(zb + lane * ZCH, g_xs + (size_t)(h * 8 + lane) * CV_BYTES + (16 + 32 * j) * 16, 512, bar);
  mbar_wait(bar, 0);
  ssm::gate_chunk(zb + (lane & 7) * ZCH + (lane >> 3) * 16, qb + ssm::t_lane(lane));
  fence_async_smem();
  __syncwarp();
  if (lane == 0) { tma_st2(&p.ao, qb, d0, 256 * j); bulk_commit(); bulk_wait_all(); }
}

__global__ void __cluster_dims__(2, 1, 1) __launch_bounds__(NTHREADS, 1)
concat_heads__ssm_conv_h3__compressed_kv_cla__prompt_kernel(uint8_t* xs, uint32_t one, const __grid_constant__ Params p) {
  if (threadIdx.x == 0) { prefetch_map(&p.wuk); prefetch_map(&p.ckv); }
  extern __shared__ uint8_t smem_raw[];
  if (threadIdx.x == 96) { ST(0); STG_(10); }
  const uint32_t sb = (smem_u32(smem_raw) + 1023) & ~1023u;
  const int warp = __shfl_sync(0xffffffffu, threadIdx.x >> 5, 0);
  const int wg = warp >> 2;
  const int cta = blockIdx.x;
  const bool attn = cta < NMAIN;
  if (attn && (threadIdx.x >> 5) == 4) {
    const Role ro = get_role();
    auto load = [&](int k) {
      const uint32_t full = bar_addr(sb, B_P1_FULL + k), dst = sb + k * P1_STAGE;
      mbar_expect_tx(full, P1_STAGE);
      tma_ld2(dst, &p.ckv, full, k * 64, kv_block(ro.j, 0) * 128);
      tma_ld3(dst + 16384, &p.wuk, full, 0, k * 64, ro.h * 4);
    };
    if (threadIdx.x == 128) {
      for (int i = 0; i < 4; i++) mbar_init(bar_addr(sb, B_P1_FULL + i), 1);
      asm volatile("fence.mbarrier_init.release.cluster;" ::: "memory");
      ST(1);
      load(0);
    }
    __syncwarp();
    named_arrive(0, NTHREADS);
    if (threadIdx.x == 128) {
      for (int k = 1; k < EARLY_LD; k++) load(k);
      ST(2);
    }
    __syncwarp();
  }
  const int lane = threadIdx.x & 31;
  if (wg == 0) {
    if (!attn) {
      asm volatile("setmaxnreg.dec.sync.aligned.u32 72;");
      if (threadIdx.x == 0) GT(0);
      if (one) { ssm::init(sb); ssm::io_warp(p, sb, cta - NMAIN, fresh_warp()); }
      if (threadIdx.x == 0) GT(14);
      return;
    }
    asm volatile("setmaxnreg.dec.sync.aligned.u32 40;");
    named_arrive(PP_BAR + 1, 256);
    if (warp == 2) {
      if (lane == 0) {
        for (int i = 0; i < 4; i++) mbar_init(bar_addr(sb, B_P1_EMPTY + i), 8);
        for (int i = 0; i < NSLOT; i++) {
          mbar_init(bar_addr(sb, B_RG_FULL + i), 1); mbar_init(bar_addr(sb, B_RG_EMPTY + i), 8);
        }
        for (int i = 0; i < 2; i++) { mbar_init(bar_addr(sb, B_ST_FULL + i), 4); mbar_init(bar_addr(sb, B_ST_EMPTY + i), 1); }
        mbar_init(bar_addr(sb, B_XS), 1); mbar_init(bar_addr(sb, B_CONV), 8); mbar_init(bar_addr(sb, B_GATE), 1); mbar_init(bar_addr(sb, B_GFREE), 1);
        for (int i = 0; i < 3; i++) mbar_init(bar_addr(sb, B_KV + i), 1);
        for (int i = 0; i < 8; i++) mbar_init(bar_addr(sb, B_CTXS + i), 4);
        for (int i = 0; i < 4; i++) { mbar_arrive(bar_addr(sb, B_RG_FULL + i)); if (i < 3) mbar_arrive_n(bar_addr(sb, B_RG_EMPTY + i), 8); }
        for (int i = 0; i < 4; i++) { mbar_init(bar_addr(sb, B_S2_FULL + i), 4); mbar_init(bar_addr(sb, B_S2_EMPTY + i), 1); }
        for (int i = 0; i < 2; i++) { mbar_init(bar_addr(sb, B_QFREE + i), 4); mbar_init(bar_addr(sb, B_CTXF + i), 1); }
        asm volatile("fence.mbarrier_init.release.cluster;" ::: "memory");
        ST(3);
      }
      __syncwarp();
      named_arrive(0, NTHREADS);
    } else {
      named_sync(0, NTHREADS);
    }
    if (threadIdx.x == 96) ST(4);
    if (warp == 0) {
      if (lane == 0) producer_main(p, sb);
    } else if (warp < 3) {
      storer_main(p, sb);
    } else {
      const unsigned epoch = load_epoch();
      mbar_wait(bar_addr(sb, B_P1_FULL + 3), 0);
      __nanosleep(SIDE_DELAY_NS);
      ssm_side_work(p, sb, epoch);
    }
  } else {
    if (attn) {
      asm volatile("setmaxnreg.inc.sync.aligned.u32 232;");
      if (threadIdx.x == 256) ST(5);
      if (one) consumer_main(p, sb, xs, one);
    } else {
      asm volatile("setmaxnreg.inc.sync.aligned.u32 216;");
      if (threadIdx.x == 128) { GT(12); PT(10); }
      if (one) { ssm::init(sb); ssm::conv_warp(p, sb, cta - NMAIN, fresh_warp() - 4); }
      if (threadIdx.x == 128) { PT(9); GT(13); }
    }
  }
}

typedef CUresult (*EncodeTiledFn)(CUtensorMap*, CUtensorMapDataType, cuuint32_t, void*, const cuuint64_t*, const cuuint64_t*,
                                  const cuuint32_t*, const cuuint32_t*, CUtensorMapInterleave, CUtensorMapSwizzle,
                                  CUtensorMapL2promotion, CUtensorMapFloatOOBfill);

void make_map(EncodeTiledFn enc, CUtensorMap* m, const void* ptr, int rank, const uint64_t* dims, const uint64_t* strides, const uint32_t* box) {
  cuuint64_t d[3], s[2]; cuuint32_t b[3], e[3] = {1, 1, 1};
  for (int i = 0; i < rank; i++) { d[i] = dims[i]; b[i] = box[i]; if (i) s[i - 1] = strides[i - 1]; }
  enc(m, CU_TENSOR_MAP_DATA_TYPE_BFLOAT16, rank, const_cast<void*>(ptr), d, s, b, e, CU_TENSOR_MAP_INTERLEAVE_NONE,
      CU_TENSOR_MAP_SWIZZLE_128B, CU_TENSOR_MAP_L2_PROMOTION_L2_256B, CU_TENSOR_MAP_FLOAT_OOB_FILL_NONE);
}
void map2(EncodeTiledFn enc, CUtensorMap* m, const void* ptr, uint64_t cols, uint64_t rows, uint32_t bc, uint32_t br) {
  const uint64_t dims[2] = {cols, rows}, st[1] = {cols * 2}; const uint32_t box[2] = {bc, br};
  make_map(enc, m, ptr, 2, dims, st, box);
}
void map2_plain(EncodeTiledFn enc, CUtensorMap* m, const void* ptr, uint64_t cols, uint64_t rows, uint32_t bc, uint32_t br) {
  cuuint64_t d[2] = {cols, rows}, st[1] = {cols * 2}; cuuint32_t b[2] = {bc, br}, e[2] = {1, 1};
  enc(m, CU_TENSOR_MAP_DATA_TYPE_BFLOAT16, 2, const_cast<void*>(ptr), d, st, b, e, CU_TENSOR_MAP_INTERLEAVE_NONE,
      CU_TENSOR_MAP_SWIZZLE_NONE, CU_TENSOR_MAP_L2_PROMOTION_L2_128B, CU_TENSOR_MAP_FLOAT_OOB_FILL_NONE);
}
void map3(EncodeTiledFn enc, CUtensorMap* m, const void* ptr, uint64_t rows, uint32_t nblk) {
  const uint64_t dims[3] = {64, rows, 64}, st[2] = {8192, 128}; const uint32_t box[3] = {64, 64, nblk};
  make_map(enc, m, ptr, 3, dims, st, box);
}

}

extern "C" void kernel_launch(void* const* d_in, const int* in_sizes, int n_in, void* d_out, int out_size) {
  (void)in_sizes; (void)n_in; (void)out_size;
  static EncodeTiledFn enc = nullptr;
  static void *kv_ptr = nullptr, *acc_ptr = nullptr, *xs_ptr = nullptr;
  if (!enc) {
    void* fn = nullptr; cudaDriverEntryPointQueryResult qr;
    cudaGetDriverEntryPoint("cuTensorMapEncodeTiled", &fn, cudaEnableDefault, &qr);
    enc = (EncodeTiledFn)fn;
    cudaGetSymbolAddress(&kv_ptr, g_kv);
    cudaGetSymbolAddress(&acc_ptr, g_ctx);
    cudaGetSymbolAddress(&xs_ptr, g_xs);
    cudaFuncSetAttribute(concat_heads__ssm_conv_h3__compressed_kv_cla__prompt_kernel, cudaFuncAttributeMaxDynamicSharedMemorySize, SMEM_BYTES);
  }
  Params p;
  p.a_q = (const bf16*)d_in[0]; p.a_k = (const bf16*)d_in[1]; p.a_v = (const bf16*)d_in[2];
  map2_plain(enc, &p.aq, d_in[0], DA, SEQ, 8, 256);
  map2_plain(enc, &p.ak, d_in[1], DA, SEQ, 8, 256);
  map2_plain(enc, &p.ak8, d_in[1], DA, SEQ, 8, 8);
  map2_plain(enc, &p.av, d_in[2], DA, SEQ, 8, 256);
  map2_plain(enc, &p.ao, d_out, OUTW, SEQ, 8, 256);
  p.a_shift = (const bf16*)d_in[3]; p.a_ssmk = (const bf16*)d_in[4]; p.a_D = (const bf16*)d_in[5];
  p.out = (bf16*)d_out; p.b_x = (const bf16*)d_in[6]; p.b_wo = (const bf16*)d_in[11];
  map2(enc, &p.x, d_in[6], DM, SEQ, 64, 128);
  map2(enc, &p.ckv, d_in[7], DC, SEQ, 64, 128);
  map3(enc, &p.wq, d_in[8], DM, 4);
  map2_plain(enc, &p.wqp, d_in[8], NH * HD, DM, 256, 4);
  map3(enc, &p.wuk, d_in[9], DC, 4);
  map3(enc, &p.wuv, d_in[10], DC, 4);
  map2(enc, &p.wo, d_in[11], DM, NH * HD, 64, 256);
  map2(enc, &p.part, d_out, OUTW, SEQ, 64, 64);
  p.kv = (uint8_t*)kv_ptr; p.ctx = (uint8_t*)acc_ptr;
  concat_heads__ssm_conv_h3__compressed_kv_cla__prompt_kernel<<<NCTA, NTHREADS, SMEM_BYTES>>>((uint8_t*)xs_ptr, 1u, p);
}
```

```cpp
#include <cuda_runtime.h>
#include <cuda_bf16.h>
#include <cuda.h>
#include <stdint.h>

namespace {

typedef __nv_bfloat16 bf16;

constexpr int SEQ  = 2048;
constexpr int DA   = 448;
constexpr int NH   = 16;
constexpr int HD   = 256;
constexpr int DM   = 448;
constexpr int DC   = 1024;
constexpr int OUTW = DA + DM;
constexpr int NMAIN = 128;
constexpr int NCONV = 4;
constexpr int NCTA  = NMAIN + NCONV;
constexpr int NTHREADS = 384;
constexpr int D_SPARE = 320;

__device__ __align__(1024) bf16 g_kv[2ull * SEQ * NH * HD];
__device__ __align__(1024) bf16 g_ctx[(size_t)NMAIN * 128 * HD];
constexpr uint32_t CV_HE = 272 * 16, CV_HCOPY = 4160, CV_D = CV_HE + 4144, CV_BYTES = CV_HE + 2 * CV_HCOPY;
__device__ __align__(128) uint8_t g_xs[NMAIN * CV_BYTES];
struct alignas(128) Flag { unsigned v; unsigned pad[31]; };
struct Flags {
  Flag kv_ready[3 * NH];
  Flag ctx_ready[NMAIN * 2];
  Flag out_ready[16 * 2];
  Flag xs_ready[NH];
  Flag zs_ready[NH];
  alignas(128) unsigned long long done;
};
__device__ Flags g_flags;
#define TS(i)
#define TSG(i)
#define GT(i)
#define PT(i)
#define WHICH_TS 0
#define PCLK(var)
#define PACC(acc, t0)
#define PDECL
#define PDUMP()

#define CP_DECL
#define CP()
#define ST(i)
#define STG_(i)
#define TR_DECL
#define TR(tag)
#define TR_END()
#define TRG(tag)

struct alignas(64) Params {
  CUtensorMap ckv;
  CUtensorMap wuk;
  CUtensorMap wuv;
  CUtensorMap x;
  CUtensorMap wq;
  CUtensorMap wqp;
  CUtensorMap part;
  CUtensorMap wo;
  CUtensorMap ak, ak8, av, aq, ao;
  const bf16 *a_q, *a_k, *a_v, *a_shift, *a_ssmk, *a_D, *b_x, *b_wo;
  bf16* out;
  uint8_t *kv, *ctx;
};

constexpr uint32_t P1_STAGE = 49152;
constexpr uint32_t P1_STG   = 196608;
constexpr uint32_t SLOT     = 32768;
constexpr int      NSLOT    = 5;
constexpr uint32_t QREG     = 163840;
constexpr uint32_t CV_X = 4 * SLOT + 16384, CV_R = 3 * SLOT;
static_assert(CV_BYTES <= 16384 && CV_BYTES % 128 == 0, "SSM operands");
constexpr uint32_t BARS     = 229376;
constexpr uint32_t SMEM_BYTES = BARS + 512 + 1024;
enum : uint32_t {
  B_P1_FULL = 0, B_P1_EMPTY = 4, B_RG_FULL = 8, B_RG_EMPTY = 13, B_ST_FULL = 18, B_ST_EMPTY = 20,
  B_XS = 22, B_S2_FULL = 28, B_S2_EMPTY = 32, B_QFREE = 36, B_CTXF = 38, B_KV = 40, B_GATE = 43, B_CTXS = 44, B_GFREE = 52, B_CONV = 53, B_COUNT = 54
};

__device__ __forceinline__ uint32_t smem_u32(const void* p) { return (uint32_t)__cvta_generic_to_shared(p); }
__device__ __forceinline__ void mbar_init(uint32_t bar, uint32_t cnt) {
  asm volatile("mbarrier.init.shared::cta.b64 [%0], %1;" :: "r"(bar), "r"(cnt) : "memory");
}
__device__ __forceinline__ void mbar_expect_tx(uint32_t bar, uint32_t bytes) {
  asm volatile("mbarrier.arrive.expect_tx.shared::cta.b64 _, [%0], %1;" :: "r"(bar), "r"(bytes) : "memory");
}
__device__ __forceinline__ void mbar_arrive(uint32_t bar) {
  asm volatile("mbarrier.arrive.shared::cta.b64 _, [%0];" :: "r"(bar) : "memory");
}
__device__ __forceinline__ void mbar_arrive_n(uint32_t bar, uint32_t n) {
  asm volatile("mbarrier.arrive.shared::cta.b64 _, [%0], %1;" :: "r"(bar), "r"(n) : "memory");
}
__device__ __forceinline__ void lane0_arrive(uint32_t bar, uint32_t n, int lane) {
  asm volatile("{\n.reg .pred p;\nsetp.eq.s32 p, %2, 0;\n@p mbarrier.arrive.shared::cta.b64 _, [%0], %1;\n}" :: "r"(bar), "r"(n), "r"(lane) : "memory");
}
__device__ __forceinline__ bool mbar_try(uint32_t bar, uint32_t parity) {
  uint32_t ok;
  asm volatile("{\n.reg .pred p;\nmbarrier.try_wait.parity.shared::cta.b64 p, [%1], %2;\nselp.u32 %0, 1, 0, p;\n}"
               : "=r"(ok) : "r"(bar), "r"(parity) : "memory");
  return ok;
}
#define FLAG_NS 100
#define NAP_NS 100
constexpr uint32_t SPIN_LIMIT = 1u << 24;
__device__ __forceinline__ void mbar_wait(uint32_t bar, uint32_t parity) {
  if (mbar_try(bar, parity)) return;
  uint32_t n = 0;
  while (!mbar_try(bar, parity)) { if (++n > SPIN_LIMIT) __trap(); }
}
__device__ __forceinline__ void mbar_wait_nap(uint32_t bar, uint32_t parity) {
  uint32_t n = 0;
  while (!mbar_try(bar, parity)) { if (++n > (SPIN_LIMIT >> 2)) __trap(); __nanosleep(NAP_NS); }
}
__device__ __forceinline__ void mbar_wait_slow(uint32_t bar, uint32_t parity) {
  uint32_t n = 0;
  while (!mbar_try(bar, parity)) { if (++n > (SPIN_LIMIT >> 4)) __trap(); __nanosleep(500); }
}
__device__ __forceinline__ unsigned load_epoch() {
  unsigned long long e; asm volatile("ld.relaxed.gpu.global.u64 %0, [%1];" : "=l"(e) : "l"(&g_flags.done) : "memory"); return (unsigned)(e / NMAIN);
}
__device__ __forceinline__ void flag_wait(const unsigned* f, unsigned count, unsigned epoch) {
  const unsigned target = (epoch + 1) * count;
  uint32_t n = 0;
  while (true) {
    unsigned v;
    asm volatile("ld.acquire.gpu.global.u32 %0, [%1];" : "=r"(v) : "l"(f) : "memory");
    if ((int)(v - target) >= 0) break;
    if (++n > SPIN_LIMIT) __trap();
    __nanosleep(FLAG_NS);
  }
}
__device__ __forceinline__ void fence_async_all() { asm volatile("fence.proxy.async;" ::: "memory"); }
__device__ __forceinline__ void flag_signal(unsigned* f) {
  asm volatile("fence.acq_rel.gpu;" ::: "memory");
  asm volatile("red.relaxed.gpu.global.add.u32 [%0], 1;" :: "l"(f) : "memory");
}
__device__ __forceinline__ void flag_signal_after_bulk(unsigned* f) {
  asm volatile("red.relaxed.gpu.global.add.u32 [%0], 1;" :: "l"(f) : "memory");
}
__device__ __forceinline__ void fence_async_smem() { asm volatile("fence.proxy.async.shared::cta;" ::: "memory"); }
__device__ __forceinline__ void tma_ld2(uint32_t dst, const CUtensorMap* m, uint32_t bar, int c0, int c1) {
  asm volatile("cp.async.bulk.tensor.2d.shared::cluster.global.mbarrier::complete_tx::bytes [%0], [%1, {%3, %4}], [%2];"
               :: "r"(dst), "l"(m), "r"(bar), "r"(c0), "r"(c1) : "memory");
}
__device__ __forceinline__ void tma_ld3(uint32_t dst, const CUtensorMap* m, uint32_t bar, int c0, int c1, int c2) {
  asm volatile("cp.async.bulk.tensor.3d.shared::cluster.global.mbarrier::complete_tx::bytes [%0], [%1, {%3, %4, %5}], [%2];"
               :: "r"(dst), "l"(m), "r"(bar), "r"(c0), "r"(c1), "r"(c2) : "memory");
}
__device__ __forceinline__ void bulk_ld(uint32_t dst, const void* src, uint32_t bytes, uint32_t bar) {
  asm volatile("cp.async.bulk.shared::cluster.global.mbarrier::complete_tx::bytes [%0], [%1], %2, [%3];"
               :: "r"(dst), "l"(src), "r"(bytes), "r"(bar) : "memory");
}
__device__ __forceinline__ void bulk_st(void* dst, uint32_t src, uint32_t bytes) {
  asm volatile("cp.async.bulk.global.shared::cta.bulk_group [%0], [%1], %2;" :: "l"(dst), "r"(src), "r"(bytes) : "memory");
}
__device__ __forceinline__ void tma_st2(const CUtensorMap* m, uint32_t src, int c0, int c1) {
  asm volatile("cp.async.bulk.tensor.2d.global.shared::cta.bulk_group [%0, {%2, %3}], [%1];"
               :: "l"(m), "r"(src), "r"(c0), "r"(c1) : "memory");
}
__device__ __forceinline__ void tma_red2(const CUtensorMap* m, uint32_t src, int c0, int c1) {
  asm volatile("cp.reduce.async.bulk.tensor.2d.global.shared::cta.add.tile.bulk_group [%0, {%2, %3}], [%1];"
               :: "l"(m), "r"(src), "r"(c0), "r"(c1) : "memory");
}
__device__ __forceinline__ void tma_pf2(const CUtensorMap* m, int c0, int c1) {
  asm volatile("cp.async.bulk.prefetch.tensor.2d.L2.global.tile [%0, {%1, %2}];" :: "l"(m), "r"(c0), "r"(c1) : "memory");
}
__device__ __forceinline__ void bulk_prefetch(const void* src, uint32_t bytes) {
  asm volatile("cp.async.bulk.prefetch.L2.global [%0], %1;" :: "l"(src), "r"(bytes) : "memory");
}
__device__ __forceinline__ void bulk_commit() { asm volatile("cp.async.bulk.commit_group;" ::: "memory"); }
__device__ __forceinline__ void bulk_wait_read() { asm volatile("cp.async.bulk.wait_group.read 0;" ::: "memory"); }
__device__ __forceinline__ void bulk_wait_all() { asm volatile("cp.async.bulk.wait_group 0;" ::: "memory"); }
__device__ __forceinline__ void prefetch_map(const CUtensorMap* m) { asm volatile("prefetch.tensormap [%0];" :: "l"(m) : "memory"); }
__device__ __forceinline__ void wg_fence() { asm volatile("wgmma.fence.sync.aligned;" ::: "memory"); }
__device__ __forceinline__ void wg_commit() { asm volatile("wgmma.commit_group.sync.aligned;" ::: "memory"); }
template <int N> __device__ __forceinline__ void wg_wait() { asm volatile("wgmma.wait_group.sync.aligned %0;" :: "n"(N) : "memory"); }
template <int N> __device__ __forceinline__ void reg_fence(float (&d)[N]) {
#pragma unroll
  for (int i = 0; i < N; i++) asm volatile("" : "+f"(d[i]) :: "memory");
}
template <int N> __device__ __forceinline__ void reg_fence(uint32_t (&d)[N]) {
#pragma unroll
  for (int i = 0; i < N; i++) asm volatile("" : "+r"(d[i]) :: "memory");
}
__device__ __forceinline__ uint32_t fresh_tid() { uint32_t t; asm volatile("mov.u32 %0, %%tid.x;" : "=r"(t)); return t; }
__device__ __forceinline__ uint32_t lane_base16() {
  const uint32_t t = fresh_tid(), lane = t & 31, wq = (t >> 5) & 3;
  return (16 * wq + (lane & 7) + 8 * ((lane >> 3) & 1)) * 128 + (((lane >> 4) ^ (lane & 7)) << 4);
}
__device__ __forceinline__ void named_sync(int id, int n) { asm volatile("bar.sync %0, %1;" :: "r"(id), "r"(n) : "memory"); }
__device__ __forceinline__ void named_arrive(int id, int n) { asm volatile("bar.arrive %0, %1;" :: "r"(id), "r"(n) : "memory"); }
__device__ __forceinline__ uint32_t pack_bf16(float lo, float hi) {
  uint32_t r; asm("cvt.rn.bf16x2.f32 %0, %1, %2;" : "=r"(r) : "f"(hi), "f"(lo)); return r;
}
__device__ __forceinline__ float ex2(float x) { float y; asm("ex2.approx.ftz.f32 %0, %1;" : "=f"(y) : "f"(x)); return y; }
__device__ __forceinline__ void stsm4(uint32_t addr, uint32_t a, uint32_t b, uint32_t c, uint32_t d) {
  asm volatile("stmatrix.sync.aligned.m8n8.x4.shared.b16 [%0], {%1, %2, %3, %4};" :: "r"(addr), "r"(a), "r"(b), "r"(c), "r"(d) : "memory");
}
__device__ __forceinline__ void stsm4t(uint32_t addr, uint32_t a, uint32_t b, uint32_t c, uint32_t d) {
  asm volatile("stmatrix.sync.aligned.m8n8.x4.trans.shared.b16 [%0], {%1, %2, %3, %4};" :: "r"(addr), "r"(a), "r"(b), "r"(c), "r"(d) : "memory");
}
__device__ __forceinline__ uint64_t mk_desc(uint32_t addr, uint32_t lbo, uint32_t sbo) {
  return (uint64_t)(((addr & 0x3FFFF) >> 4) | ((lbo >> 4) << 16)) | ((uint64_t)((sbo >> 4) | (1u << 30)) << 32);
}
__device__ __forceinline__ uint64_t desc_k(uint32_t addr)  { return mk_desc(addr, 16, 1024); }
__device__ __forceinline__ uint64_t desc_mn(uint32_t addr) { return mk_desc(addr, 8192, 1024); }
__device__ __forceinline__ uint64_t desc_add(uint64_t d, uint32_t bytes) { return d + (bytes >> 4); }

__device__ __forceinline__ void wgmma_ss_n256_tb(float (&d)[128], uint64_t da, uint64_t db, int sd) {
  asm volatile("{\n.reg .pred p;\nsetp.ne.b32 p, %130, 0;\n"
    "wgmma.mma_async.sync.aligned.m64n256k16.f32.bf16.bf16 "
    "{%0, %1, %2, %3, %4, %5, %6, %7, %8, %9, %10, %11, %12, %13, %14, %15, "
    "%16, %17, %18, %19, %20, %21, %22, %23, %24, %25, %26, %27, %28, %29, %30, %31, "
    "%32, %33, %34, %35, %36, %37, %38, %39, %40, %41, %42, %43, %44, %45, %46, %47, "
    "%48, %49, %50, %51, %52, %53, %54, %55, %56, %57, %58, %59, %60, %61, %62, %63, "
    "%64, %65, %66, %67, %68, %69, %70, %71, %72, %73, %74, %75, %76, %77, %78, %79, "
    "%80, %81, %82, %83, %84, %85, %86, %87, %88, %89, %90, %91, %92, %93, %94, %95, "
    "%96, %97, %98, %99, %100, %101, %102, %103, %104, %105, %106, %107, %108, %109, %110, %111, "
    "%112, %113, %114, %115, %116, %117, %118, %119, %120, %121, %122, %123, %124, %125, %126, %127}, "
    "%128, %129, p, 1, 1, 0, 1;\n}"
    : "+f"(d[0]), "+f"(d[1]), "+f"(d[2]), "+f"(d[3]), "+f"(d[4]), "+f"(d[5]), "+f"(d[6]), "+f"(d[7]),
      "+f"(d[8]), "+f"(d[9]), "+f"(d[10]), "+f"(d[11]), "+f"(d[12]), "+f"(d[13]), "+f"(d[14]), "+f"(d[15]),
      "+f"(d[16]), "+f"(d[17]), "+f"(d[18]), "+f"(d[19]), "+f"(d[20]), "+f"(d[21]), "+f"(d[22]), "+f"(d[23]),
      "+f"(d[24]), "+f"(d[25]), "+f"(d[26]), "+f"(d[27]), "+f"(d[28]), "+f"(d[29]), "+f"(d[30]), "+f"(d[31]),
      "+f"(d[32]), "+f"(d[33]), "+f"(d[34]), "+f"(d[35]), "+f"(d[36]), "+f"(d[37]), "+f"(d[38]), "+f"(d[39]),
      "+f"(d[40]), "+f"(d[41]), "+f"(d[42]), "+f"(d[43]), "+f"(d[44]), "+f"(d[45]), "+f"(d[46]), "+f"(d[47]),
      "+f"(d[48]), "+f"(d[49]), "+f"(d[50]), "+f"(d[51]), "+f"(d[52]), "+f"(d[53]), "+f"(d[54]), "+f"(d[55]),
      "+f"(d[56]), "+f"(d[57]), "+f"(d[58]), "+f"(d[59]), "+f"(d[60]), "+f"(d[61]), "+f"(d[62]), "+f"(d[63]),
      "+f"(d[64]), "+f"(d[65]), "+f"(d[66]), "+f"(d[67]), "+f"(d[68]), "+f"(d[69]), "+f"(d[70]), "+f"(d[71]),
      "+f"(d[72]), "+f"(d[73]), "+f"(d[74]), "+f"(d[75]), "+f"(d[76]), "+f"(d[77]), "+f"(d[78]), "+f"(d[79]),
      "+f"(d[80]), "+f"(d[81]), "+f"(d[82]), "+f"(d[83]), "+f"(d[84]), "+f"(d[85]), "+f"(d[86]), "+f"(d[87]),
      "+f"(d[88]), "+f"(d[89]), "+f"(d[90]), "+f"(d[91]), "+f"(d[92]), "+f"(d[93]), "+f"(d[94]), "+f"(d[95]),
      "+f"(d[96]), "+f"(d[97]), "+f"(d[98]), "+f"(d[99]), "+f"(d[100]), "+f"(d[101]), "+f"(d[102]), "+f"(d[103]),
      "+f"(d[104]), "+f"(d[105]), "+f"(d[106]), "+f"(d[107]), "+f"(d[108]), "+f"(d[109]), "+f"(d[110]), "+f"(d[111]),
      "+f"(d[112]), "+f"(d[113]), "+f"(d[114]), "+f"(d[115]), "+f"(d[116]), "+f"(d[117]), "+f"(d[118]), "+f"(d[119]),
      "+f"(d[120]), "+f"(d[121]), "+f"(d[122]), "+f"(d[123]), "+f"(d[124]), "+f"(d[125]), "+f"(d[126]), "+f"(d[127])
    : "l"(da), "l"(db), "r"(sd));
}
__device__ __forceinline__ void wgmma_ss_n64(float (&d)[32], uint64_t da, uint64_t db, int sd) {
  asm volatile("{\n.reg .pred p;\nsetp.ne.b32 p, %34, 0;\n"
    "wgmma.mma_async.sync.aligned.m64n64k16.f32.bf16.bf16 "
    "{%0, %1, %2, %3, %4, %5, %6, %7, %8, %9, %10, %11, %12, %13, %14, %15, "
    "%16, %17, %18, %19, %20, %21, %22, %23, %24, %25, %26, %27, %28, %29, %30, %31}, "
    "%32, %33, p, 1, 1, 0, 0;\n}"
    : "+f"(d[0]), "+f"(d[1]), "+f"(d[2]), "+f"(d[3]), "+f"(d[4]), "+f"(d[5]), "+f"(d[6]), "+f"(d[7]),
      "+f"(d[8]), "+f"(d[9]), "+f"(d[10]), "+f"(d[11]), "+f"(d[12]), "+f"(d[13]), "+f"(d[14]), "+f"(d[15]),
      "+f"(d[16]), "+f"(d[17]), "+f"(d[18]), "+f"(d[19]), "+f"(d[20]), "+f"(d[21]), "+f"(d[22]), "+f"(d[23]),
      "+f"(d[24]), "+f"(d[25]), "+f"(d[26]), "+f"(d[27]), "+f"(d[28]), "+f"(d[29]), "+f"(d[30]), "+f"(d[31])
    : "l"(da), "l"(db), "r"(sd));
}
__device__ __forceinline__ void wgmma_rs_n256_tb(float (&d)[128], uint32_t a0, uint32_t a1, uint32_t a2, uint32_t a3, uint64_t db, int sd) {
  asm volatile("{\n.reg .pred p;\nsetp.ne.b32 p, %133, 0;\n"
    "wgmma.mma_async.sync.aligned.m64n256k16.f32.bf16.bf16 "
    "{%0, %1, %2, %3, %4, %5, %6, %7, %8, %9, %10, %11, %12, %13, %14, %15, "
    "%16, %17, %18, %19, %20, %21, %22, %23, %24, %25, %26, %27, %28, %29, %30, %31, "
    "%32, %33, %34, %35, %36, %37, %38, %39, %40, %41, %42, %43, %44, %45, %46, %47, "
    "%48, %49, %50, %51, %52, %53, %54, %55, %56, %57, %58, %59, %60, %61, %62, %63, "
    "%64, %65, %66, %67, %68, %69, %70, %71, %72, %73, %74, %75, %76, %77, %78, %79, "
    "%80, %81, %82, %83, %84, %85, %86, %87, %88, %89, %90, %91, %92, %93, %94, %95, "
    "%96, %97, %98, %99, %100, %101, %102, %103, %104, %105, %106, %107, %108, %109, %110, %111, "
    "%112, %113, %114, %115, %116, %117, %118, %119, %120, %121, %122, %123, %124, %125, %126, %127}, "
    "{%128, %129, %130, %131}, %132, p, 1, 1, 1;\n}"
    : "+f"(d[0]), "+f"(d[1]), "+f"(d[2]), "+f"(d[3]), "+f"(d[4]), "+f"(d[5]), "+f"(d[6]), "+f"(d[7]),
      "+f"(d[8]), "+f"(d[9]), "+f"(d[10]), "+f"(d[11]), "+f"(d[12]), "+f"(d[13]), "+f"(d[14]), "+f"(d[15]),
      "+f"(d[16]), "+f"(d[17]), "+f"(d[18]), "+f"(d[19]), "+f"(d[20]), "+f"(d[21]), "+f"(d[22]), "+f"(d[23]),
      "+f"(d[24]), "+f"(d[25]), "+f"(d[26]), "+f"(d[27]), "+f"(d[28]), "+f"(d[29]), "+f"(d[30]), "+f"(d[31]),
      "+f"(d[32]), "+f"(d[33]), "+f"(d[34]), "+f"(d[35]), "+f"(d[36]), "+f"(d[37]), "+f"(d[38]), "+f"(d[39]),
      "+f"(d[40]), "+f"(d[41]), "+f"(d[42]), "+f"(d[43]), "+f"(d[44]), "+f"(d[45]), "+f"(d[46]), "+f"(d[47]),
      "+f"(d[48]), "+f"(d[49]), "+f"(d[50]), "+f"(d[51]), "+f"(d[52]), "+f"(d[53]), "+f"(d[54]), "+f"(d[55]),
      "+f"(d[56]), "+f"(d[57]), "+f"(d[58]), "+f"(d[59]), "+f"(d[60]), "+f"(d[61]), "+f"(d[62]), "+f"(d[63]),
      "+f"(d[64]), "+f"(d[65]), "+f"(d[66]), "+f"(d[67]), "+f"(d[68]), "+f"(d[69]), "+f"(d[70]), "+f"(d[71]),
      "+f"(d[72]), "+f"(d[73]), "+f"(d[74]), "+f"(d[75]), "+f"(d[76]), "+f"(d[77]), "+f"(d[78]), "+f"(d[79]),
      "+f"(d[80]), "+f"(d[81]), "+f"(d[82]), "+f"(d[83]), "+f"(d[84]), "+f"(d[85]), "+f"(d[86]), "+f"(d[87]),
      "+f"(d[88]), "+f"(d[89]), "+f"(d[90]), "+f"(d[91]), "+f"(d[92]), "+f"(d[93]), "+f"(d[94]), "+f"(d[95]),
      "+f"(d[96]), "+f"(d[97]), "+f"(d[98]), "+f"(d[99]), "+f"(d[100]), "+f"(d[101]), "+f"(d[102]), "+f"(d[103]),
      "+f"(d[104]), "+f"(d[105]), "+f"(d[106]), "+f"(d[107]), "+f"(d[108]), "+f"(d[109]), "+f"(d[110]), "+f"(d[111]),
      "+f"(d[112]), "+f"(d[113]), "+f"(d[114]), "+f"(d[115]), "+f"(d[116]), "+f"(d[117]), "+f"(d[118]), "+f"(d[119]),
      "+f"(d[120]), "+f"(d[121]), "+f"(d[122]), "+f"(d[123]), "+f"(d[124]), "+f"(d[125]), "+f"(d[126]), "+f"(d[127])
    : "r"(a0), "r"(a1), "r"(a2), "r"(a3), "l"(db), "r"(sd));
}
__device__ __forceinline__ void wgmma_rs_n64_tb(float (&d)[32], uint32_t a0, uint32_t a1, uint32_t a2, uint32_t a3, uint64_t db, int sd) {
  asm volatile("{\n.reg .pred p;\nsetp.ne.b32 p, %37, 0;\n"
    "wgmma.mma_async.sync.aligned.m64n64k16.f32.bf16.bf16 "
    "{%0, %1, %2, %3, %4, %5, %6, %7, %8, %9, %10, %11, %12, %13, %14, %15, "
    "%16, %17, %18, %19, %20, %21, %22, %23, %24, %25, %26, %27, %28, %29, %30, %31}, "
    "{%32, %33, %34, %35}, %36, p, 1, 1, 1;\n}"
    : "+f"(d[0]), "+f"(d[1]), "+f"(d[2]), "+f"(d[3]), "+f"(d[4]), "+f"(d[5]), "+f"(d[6]), "+f"(d[7]),
      "+f"(d[8]), "+f"(d[9]), "+f"(d[10]), "+f"(d[11]), "+f"(d[12]), "+f"(d[13]), "+f"(d[14]), "+f"(d[15]),
      "+f"(d[16]), "+f"(d[17]), "+f"(d[18]), "+f"(d[19]), "+f"(d[20]), "+f"(d[21]), "+f"(d[22]), "+f"(d[23]),
      "+f"(d[24]), "+f"(d[25]), "+f"(d[26]), "+f"(d[27]), "+f"(d[28]), "+f"(d[29]), "+f"(d[30]), "+f"(d[31])
    : "r"(a0), "r"(a1), "r"(a2), "r"(a3), "l"(db), "r"(sd));
}
__device__ __forceinline__ void wgmma_rs_n64(float (&d)[32], uint32_t a0, uint32_t a1, uint32_t a2, uint32_t a3, uint64_t db, int sd) {
  asm volatile("{\n.reg .pred p;\nsetp.ne.b32 p, %37, 0;\n"
    "wgmma.mma_async.sync.aligned.m64n64k16.f32.bf16.bf16 "
    "{%0, %1, %2, %3, %4, %5, %6, %7, %8, %9, %10, %11, %12, %13, %14, %15, "
    "%16, %17, %18, %19, %20, %21, %22, %23, %24, %25, %26, %27, %28, %29, %30, %31}, "
    "{%32, %33, %34, %35}, %36, p, 1, 1, 0;\n}"
    : "+f"(d[0]), "+f"(d[1]), "+f"(d[2]), "+f"(d[3]), "+f"(d[4]), "+f"(d[5]), "+f"(d[6]), "+f"(d[7]),
      "+f"(d[8]), "+f"(d[9]), "+f"(d[10]), "+f"(d[11]), "+f"(d[12]), "+f"(d[13]), "+f"(d[14]), "+f"(d[15]),
      "+f"(d[16]), "+f"(d[17]), "+f"(d[18]), "+f"(d[19]), "+f"(d[20]), "+f"(d[21]), "+f"(d[22]), "+f"(d[23]),
      "+f"(d[24]), "+f"(d[25]), "+f"(d[26]), "+f"(d[27]), "+f"(d[28]), "+f"(d[29]), "+f"(d[30]), "+f"(d[31])
    : "r"(a0), "r"(a1), "r"(a2), "r"(a3), "l"(db), "r"(sd));
}

__device__ __forceinline__ uint4 lds16(uint32_t a) {
  uint4 v; asm volatile("ld.shared.v4.u32 {%0, %1, %2, %3}, [%4];" : "=r"(v.x), "=r"(v.y), "=r"(v.z), "=r"(v.w) : "r"(a) : "memory"); return v;
}
__device__ __forceinline__ void sts16(uint32_t a, uint32_t x, uint32_t y, uint32_t z, uint32_t w) {
  asm volatile("st.shared.v4.u32 [%0], {%1, %2, %3, %4};" :: "r"(a), "r"(x), "r"(y), "r"(z), "r"(w) : "memory");
}
__device__ __forceinline__ uint32_t lds4(uint32_t a) { uint32_t v; asm volatile("ld.shared.u32 %0, [%1];" : "=r"(v) : "r"(a) : "memory"); return v; }
__device__ __forceinline__ uint32_t lds4v(uint32_t a) { uint32_t v; asm volatile("ld.volatile.shared.u32 %0, [%1];" : "=r"(v) : "r"(a) : "memory"); return v; }
__device__ __forceinline__ uint32_t bmul(uint32_t a, uint32_t b) { uint32_t r; asm("mul.rn.bf16x2 %0, %1, %2;" : "=r"(r) : "r"(a), "r"(b)); return r; }
__device__ __forceinline__ uint32_t bfma(uint32_t a, uint32_t b, uint32_t c) { uint32_t r; asm("fma.rn.bf16x2 %0, %1, %2, %3;" : "=r"(r) : "r"(a), "r"(b), "r"(c)); return r; }
__device__ __forceinline__ uint32_t badd(uint32_t a, uint32_t b) { uint32_t r; asm("add.rn.bf16x2 %0, %1, %2;" : "=r"(r) : "r"(a), "r"(b)); return r; }

__device__ __forceinline__ void ldsm4(uint32_t (&r)[4], uint32_t a) {
  asm volatile("ldmatrix.sync.aligned.m8n8.x4.shared.b16 {%0, %1, %2, %3}, [%4];" : "=r"(r[0]), "=r"(r[1]), "=r"(r[2]), "=r"(r[3]) : "r"(a) : "memory");
}
__device__ __forceinline__ void ldsm4t(uint32_t (&r)[4], uint32_t a) {
  asm volatile("ldmatrix.sync.aligned.m8n8.x4.trans.shared.b16 {%0, %1, %2, %3}, [%4];" : "=r"(r[0]), "=r"(r[1]), "=r"(r[2]), "=r"(r[3]) : "r"(a) : "memory");
}
__device__ __forceinline__ uint32_t transpose8(uint32_t a) { uint32_t d; asm volatile("movmatrix.sync.aligned.m8n8.trans.b16 %0, %1;" : "=r"(d) : "r"(a)); return d; }

__device__ __forceinline__ void mma16816(float (&d)[4], const uint32_t (&a)[4], uint32_t b0, uint32_t b1) {
  asm volatile("mma.sync.aligned.m16n8k16.row.col.f32.bf16.bf16.f32 {%0, %1, %2, %3}, {%4, %5, %6, %7}, {%8, %9}, {%0, %1, %2, %3};"
               : "+f"(d[0]), "+f"(d[1]), "+f"(d[2]), "+f"(d[3]) : "r"(a[0]), "r"(a[1]), "r"(a[2]), "r"(a[3]), "r"(b0), "r"(b1));
}

#define STG_K1 2
#define STG_K2 10
#define STG_Q1 1
#define STG_Q2 5
#define PACE_A 400
#define PACE_B 100
#define PF_QA 48
#define PF_CV 64
#define PF_X 8
#define PF_WO 11
#define Q_PRE 2
#define CV_SER -1
#define CV_QX 0
#define CV_FX 1
#define TAIL_WAIT 0
#define ARRIVE_KK 12
#define SIDE_DELAY_NS 4000
#define HEAD_MAP 2
#define EARLY_LD 2
#define HI_ORDER 9
constexpr int CV_BAR = 5;
constexpr int PP_BAR = 3;
template <int V> struct Int { static constexpr int value = V; };
struct Ring {
  uint32_t slot, phase;
  __device__ __forceinline__ void next() { if (++slot == NSLOT) { slot = 0; phase ^= 1; } }
};
__device__ __forceinline__ uint32_t bar_addr(uint32_t sb, uint32_t i) { return sb + BARS + 8 * i; }
__device__ __forceinline__ uint32_t q_region(uint32_t sb, int w) { return sb + QREG + (w ^ 1) * 32768; }

struct Role { int h, j; };
__device__ __forceinline__ Role get_role() {
  int cta; asm volatile("mov.u32 %0, %%ctaid.x;" : "=r"(cta));
  const int c = cta >> 1;
  int h, u;
  const int a = c - 4, b = c - 36, q = (b * 37) >> 8;
  h = a < 0 ? (HEAD_MAP == 2 ? 8 : 15) : b < 0 ? a & 7 : (HEAD_MAP == 2 ? 9 : 8) + b - 7 * q;
  u = a < 0 ? c : b < 0 ? a >> 3 : q;
  return Role{h, 2 * u + (cta & 1)};
}
__device__ __forceinline__ int fresh_warp() { return __shfl_sync(0xffffffffu, fresh_tid() >> 5, 0); }

__device__ __forceinline__ int q_tile(int h, int j, int which) { return ((h < 8) == (which == 0)) ? 15 - j : j; }

__device__ __forceinline__ int o_chunk(int h, int c) { const int x = c + (h & 7); return x % 7; }

__device__ __forceinline__ int kv_block(int j, int t) { return j + 8 * ((HI_ORDER >> t) & 1); }
__device__ __forceinline__ uint8_t* kv_tile(const Params& p, int v, int h, int tile) {
  return p.kv + (size_t)((v * NH + h) * 32 + tile) * 32768;
}

__device__ __forceinline__ void ring_acquire(uint32_t sb, Ring& r, uint32_t bytes) {
  mbar_wait(bar_addr(sb, B_RG_EMPTY + r.slot), r.phase ^ 1);
  mbar_expect_tx(bar_addr(sb, B_RG_FULL + r.slot), bytes);
}
__device__ __forceinline__ void producer_main(const Params& p, uint32_t sb) {
  const Role ro = get_role();
  const int h = ro.h, j = ro.j;
  TR_DECL;
  CP_DECL;
  ST(11);
  for (int it = EARLY_LD; it < 71; it++) {
    const int t = it >> 4, k = it & 15, s = it & 3;
    mbar_wait(bar_addr(sb, B_P1_EMPTY + s), ((it >> 2) & 1) ^ 1);
    const uint32_t full = bar_addr(sb, B_P1_FULL + s), dst = sb + s * P1_STAGE;
    mbar_expect_tx(full, P1_STAGE);
    if ((it & 7) == 4) TRG(it);
    if (t < 4) {
      tma_ld2(dst, &p.ckv, full, k * 64, kv_block(j, t) * 128);
      tma_ld3(dst + 16384, (t >> 1) ? &p.wuv : &p.wuk, full, 0, k * 64, h * 4);
    } else {
      tma_ld2(dst, &p.x, full, k * 64, q_tile(h, j, 0) * 128);
      tma_ld3(dst + 16384, &p.wq, full, 0, k * 64, h * 4);
    }
    CP();
    if (it >= PF_QA && it < PF_QA + 14) {
      const int i = it - PF_QA;
      bulk_prefetch(p.b_x + (size_t)(q_tile(h, j, 0) * 128 + (h & 7) * 16) * DM + i * 512, 1024);
      tma_pf2(&p.wqp, h * HD, (i * 8 + j) * 4);
    }
    if (it >= PF_CV && it < PF_CV + 3) {
      mbar_wait(bar_addr(sb, B_XS), 0);
      bulk_prefetch(g_xs + (size_t)(h * 8 + j) * CV_BYTES + (it - PF_CV) * (CV_BYTES / 3), CV_BYTES / 3);
    }
  }
  mbar_wait(bar_addr(sb, B_P1_EMPTY + 3), 0);
  mbar_wait(bar_addr(sb, B_XS), 0);
  mbar_expect_tx(bar_addr(sb, B_RG_FULL + 4), CV_BYTES);
  bulk_ld(sb + CV_X, g_xs + (size_t)(h * 8 + j) * CV_BYTES, CV_BYTES, bar_addr(sb, B_RG_FULL + 4));
  Ring r{0, 1};
  auto prefetch_wo = [&](int left) {
    const int i = PF_WO - left;
    if (PF_WO && i >= 0 && i < 8) bulk_prefetch(p.b_wo + (size_t)(h * HD + j * 32 + 4 * i) * DM, 4 * DM * 2);
  };
  mbar_wait(bar_addr(sb, B_KV), 0);
  for (int which = 0; which < 2; which++) {
    const int qt = q_tile(h, j, which);
    if (which == 1) {
      for (int kc = 0; kc < 7; kc++) {
        prefetch_wo(4 * qt + 4 + 7 - kc);
        ring_acquire(sb, r, 32768);
        tma_ld3(sb + r.slot * SLOT, &p.wq, bar_addr(sb, B_RG_FULL + r.slot), 0, kc * 64, h * 4);
        r.next();
        if (kc == 0 || (kc & 1)) {
          ring_acquire(sb, r, kc == 0 ? 16384 : 32768);
          const uint32_t full = bar_addr(sb, B_RG_FULL + r.slot), dst = sb + r.slot * SLOT;
          tma_ld2(dst, &p.x, full, kc * 64, qt * 128);
          if (kc > 0) tma_ld2(dst + 16384, &p.x, full, kc * 64 + 64, qt * 128);
          r.next();
        }
      }
    }
    const int n = 2 * qt + 2;
    for (int f = 0; f < 2 * n; f++) {
      if (which == 0) {
        const int i = f - max(2 * n - PF_X, 0);
        if (PF_X && i >= 0 && i < 4) bulk_prefetch(p.b_x + (size_t)((15 - qt) * 128 + (h & 7) * 16 + 4 * i) * DM, 4 * DM * 2);
      } else prefetch_wo(2 * n - f);
      const bool isK = (f == 0) || ((f & 1) && f < 2 * n - 1);
      const int i = isK ? (f + 1) >> 1 : (f == 2 * n - 1 ? n - 1 : (f >> 1) - 1);
      const int tile = which ? n - 1 - i : i;
      if (!isK) mbar_wait(bar_addr(sb, B_KV + 1 + ((tile >> 4) ^ ((HI_ORDER >> 2) & 1))), 0);
      if (which == 0 && f < 2) mbar_wait(bar_addr(sb, B_P1_EMPTY + f), 1);
      ring_acquire(sb, r, 32768);
      if (isK && (tile & 3) == 0) TRG(100 + 50 * which + tile);
      bulk_ld(sb + r.slot * SLOT, kv_tile(p, !isK, h, tile), 32768, bar_addr(sb, B_RG_FULL + r.slot));
      r.next();
      CP();
    }
  }
  for (int i = 0; i < 14; i++) {
    ring_acquire(sb, r, 32768);
    if ((i & 3) == 0) TRG(200 + i);
    if (i == 13) TR_END();
    tma_ld2(sb + r.slot * SLOT, &p.wo, bar_addr(sb, B_RG_FULL + r.slot), o_chunk(h, i >> 1) * 64, ((i & 1) ? h ^ 8 : h) * HD);
    r.next();
    CP();
  }
}

__device__ __forceinline__ void storer_main(const Params& p, uint32_t sb) {
  const Role ro = get_role();
  const int h = ro.h, j = ro.j, w = fresh_warp() - 1;
  const uint32_t full = bar_addr(sb, B_ST_FULL + w), empty = bar_addr(sb, B_ST_EMPTY + w);
  const int lane = threadIdx.x & 31;
  const unsigned epoch = load_epoch();
  if (lane == 0) {
    for (int job = 0; job < 8; job++) {
      const int t = job >> 1;
      uint8_t* dst = kv_tile(p, t >> 1, h, 2 * kv_block(j, t) + w) + (job & 1) * 16384;
      mbar_wait_nap(full, job & 1);
      for (int i = 0; i < 8; i++) {
        if (i) __nanosleep(job < 6 ? PACE_A : PACE_B);
        bulk_st(dst + i * 2048, sb + P1_STG + w * 16384 + i * 2048, 2048);
      }
      bulk_commit();
      bulk_wait_read();
      mbar_arrive(empty);
      if (job >= 3 && (job & 1)) { bulk_wait_all(); flag_signal(&g_flags.kv_ready[3 * h + t - 1].v); }
    }
  }
  __syncwarp();
  const int cta = h * 8 + j, qt = q_tile(h, j, 1);
  const uint32_t qreg = q_region(sb, w);
  {
    mbar_wait_nap(bar_addr(sb, B_CTXS + 4 * w), 0);
    uint4* z = reinterpret_cast<uint4*>(p.out + (size_t)(qt * 128 + w * 64 + (h & 7) * 8 + (lane >> 2)) * OUTW + DA) + (lane & 3);
#pragma unroll
    for (int i = 0; i < 14; i++) z[4 * i] = make_uint4(0, 0, 0, 0);
    __syncwarp();
    if (lane != 0) return;
    for (int b = 0; b < 4; b++) {
      mbar_wait(bar_addr(sb, B_CTXS + 4 * w + b), 0);
      bulk_st(p.ctx + (size_t)(cta * 2 + w) * 32768 + b * 8192, qreg + b * 8192, 8192);
      bulk_commit();
    }
    bulk_wait_read();
    mbar_arrive(empty);
    bulk_wait_all();
    flag_signal(&g_flags.ctx_ready[cta * 2 + w].v);
    flag_signal_after_bulk(&g_flags.out_ready[qt * 2 + w].v);
  }
  {
    const int wx = w ^ 1;
    flag_wait(&g_flags.ctx_ready[(cta ^ 64) * 2 + wx].v, 1, epoch);
    flag_wait(&g_flags.out_ready[qt * 2 + wx].v, 8, epoch);
    fence_async_all();
    mbar_wait_nap(bar_addr(sb, B_QFREE + w), 0);
    mbar_expect_tx(bar_addr(sb, B_CTXF + w), 32768);
    bulk_ld(qreg, p.ctx + (size_t)((cta ^ 64) * 2 + wx) * 32768, 32768, bar_addr(sb, B_CTXF + w));
    for (int ch = 0; ch < 7; ch++) {
      const int b = ch & 1;
      mbar_wait(bar_addr(sb, B_S2_FULL + w * 2 + b), (ch >> 1) & 1);
      tma_red2(&p.part, qreg + b * 8192, DA + o_chunk(h, ch) * 64, qt * 128 + wx * 64);
      bulk_commit();
      if (ch == 0 && w == 1) mbar_arrive(bar_addr(sb, B_GFREE));
      bulk_wait_read();
      mbar_arrive(bar_addr(sb, B_S2_EMPTY + w * 2 + b));
    }
    GT(48 + w);
    if (TAIL_WAIT) bulk_wait_all();
    GT(50 + w); GT(52 + w); GT(56);
    if (w == 0) { ST(12); STG_(13); }
  }
}

template <int OFF, int NB, int NREG>
__device__ __forceinline__ void store_blocks(uint32_t base, uint32_t lanebase, const uint32_t (&pk)[NREG]) {
#pragma unroll
  for (int J = 0; J < NB * 8; J += 2) {
    const uint32_t a = base + (J >> 3) * 8192 + (lanebase ^ ((J & 7) << 4));
    stsm4(a, pk[OFF + 2 * J], pk[OFF + 2 * J + 1], pk[OFF + 2 * J + 2], pk[OFF + 2 * J + 3]);
  }
}
__device__ __forceinline__ void warp_arrive(uint32_t bar, int lane) { __syncwarp(); if (lane == 0) mbar_arrive(bar); }
__device__ __forceinline__ void release(uint32_t bar, int lane) { lane0_arrive(bar, 1, lane); }

template <int W> __device__ __forceinline__ constexpr int cv_tile(int u) { return 2 * u + ((u ^ W) & 1); }
__device__ __forceinline__ uint32_t cv_x_lane(uint32_t lane) { return (16 + (lane & 15) - (lane >> 4)) * 16; }
__device__ __forceinline__ uint32_t cv_h_lane(uint32_t lane, uint32_t hE, uint32_t hO) {
  const uint32_t g = lane >> 2, c = lane & 3;
  return (g & 1) ? hO + (15 + 2 * c - g) * 2 : hE + (16 + 2 * c - g) * 2;
}
template <int W>
__device__ __forceinline__ void conv_mma(float (&ca)[8][4], uint32_t xa, uint32_t ha, uint32_t sb, uint32_t lb, const uint32_t (&pk)[64]) {
  constexpr int N = 16 - W;
  uint32_t fx[N][4], fh[N][2];
  auto ld_h = [&](int i, int rr) { fh[i][0] = lds4(ha + i * 256 + rr * 32); fh[i][1] = lds4(ha + i * 256 + rr * 32 + 16); };
  if (CV_SER >= 0 && W == 0) named_sync(CV_BAR, 256);
  ldsm4(fx[0], xa);
#pragma unroll
  for (int u = 0; u < 8; u++) ld_h(cv_tile<W>(u), 0);
  ldsm4(fx[1], xa + 256);
#pragma unroll
  for (int u = 0; u < 8; u++) if (cv_tile<W ^ 1>(u) < N) ld_h(cv_tile<W ^ 1>(u), 0);
#pragma unroll
  for (int i = 2; i < N; i++) ldsm4(fx[i], xa + i * 256);
#pragma unroll
  for (int sx = 0; sx < N; sx++) {
#pragma unroll
    for (int u = 0; u < 8; u++) {
      const int jj = cv_tile<W>(u) - sx;
      if (jj >= 0) mma16816(ca[u], fx[sx], fh[jj < 0 ? 0 : jj][0], fh[jj < 0 ? 0 : jj][1]);
    }
    ldsm4(fx[sx], xa + sx * 256 - 32);
    ld_h(N - 1 - sx, 1);
    if (W == 1 && sx == CV_SER) named_arrive(CV_BAR, 256);
  }
  mbar_wait(bar_addr(sb, B_P1_EMPTY + 2), 1);
  if (W == 0) { mbar_wait(bar_addr(sb, B_ST_EMPTY), 1); mbar_wait(bar_addr(sb, B_ST_EMPTY + 1), 1); }
#pragma unroll
  for (int jj = 15; jj >= 0; jj--) {
    if (W == 0 || CV_QX) stsm4(q_region(sb, W) + (jj >> 2) * 8192 + (lb ^ ((jj & 3) << 5)), pk[4 * jj], pk[4 * jj + 1], pk[4 * jj + 2], pk[4 * jj + 3]);
#pragma unroll
    for (int u = 0; u < 8; u++) {
      const int sx = cv_tile<W>(u) - jj;
      if (sx >= 0) mma16816(ca[u], fx[sx < 0 ? 0 : sx], fh[jj < N ? jj : 0][0], fh[jj < N ? jj : 0][1]);
    }
  }
}

__device__ __forceinline__ void consumer_main(const Params& p, uint32_t sb, uint8_t* xs_base, uint32_t one) {
  const int lane = fresh_tid() & 31, w = (fresh_warp() >> 2) - 1;
  const uint32_t lb = lane_base16();
  int qt, cc;
  { const Role ro = get_role(); qt = q_tile(ro.h, ro.j, 0); cc = ro.h * 8 + ro.j; }
  const uint32_t st_full = bar_addr(sb, B_ST_FULL + w), st_empty = bar_addr(sb, B_ST_EMPTY + w);
  const uint32_t stg = sb + P1_STG + w * 16384;

  auto turn_begin = [&]() { named_sync(PP_BAR + w, 256); };
  auto turn_end = [&]() { named_arrive(PP_BAR + (w ^ 1), 256); };
  float acc[128];
#pragma unroll
  for (int i = 0; i < 128; i++) acc[i] = 0.f;
  uint32_t pk[64];
#pragma unroll
  for (int i = 0; i < 64; i++) pk[i] = 0;
  if (fresh_warp() != 4) named_sync(0, NTHREADS);
  PDECL;
  TR_DECL;
  TR(0);
  TSG(0); TS(1);
  const uint32_t qreg = q_region(sb, w);
  for (int t = 0; t < 5; t++) {
    const int nk = t < 4 ? 16 : 7;
#pragma unroll 1
    for (int k = 0; k < nk; k++) {
      const int it = t * 16 + k, s = k & 3;
      if (it == 0 && threadIdx.x == 256) ST(6);
      mbar_wait(bar_addr(sb, B_P1_FULL + s), (it >> 2) & 1);
      if (it < 3 && threadIdx.x == 256) ST(7 + it);
      TR(1);
      const uint64_t da = desc_k(sb + s * P1_STAGE + w * 8192), db = desc_mn(sb + s * P1_STAGE + 16384);
      turn_begin();
      wg_fence();
#pragma unroll
      for (int kk = 0; kk < 4; kk++) wgmma_ss_n256_tb(acc, desc_add(da, kk * 32), desc_add(db, kk * 2048), (k | kk) != 0);
      wg_commit();
      turn_end();
      TR(3);
      wg_wait<1>();
      if (k > 0) release(bar_addr(sb, B_P1_EMPTY + ((k - 1) & 3)), lane);
      const int k1 = t < 4 ? STG_K1 : STG_Q1, k2 = t < 4 ? STG_K2 : STG_Q2;
      if (t > 0 && (k == k1 || k == k2)) {
        const int job = 2 * (t - 1) + (k != k1);
        if (job > 0) mbar_wait(st_empty, (job - 1) & 1);
        if (k == k1) store_blocks<0, 2>(stg, lb, pk); else store_blocks<32, 2>(stg, lb, pk);
      }
      if (t > 0 && (k == k1 + 1 || k == k2 + 1)) { fence_async_smem(); warp_arrive(st_full, lane); }
      TR(5);
    }
    wg_wait<0>();
    TR(6);
    reg_fence(acc);
    release(bar_addr(sb, B_P1_EMPTY + ((nk - 1) & 3)), lane);
#pragma unroll
    for (int i = 0; i < 64; i++) pk[i] = pack_bf16(acc[2 * i], acc[2 * i + 1]);
    TS(t < 4 ? 2 + t : 60);
  }
  TS(6);
  {
    const uint32_t wq = lb >> 11, ln = lane, cx = sb + CV_X;
    float ca[8][4];
#pragma unroll
    for (int i = 0; i < 8; i++) { ca[i][0] = 0.f; ca[i][1] = 0.f; ca[i][2] = 0.f; ca[i][3] = 0.f; }
    const uint32_t xa = cx + cv_x_lane(ln) - wq * 64, ha = cv_h_lane(ln, cx + CV_HE, cx + CV_HE + CV_HCOPY) + wq * 64;
    mbar_wait(bar_addr(sb, B_RG_FULL + 4), 0);
    TR(7); TS(19); TS(20);
    if (w) conv_mma<1>(ca, xa, ha, sb, lb, pk); else conv_mma<0>(ca, xa, ha, sb, lb, pk);
    TR(8); TS(21);
    const uint32_t ex = sb + CV_R + w * 16384 + ln * 16;
#pragma unroll
    for (int u = 0; u < 8; u++)
      sts16(ex + (wq * 8 + u) * 512, __float_as_uint(ca[u][0]), __float_as_uint(ca[u][1]), __float_as_uint(ca[u][2]), __float_as_uint(ca[u][3]));
  }
  auto conv_finish = [&]() {
    const uint32_t wq = lb >> 11, cx = sb + CV_X, ex = sb + CV_R + w * 16384 + lane * 16;
    uint8_t* gz = xs_base + (size_t)cc * CV_BYTES;
    const uint32_t Dd = lds4(cx + CV_D);
    uint32_t z[2][2];
#pragma unroll
    for (int e = 0; e < 2; e++) {
      const uint32_t u = 2 * wq + e, nt = 2 * u + ((e ^ w) & 1);
      float y[4] = {0.f, 0.f, 0.f, 0.f};
#pragma unroll
      for (int v = 0; v < 4; v++) {
        const uint4 t = lds16(ex + (v * 8 + u) * 512);
        y[0] += __uint_as_float(t.x); y[1] += __uint_as_float(t.y); y[2] += __uint_as_float(t.z); y[3] += __uint_as_float(t.w);
      }
      const uint32_t o = (16 + 16 * nt) * 16 + lane * 4;
      *reinterpret_cast<uint32_t*>(gz + o)       = badd(pack_bf16(y[0], y[1]), bmul(lds4(cx + o), Dd));
      *reinterpret_cast<uint32_t*>(gz + o + 128) = badd(pack_bf16(y[2], y[3]), bmul(lds4(cx + o + 128), Dd));
    }
    __syncwarp();
    release(bar_addr(sb, B_RG_EMPTY + 3), lane);
    release(bar_addr(sb, B_RG_EMPTY + 4), lane);
    if (lane == 0) mbar_arrive(bar_addr(sb, B_CONV));
  };
  TS(15);
  TR(10);
  Ring r{0, 1};
  auto take = [&]() { const uint32_t sl = r.slot; mbar_wait(bar_addr(sb, B_RG_FULL + sl), r.phase); r.next(); return sl; };
  constexpr float SC = 0.0625f * 1.4426950408889634f;
  uint32_t ws;
#pragma unroll 1
  for (int which = 0;; which++) {
    float s[32];
#pragma unroll
    for (int i = 0; i < 32; i++) s[i] = 0.f;
    uint32_t pa[16];
    float b0, b1, l0, l1;
    const uint64_t dq = desc_k(qreg);
    uint64_t dk = 0, dqq = 0, dv = 0;
    auto prep_qk = [&](uint32_t kaddr) { dk = desc_k(kaddr); dqq = dq + (kaddr >> 31); asm volatile("" : "+l"(dk), "+l"(dqq)); };
    auto prep_pv = [&](uint32_t vaddr) { dv = desc_mn(vaddr); asm volatile("" : "+l"(dv)); };
    auto issue_qk = [&]() {
#pragma unroll
      for (int kk = 0; kk < 16; kk++)
        wgmma_ss_n64(s, desc_add(dqq, (kk >> 2) * 8192 + (kk & 3) * 32), desc_add(dk, (kk >> 2) * 8192 + (kk & 3) * 32), kk != 0);
    };
    auto issue_pv = [&](int accumulate) {
#pragma unroll
      for (int kk = 0; kk < 4; kk++)
        wgmma_rs_n256_tb(acc, pa[4 * kk], pa[4 * kk + 1], pa[4 * kk + 2], pa[4 * kk + 3], desc_add(dv, kk * 2048), accumulate | kk);
    };
    auto mask_diag = [&]() {
      const int d = (int)((lb >> 11) << 4) + (lane >> 2) - 2 * (lane & 3);
#pragma unroll
      for (int jj = 0; jj < 8; jj++) {
        if (8 * jj > d)     s[4 * jj]     = -INFINITY;
        if (8 * jj + 1 > d) s[4 * jj + 1] = -INFINITY;
        if (8 * jj - 8 > d) s[4 * jj + 2] = -INFINITY;
        if (8 * jj - 7 > d) s[4 * jj + 3] = -INFINITY;
      }
    };
    auto row_max = [&](float& x0, float& x1) {
      x0 = fmaxf(s[0], s[1]); x1 = fmaxf(s[2], s[3]);
#pragma unroll
      for (int jj = 1; jj < 8; jj++) {
        x0 = fmaxf(x0, fmaxf(s[4 * jj], s[4 * jj + 1]));
        x1 = fmaxf(x1, fmaxf(s[4 * jj + 2], s[4 * jj + 3]));
      }
      x0 = fmaxf(x0, __shfl_xor_sync(0xffffffffu, x0, 1));
      x1 = fmaxf(x1, __shfl_xor_sync(0xffffffffu, x1, 1));
      x0 = fmaxf(x0, __shfl_xor_sync(0xffffffffu, x0, 2));
      x1 = fmaxf(x1, __shfl_xor_sync(0xffffffffu, x1, 2));
    };
    auto exps = [&](uint32_t (&pp)[16], float& r0, float& r1) {
      float t0, t1, t2, t3;
#pragma unroll
      for (int jj = 0; jj < 8; jj++) {
        const float e0 = ex2(fmaf(s[4 * jj], SC, b0)), e1 = ex2(fmaf(s[4 * jj + 1], SC, b0));
        const float e2 = ex2(fmaf(s[4 * jj + 2], SC, b1)), e3 = ex2(fmaf(s[4 * jj + 3], SC, b1));
        if (jj == 0) { t0 = e0; t1 = e1; t2 = e2; t3 = e3; } else { t0 += e0; t1 += e1; t2 += e2; t3 += e3; }
        pp[2 * jj] = pack_bf16(e0, e1); pp[2 * jj + 1] = pack_bf16(e2, e3);
      }
      r0 = t0 + t1; r1 = t2 + t3;
    };

    const bool up = w == which;
    const int n = 2 * qt + 2, nw = n - up;
    int fd = which ? 0 : 2 * n - 1;
    const int dir = which ? 1 : -1;
    auto skip = [&]() { r.next(); fd += dir; };
    auto give = [&](uint32_t sl, int d) {
      lane0_arrive(bar_addr(sb, B_RG_EMPTY + sl), (d & ~2) == 0 ? 2 : 1, lane);
    };
    if (which && up) skip();
    uint32_t ks = take();
    TS(62 + which);
    TR(20);
    prep_qk(sb + ks * SLOT);
    turn_begin();
    wg_fence();
#pragma unroll
    for (int kk = 0; kk < 16; kk++)
      wgmma_rs_n64(s, pk[4 * kk], pk[4 * kk + 1], pk[4 * kk + 2], pk[4 * kk + 3], desc_add(dk, (kk >> 2) * 8192 + (kk & 3) * 32), kk != 0);
    wg_commit();
    turn_end();
    TR(21);
    if (!which && (up || !CV_FX)) conv_finish();
    TR(23);
    if (which) mbar_wait(st_empty, 0);
    if ((which || !CV_QX) && !up) store_blocks<0, Q_PRE>(qreg, lb, pk);
    TR(24);
    wg_wait<0>();
    TR(22);
    reg_fence(s);
    reg_fence(pk);
    give(ks, fd);
    fd += dir;
    if (which && up) { skip(); store_blocks<0, 4>(qreg, lb, pk); }
    if (which || nw == 1) mask_diag();
    row_max(b0, b1);
    if ((which || !CV_QX) && !up) store_blocks<16 * Q_PRE, 4 - Q_PRE>(qreg + Q_PRE * 8192, lb, pk);
    b0 *= -SC; b1 *= -SC;
#pragma unroll
    for (int i = 0; i < 128; i++) acc[i] = 0.f;
    exps(pa, l0, l1);
    if (CV_FX && !which && !up) conv_finish();
    if (which && nw == 1) { fence_async_smem(); warp_arrive(bar_addr(sb, B_QFREE + w), lane); }
#pragma unroll 1
    for (int jj = 1; jj < nw; jj++) {
      ks = take();
      const uint32_t vs = take();
      if (jj == 1) fence_async_smem();
      TR(30);
#pragma unroll
      for (int i = 0; i < 32; i++) s[i] = 0.f;
      prep_qk(sb + ks * SLOT);
      prep_pv(sb + vs * SLOT);
      turn_begin();
      wg_fence();
      issue_qk();
      wg_commit();
      issue_pv(1);
      wg_commit();
      turn_end();
      TR(31);
      wg_wait<1>();
      TR(32);
      reg_fence(s);
      give(ks, fd);
      if (jj == nw - 1) {
        if (!which) mask_diag();
        else if (lane == 0) mbar_arrive(bar_addr(sb, B_QFREE + w));
      }
      uint32_t pn[16];
      float t0, t1, a0 = 1.f, a1 = 1.f;
      exps(pn, t0, t1);
      const bool redo = __any_sync(0xffffffffu, !(t0 + t1 <= 65536.f));
      if (redo) {
        row_max(a0, a1);
        const float c0 = fminf(b0, -SC * a0), c1 = fminf(b1, -SC * a1);
        a0 = ex2(c0 - b0); a1 = ex2(c1 - b1);
        b0 = c0; b1 = c1;
        l0 *= a0; l1 *= a1;
        exps(pn, t0, t1);
      }
      l0 += t0; l1 += t1;
      wg_wait<0>();
      reg_fence(acc);
      reg_fence(pa);
      give(vs, fd + dir);
      fd += 2 * dir;
      if (redo) {
#pragma unroll
        for (int i = 0; i < 32; i++) { acc[4 * i] *= a0; acc[4 * i + 1] *= a0; acc[4 * i + 2] *= a1; acc[4 * i + 3] *= a1; }
      }
#pragma unroll
      for (int i = 0; i < 16; i++) pa[i] = (i & 1) ? pn[i] ^ (one - 1) : pn[i] * one;
    }
    if (!which && up) skip();
    const uint32_t vs = take();
    TR(40);
    prep_pv(sb + vs * SLOT);
    turn_begin();
    wg_fence();
    issue_pv(1);
    wg_commit();
    turn_end();
    TR(41);
    if (!which && up) r.next();
    ws = take();
    l0 += __shfl_xor_sync(0xffffffffu, l0, 1); l1 += __shfl_xor_sync(0xffffffffu, l1, 1);
    l0 += __shfl_xor_sync(0xffffffffu, l0, 2); l1 += __shfl_xor_sync(0xffffffffu, l1, 2);
    float i0, i1;
    asm volatile("rcp.approx.ftz.f32 %0, %1;" : "=f"(i0) : "f"(l0));
    asm volatile("rcp.approx.ftz.f32 %0, %1;" : "=f"(i1) : "f"(l1));
    uint32_t xs = 0;
    if (!which) xs = take();
    wg_wait<0>();
    TR(42);
    reg_fence(acc);
    reg_fence(pa);
    give(vs, fd);
    TS(7 + 3 * which);
#pragma unroll
    for (int i = 0; i < 32; i++) {
      pk[2 * i]     = pack_bf16(acc[4 * i] * i0, acc[4 * i + 1] * i0);
      pk[2 * i + 1] = pack_bf16(acc[4 * i + 2] * i1, acc[4 * i + 3] * i1);
    }
    TS(8 + 3 * which); TR(46);
    if (which) break;
    TS(31);
    uint32_t xaddr = sb + xs * SLOT + (w ^ 1) * 8192;
#pragma unroll 1
    for (int kc = 0;; kc++) {
      TR(11);
      const uint64_t da = desc_k(xaddr), db = desc_mn(sb + ws * SLOT);
      turn_begin();
      wg_fence();
#pragma unroll
      for (int kk = 0; kk < 4; kk++) wgmma_ss_n256_tb(acc, desc_add(da, kk * 32), desc_add(db, kk * 2048), (kc | kk) != 0);
      wg_commit();
      turn_end();
      TR(13);
      const int cb = kc;
      if (cb >= 1 && cb <= 4) { fence_async_smem(); warp_arrive(bar_addr(sb, B_CTXS + 4 * w + cb - 1), lane); }
      if ((unsigned)cb < 4) {
        if (cb & 2) { if (cb & 1) store_blocks<48, 1>(qreg + 24576, lb, pk); else store_blocks<32, 1>(qreg + 16384, lb, pk); }
        else        { if (cb & 1) store_blocks<16, 1>(qreg + 8192, lb, pk);  else store_blocks<0, 1>(qreg, lb, pk); }
      }
      TR(15);
      wg_wait<0>();
      release(bar_addr(sb, B_RG_EMPTY + ws), lane);
      if (!(kc & 1)) release(bar_addr(sb, B_RG_EMPTY + xs), lane);
      if (kc == 6) break;
      ws = take();
      if (!(kc & 1)) { xs = take(); xaddr = sb + xs * SLOT + (w ^ 1) * 8192; } else xaddr += 16384;
    }
    reg_fence(acc);
    TS(61); TR(16);
#pragma unroll
    for (int i = 0; i < 64; i++) pk[i] = pack_bf16(acc[2 * i], acc[2 * i + 1]);
    TS(9); TR(19);
    qt = 15 - qt;
  }

  {
    float oa[32], ob[32];
#pragma unroll
    for (int i = 0; i < 32; i++) { oa[i] = 0.f; ob[i] = 0.f; }
    auto stage_o = [&](float (&o)[32], int ch) {
      reg_fence(o);
      uint32_t q[16];
#pragma unroll
      for (int i = 0; i < 16; i++) q[i] = pack_bf16(o[2 * i], o[2 * i + 1]);
      if (ch >= 2) mbar_wait(bar_addr(sb, B_S2_EMPTY + w * 2 + (ch & 1)), ((ch >> 1) - 1) & 1);
      store_blocks<0, 1>(qreg + (ch & 1) * 8192, lb, q);
    };
    auto hand_over = [&](int ch) {
      fence_async_smem();
      warp_arrive(bar_addr(sb, B_S2_FULL + w * 2 + (ch & 1)), lane);
    };
    uint32_t pk2[64];
    uint32_t p2 = 0;
    auto chunk = [&](int ch, auto first, float (&o)[32], float (&oprev)[32]) {
      constexpr bool FIRST = decltype(first)::value;
      const uint32_t s1 = FIRST ? ws : take();
      TR(50);
      const uint64_t d1 = desc_mn(sb + s1 * SLOT);
      turn_begin();
      wg_fence();
#pragma unroll
      for (int kk = 0; kk < 16; kk++) {
        wgmma_rs_n64_tb(o, pk[4 * kk], pk[4 * kk + 1], pk[4 * kk + 2], pk[4 * kk + 3], desc_add(d1, kk * 2048), kk != 0);
        if (kk == ARRIVE_KK) turn_end();
      }
      wg_commit();
      TR(51);
      if constexpr (!FIRST) {
        wg_wait<1>();
        release(bar_addr(sb, B_RG_EMPTY + p2), lane);
        stage_o(oprev, ch - 1);
      } else {
        mbar_wait(bar_addr(sb, B_CTXF + w), 0);
#pragma unroll
        for (int kk = 0; kk < 16; kk++) {
          uint32_t f[4];
          ldsm4(f, qreg + (kk >> 2) * 8192 + (lb ^ ((kk & 3) << 5)));
          pk2[4 * kk] = f[0]; pk2[4 * kk + 1] = f[1]; pk2[4 * kk + 2] = f[2]; pk2[4 * kk + 3] = f[3];
        }
      }
      const uint32_t s2 = take();
      TR(53);
      const uint64_t d2 = desc_mn(sb + s2 * SLOT);
      turn_begin();
      wg_fence();
#pragma unroll
      for (int kk = 0; kk < 16; kk++) {
        wgmma_rs_n64_tb(o, pk2[4 * kk], pk2[4 * kk + 1], pk2[4 * kk + 2], pk2[4 * kk + 3], desc_add(d2, kk * 2048), 1);
        if (kk == ARRIVE_KK && (ch < 6 || w == 1)) turn_end();
      }
      wg_commit();
      TR(54);
      if (!FIRST) hand_over(ch - 1);
      wg_wait<1>();
      TR(55);
      release(bar_addr(sb, B_RG_EMPTY + s1), lane);
      p2 = s2;
    };
    chunk(0, Int<1>(), oa, ob);
#pragma unroll 1
    for (int ch = 1; ch < 7; ch += 2) { chunk(ch, Int<0>(), ob, oa); chunk(ch + 1, Int<0>(), oa, ob); }
    wg_wait<0>();
    TR(58);
    reg_fence(pk);
    reg_fence(pk2);
    stage_o(oa, 6);
    hand_over(6);
  }
  TS(12); TR(59);
  if (threadIdx.x == 128) ST(14);
  if ((threadIdx.x & 127) == 0) GT(54 + w);

  TS(16); TS(18); TS(17);
  TR(99); TR_END();
  TS(13); TSG(14);
}

#define CONV_STAGGER_NS 1200
namespace ssm {
#define CONV_GROUPS (D_SPARE / 8 / NCONV)
constexpr int GROUPS = CONV_GROUPS;
constexpr uint32_t ZROWS = 16;
constexpr uint32_t CHAN = (ZROWS + 256 + 1) * 16;
constexpr uint32_t XBUF = 8 * CHAN;
constexpr uint32_t OFF_X = 0;
constexpr uint32_t HCOPY = 4160;
constexpr uint32_t OFF_H = 2 * XBUF;
constexpr uint32_t HWARP = 3 * HCOPY;
constexpr uint32_t IO_K = 128, IO_V = IO_K + 4096, IO_Q = IO_V + 4096, IOBUF = IO_Q + 4096;
constexpr uint32_t OFF_IO = (OFF_H + 8 * HWARP + 127) / 128 * 128;
constexpr uint32_t END = OFF_IO + 4 * IOBUF;
static_assert(IOBUF % 128 == 0 && OFF_H % 16 == 0, "TMA destination alignment");
static_assert(END <= BARS, "smem");
enum : uint32_t { B_XREADY = 0, B_ZDONE = 2, B_KV = 4, B_Q = 8, B_HRAW = 12, B_QLAST = 20 };
constexpr int CW_BAR = 4;

__device__ __forceinline__ int group_d0(int cidx, int grp) { return (grp * NCONV + cidx) * 8; }
__device__ __forceinline__ uint32_t x_lane(int lane) { return (lane & 7) * CHAN + (ZROWS + (lane >> 3)) * 16; }
__device__ __forceinline__ uint32_t t_lane(int lane) { return (uint32_t)(8 * (lane >> 3) + 7 - (lane & 7)) * 16; }
struct Taps { uint32_t s[4]; };
__device__ __forceinline__ Taps load_taps(const Params& p, int d0, int c) {
  const uint2 s0 = __ldg(reinterpret_cast<const uint2*>(p.a_shift + (d0 + 2 * c) * 4)), s1 = __ldg(reinterpret_cast<const uint2*>(p.a_shift + (d0 + 2 * c + 1) * 4));
  return Taps{{__byte_perm(s0.x, s1.x, 0x5410), __byte_perm(s0.x, s1.x, 0x7632), __byte_perm(s0.y, s1.y, 0x5410), __byte_perm(s0.y, s1.y, 0x7632)}};
}
__device__ __forceinline__ uint32_t short_conv(const Taps& t, uint32_t k0, uint32_t k1, uint32_t k2, uint32_t k3, uint32_t v) {
  return bmul(bfma(k3, t.s[0], bfma(k2, t.s[1], bfma(k1, t.s[2], bmul(k0, t.s[3])))), v);
}
__device__ __forceinline__ void gate_chunk(uint32_t xa, uint32_t qa) {
#pragma unroll 4
  for (int i = 0; i < 8; i++) {
    uint32_t zz[4], qq[4];
    ldsm4t(zz, xa + i * 64);
    ldsm4(qq, qa + i * 512);
    stsm4(qa + i * 512, bmul(qq[0], zz[0]), bmul(qq[1], zz[1]), bmul(qq[2], zz[2]), bmul(qq[3], zz[3]));
  }
}

__device__ __forceinline__ void io_warp(const Params& p, uint32_t sb, int cidx, int wq) {
  const int lane = threadIdx.x & 31;
  const uint32_t io = sb + OFF_IO + wq * IOBUF, bkv = bar_addr(sb, B_KV + wq), bq = bar_addr(sb, B_Q + wq);
  auto load_kv = [&](int e) {
    __syncwarp();
    if (lane != 0) return;
    const int d0 = group_d0(cidx, e >> 1), row = (2 * wq + (e & 1)) * 256;
    if (e < 2 * GROUPS) {
      mbar_expect_tx(bkv, IO_Q);
      tma_ld2(io, &p.ak8, bkv, d0, row - 8);
      tma_ld2(io + IO_K, &p.ak, bkv, d0, row);
      tma_ld2(io + IO_V, &p.av, bkv, d0, row);
    } else {
      const uint32_t bar = bar_addr(sb, B_QLAST + 2 * wq + 1);
      mbar_expect_tx(bar, 4096);
      tma_ld2(io + IO_K, &p.aq, bar, group_d0(cidx, GROUPS - 1), row + 256);
    }
  };
  auto load_q = [&](int e) {
    __syncwarp();
    if (lane != 0) return;
    const uint32_t bar = e < 2 * GROUPS - 2 ? bq : bar_addr(sb, B_QLAST + 2 * wq);
    mbar_expect_tx(bar, 4096);
    tma_ld2(io + IO_Q, &p.aq, bar, group_d0(cidx, e >> 1), (2 * wq + (e & 1)) * 256);
  };
  TR_DECL;
  TR(0);
  load_kv(0);
  const uint32_t xl = sb + OFF_X + x_lane(lane) + wq * 1024, tl = io + t_lane(lane);
#pragma unroll 1
  for (int grp = -2; grp + 1 < GROUPS; grp++) {
    const bool more = grp + 2 < GROUPS;
    const Taps taps = load_taps(p, group_d0(cidx, more ? grp + 2 : 0), lane & 3);
    PCLK(c0);
    if (grp >= 0) mbar_wait_nap(bar_addr(sb, B_ZDONE + (grp & 1)), (grp >> 1) & 1);
    PACC(tp, c0);
    PCLK(c1);
    TR(80);
#pragma unroll 1
    for (int i = 0; i < 2; i++) {
      const uint32_t xa = xl + (grp & 1) * XBUF + i * 512;
      if (grp >= 0) {
        mbar_wait_nap(bq, i);
        TR(81);
        gate_chunk(xa, tl + IO_Q);
      }
      if (more) {
        TR(82);
        mbar_wait_nap(bkv, i);
        TR(83);
#pragma unroll 2
        for (int u = 0; u < 8; u++) {
          const uint32_t ka = tl + IO_K + u * 512;
          uint32_t k0[4], k1[4], k2[4], k3[4], vv[4];
          ldsm4(k0, ka - 48); ldsm4(k1, ka - 32); ldsm4(k2, ka - 16); ldsm4(k3, ka); ldsm4(vv, ka + 4096);
          stsm4t(xa + u * 64, short_conv(taps, k0[0], k1[0], k2[0], k3[0], vv[0]), short_conv(taps, k0[1], k1[1], k2[1], k3[1], vv[1]),
                 short_conv(taps, k0[2], k1[2], k2[2], k3[2], vv[2]), short_conv(taps, k0[3], k1[3], k2[3], k3[3], vv[3]));
        }
        load_kv(2 * (grp + 2) + i + 1);
        TR(84);
        if (i == 1) warp_arrive(bar_addr(sb, B_XREADY + (grp & 1)), lane);
      }
      if (grp >= 0) {
        fence_async_smem();
        __syncwarp();
        if (lane == 0) {
          tma_st2(&p.ao, io + IO_Q, group_d0(cidx, grp), (2 * wq + i) * 256);
          bulk_commit();
          bulk_wait_read();
        }
      }
      if (2 * grp + i + 1 >= 0) load_q(2 * grp + i + 1);
      TR(85);
    }
    PACC(te, c1);
  }
  if (lane == 0) bulk_wait_all();
  TR(99); TR_END();
}

__device__ __forceinline__ void conv_warp(const Params& p, uint32_t sb, int cidx, int ch) {
  const int lane = threadIdx.x & 31;
  const uint32_t hE0 = sb + OFF_H + ch * HWARP, hO = hE0 + HCOPY;
  const uint32_t hbar = bar_addr(sb, B_HRAW + ch);
  auto fetch_h = [&](int grp) {
    if (lane == 0) {
      mbar_expect_tx(hbar, 4096);
      asm volatile("cp.async.bulk.shared::cluster.global.mbarrier::complete_tx::bytes [%0], [%1], %2, [%3];"
                   :: "r"(hE0 + (grp & 1) * 2 * HCOPY + 32), "l"(p.a_ssmk + (size_t)(group_d0(cidx, grp) + ch) * SEQ), "r"(4096), "r"(hbar) : "memory");
    }
  };
  TR_DECL;
  TR(0);
  fetch_h(0);
#pragma unroll 1
  for (int grp = 0; grp < GROUPS; grp++) {
    const uint32_t xc = sb + OFF_X + (grp & 1) * XBUF + ch * CHAN;
    const uint32_t Dd = (uint32_t)__ldg(reinterpret_cast<const unsigned short*>(p.a_D + group_d0(cidx, grp) + ch)) * 0x10001u;
    PCLK(k0);
    mbar_wait(hbar, grp & 1);
    const uint32_t hE = hE0 + (grp & 1) * 2 * HCOPY;
    if (grp + 1 < GROUPS) fetch_h(grp + 1);
#pragma unroll
    for (int i = 0; i < 8; i++) {
      const uint32_t o = 32 + (i * 32 + lane) * 16;
      const uint4 w = lds16(hE + o);
      const uint32_t nx = lds4(hE + o + 16);
      sts16(hO + o, __byte_perm(w.x, w.y, 0x5432), __byte_perm(w.y, w.z, 0x5432), __byte_perm(w.z, w.w, 0x5432), __byte_perm(w.w, nx, 0x5432));
      if (o == 32) asm volatile("st.shared.u32 [%0], %1;" :: "r"(hO + 28), "r"(w.x << 16) : "memory");
    }
    __syncwarp();
    const uint32_t ha = cv_h_lane(lane, hE, hO), xa = xc + cv_x_lane(lane);
    TR(71);
    mbar_wait(bar_addr(sb, B_XREADY + (grp & 1)), (grp >> 1) & 1);
    TR(72);
    if (grp == 0 && ch >= 4) __nanosleep(CONV_STAGGER_NS);
    PACC(tw, k0);
    PCLK(k1);
    float acc[16][4];
#pragma unroll
    for (int i = 0; i < 16; i++) { acc[i][0] = 0.f; acc[i][1] = 0.f; acc[i][2] = 0.f; acc[i][3] = 0.f; }
#pragma unroll 1
    for (int r = 0; r < 8; r++) {
      uint32_t fx[16][4], fh[16][2];
#pragma unroll
      for (int i = 0; i < 16; i++) { fh[i][0] = lds4(ha + i * 256 + r * 32); fh[i][1] = lds4(ha + i * 256 + r * 32 + 16); }
#pragma unroll
      for (int i = 0; i < 16; i++) ldsm4(fx[i], xa + i * 256 - r * 32);
#pragma unroll
      for (int sx = 0; sx < 16; sx++)
#pragma unroll
        for (int jj = 0; jj < 16 - sx; jj++) mma16816(acc[jj + sx], fx[sx], fh[jj][0], fh[jj][1]);
    }
    PACC(tm, k1);
    PCLK(k2);
    TR(73);
#pragma unroll
    for (int i = 0; i < 8; i++) {
      uint32_t x[4];
      const uint32_t ad = xc + (ZROWS + lane) * 16 + i * 512;
      ldsm4(x, ad);
      stsm4(ad, badd(pack_bf16(acc[2 * i][0], acc[2 * i][1]), bmul(x[0], Dd)), badd(pack_bf16(acc[2 * i][2], acc[2 * i][3]), bmul(x[1], Dd)),
            badd(pack_bf16(acc[2 * i + 1][0], acc[2 * i + 1][1]), bmul(x[2], Dd)), badd(pack_bf16(acc[2 * i + 1][2], acc[2 * i + 1][3]), bmul(x[3], Dd)));
    }
    if (grp + 1 < GROUPS) warp_arrive(bar_addr(sb, B_ZDONE + (grp & 1)), lane);
    PACC(tr, k2);
    TR(74);
  }
  {
    mbar_wait(bar_addr(sb, B_QLAST + ch), 0);
    named_sync(CW_BAR, 256);
    TR(75);
    const uint32_t qb = sb + OFF_IO + (ch >> 1) * IOBUF + ((ch & 1) ? IO_K : IO_Q);
    gate_chunk(sb + OFF_X + ((GROUPS - 1) & 1) * XBUF + x_lane(lane) + ch * 512, qb + t_lane(lane));
    fence_async_smem();
    __syncwarp();
    if (lane == 0) { tma_st2(&p.ao, qb, group_d0(cidx, GROUPS - 1), ch * 256); bulk_commit(); bulk_wait_all(); }
    TR(99); TR_END();
  }
}

__device__ __forceinline__ void init(uint32_t sb) {
  if (threadIdx.x < 16 * ZROWS) sts16(sb + OFF_X + (threadIdx.x >> 4) * CHAN + (threadIdx.x & 15) * 16, 0, 0, 0, 0);
  if (threadIdx.x < 96) sts16(sb + OFF_H + (threadIdx.x >> 2) * HCOPY + (threadIdx.x & 1) * 16 + ((threadIdx.x & 2) ? 4128 : 0), 0, 0, 0, 0);
  if (threadIdx.x == 0) {
    for (int i = 0; i < 2; i++) { mbar_init(bar_addr(sb, B_XREADY + i), 4); mbar_init(bar_addr(sb, B_ZDONE + i), 8); }
    for (int i = 0; i < 4; i++) { mbar_init(bar_addr(sb, B_KV + i), 1); mbar_init(bar_addr(sb, B_Q + i), 1); }
    for (int i = 0; i < 8; i++) { mbar_init(bar_addr(sb, B_HRAW + i), 1); mbar_init(bar_addr(sb, B_QLAST + i), 1); }
    fence_async_smem();
  }
  named_sync(0, NTHREADS);
}
}

__device__ __forceinline__ void ssm_side_work(const Params& p, uint32_t sb, unsigned epoch) {
  const Role ro = get_role();
  const int h = ro.h, j = ro.j;
  const int lane = threadIdx.x & 31, g = lane >> 2, c = lane & 3;
  const int d0 = D_SPARE + 8 * h;
  uint8_t* xs = g_xs + (size_t)(h * 8 + g) * CV_BYTES + c * 4;
  auto xrow = [&](int beta) { return xs + (16 + beta) * 16; };
  {
    const uint4* hp = reinterpret_cast<const uint4*>(p.a_ssmk + (size_t)(d0 + j) * SEQ) + lane;
    uint8_t* he = g_xs + (size_t)(h * 8 + j) * CV_BYTES + CV_HE;
#pragma unroll 2
    for (int i = 0; i < 8; i++) {
      const uint4 wv = __ldg(hp + i * 32);
      const uint32_t nx = i * 32 + lane < 255 ? __ldg(reinterpret_cast<const uint32_t*>(hp + i * 32 + 1)) : 0u;
      const uint32_t o = 32 + (i * 32 + lane) * 16;
      *reinterpret_cast<uint4*>(he + o) = wv;
      *reinterpret_cast<uint4*>(he + CV_HCOPY + o) =
          make_uint4(__byte_perm(wv.x, wv.y, 0x5432), __byte_perm(wv.y, wv.z, 0x5432), __byte_perm(wv.z, wv.w, 0x5432), __byte_perm(wv.w, nx, 0x5432));
      if (o == 32) *reinterpret_cast<uint32_t*>(he + CV_HCOPY + 28) = wv.x << 16;
    }
    if (lane == 0) *reinterpret_cast<uint32_t*>(he + CV_D - CV_HE) = (uint32_t)__ldg(reinterpret_cast<const unsigned short*>(p.a_D + d0 + j)) * 0x10001u;
  }
  {
    const ssm::Taps taps = ssm::load_taps(p, d0, c);
    const uint32_t* kp = reinterpret_cast<const uint32_t*>(p.a_k + (size_t)(256 * j + 7 - g) * DA + d0) + c;
    const uint32_t* vp = reinterpret_cast<const uint32_t*>(p.a_v + (size_t)(256 * j + 7 - g) * DA + d0) + c;
    uint32_t kprev = j > 0 ? __ldg(kp - 8 * (DA / 2)) : 0u;
#pragma unroll 1
    for (int i0 = 0; i0 < 32; i0 += 8) {
      uint32_t kk[8], vv[8];
#pragma unroll
      for (int i = 0; i < 8; i++) { kk[i] = __ldg(kp + (i0 + i) * 8 * (DA / 2)); vv[i] = __ldg(vp + (i0 + i) * 8 * (DA / 2)); }
#pragma unroll
      for (int i = 0; i < 8; i++) {
        const uint32_t k2 = __shfl_sync(0xffffffffu, g < 1 ? kprev : kk[i], (lane + 4) & 31);
        const uint32_t k1 = __shfl_sync(0xffffffffu, g < 2 ? kprev : kk[i], (lane + 8) & 31);
        const uint32_t k0 = __shfl_sync(0xffffffffu, g < 3 ? kprev : kk[i], (lane + 12) & 31);
        *reinterpret_cast<uint32_t*>(xrow(32 * j + i0 + i)) = transpose8(ssm::short_conv(taps, k0, k1, k2, kk[i], vv[i]));
        kprev = kk[i];
      }
    }
    __syncwarp();
    if (lane == 0) {
      flag_signal(&g_flags.xs_ready[h].v);
      flag_wait(&g_flags.xs_ready[h].v, 8, epoch);
      fence_async_all();
      mbar_arrive(bar_addr(sb, B_XS));
    }
  }
  if (lane == 0) {
    for (int i = 0; i < 3; i++) {
      flag_wait(&g_flags.kv_ready[3 * h + i].v, 16, epoch);
      fence_async_all();
      mbar_arrive(bar_addr(sb, B_KV + i));
    }
    mbar_wait_nap(bar_addr(sb, B_CONV), 0);
    flag_signal(&g_flags.zs_ready[h].v);
    flag_wait(&g_flags.zs_ready[h].v, 8, epoch);
    asm volatile("red.relaxed.gpu.global.add.u64 [%0], 1;" :: "l"(&g_flags.done) : "memory");
  }
  __syncwarp();
  fence_async_all();
  const uint32_t qb = q_region(sb, 1) + 16384, zb = qb + 4096, bar = bar_addr(sb, B_GATE);
  constexpr uint32_t ZCH = 528;
  mbar_wait_slow(bar_addr(sb, B_GFREE), 0);
  if (lane == 0) { mbar_expect_tx(bar, 8192); tma_ld2(qb, &p.aq, bar, d0, 256 * j); }
  __syncwarp();
  if (lane < 8) bulk_ld(zb + lane * ZCH, g_xs + (size_t)(h * 8 + lane) * CV_BYTES + (16 + 32 * j) * 16, 512, bar);
  mbar_wait(bar, 0);
  ssm::gate_chunk(zb + (lane & 7) * ZCH + (lane >> 3) * 16, qb + ssm::t_lane(lane));
  fence_async_smem();
  __syncwarp();
  if (lane == 0) { tma_st2(&p.ao, qb, d0, 256 * j); bulk_commit(); bulk_wait_all(); }
}

__global__ void __cluster_dims__(2, 1, 1) __launch_bounds__(NTHREADS, 1)
concat_heads__ssm_conv_h3__compressed_kv_cla__prompt_kernel(uint8_t* xs, uint32_t one, const __grid_constant__ Params p) {
  if (threadIdx.x == 0) { prefetch_map(&p.wuk); prefetch_map(&p.ckv); }
  extern __shared__ uint8_t smem_raw[];
  if (threadIdx.x == 96) { ST(0); STG_(10); }
  const uint32_t sb = (smem_u32(smem_raw) + 1023) & ~1023u;
  const int warp = __shfl_sync(0xffffffffu, threadIdx.x >> 5, 0);
  const int wg = warp >> 2;
  const int cta = blockIdx.x;
  const bool attn = cta < NMAIN;
  if (attn && (threadIdx.x >> 5) == 4) {
    const Role ro = get_role();
    auto load = [&](int k) {
      const uint32_t full = bar_addr(sb, B_P1_FULL + k), dst = sb + k * P1_STAGE;
      mbar_expect_tx(full, P1_STAGE);
      tma_ld2(dst, &p.ckv, full, k * 64, kv_block(ro.j, 0) * 128);
      tma_ld3(dst + 16384, &p.wuk, full, 0, k * 64, ro.h * 4);
    };
    if (threadIdx.x == 128) {
      for (int i = 0; i < 4; i++) mbar_init(bar_addr(sb, B_P1_FULL + i), 1);
      asm volatile("fence.mbarrier_init.release.cluster;" ::: "memory");
      ST(1);
      load(0);
    }
    __syncwarp();
    named_arrive(0, NTHREADS);
    if (threadIdx.x == 128) {
      for (int k = 1; k < EARLY_LD; k++) load(k);
      ST(2);
    }
    __syncwarp();
  }
  const int lane = threadIdx.x & 31;
  if (wg == 0) {
    if (!attn) {
      asm volatile("setmaxnreg.dec.sync.aligned.u32 72;");
      if (threadIdx.x == 0) GT(0);
      if (one) { ssm::init(sb); ssm::io_warp(p, sb, cta - NMAIN, fresh_warp()); }
      if (threadIdx.x == 0) GT(14);
      return;
    }
    asm volatile("setmaxnreg.dec.sync.aligned.u32 40;");
    named_arrive(PP_BAR + 1, 256);
    if (warp == 2) {
      if (lane == 0) {
        for (int i = 0; i < 4; i++) mbar_init(bar_addr(sb, B_P1_EMPTY + i), 8);
        for (int i = 0; i < NSLOT; i++) {
          mbar_init(bar_addr(sb, B_RG_FULL + i), 1); mbar_init(bar_addr(sb, B_RG_EMPTY + i), 8);
        }
        for (int i = 0; i < 2; i++) { mbar_init(bar_addr(sb, B_ST_FULL + i), 4); mbar_init(bar_addr(sb, B_ST_EMPTY + i), 1); }
        mbar_init(bar_addr(sb, B_XS), 1); mbar_init(bar_addr(sb, B_CONV), 8); mbar_init(bar_addr(sb, B_GATE), 1); mbar_init(bar_addr(sb, B_GFREE), 1);
        for (int i = 0; i < 3; i++) mbar_init(bar_addr(sb, B_KV + i), 1);
        for (int i = 0; i < 8; i++) mbar_init(bar_addr(sb, B_CTXS + i), 4);
        for (int i = 0; i < 4; i++) { mbar_arrive(bar_addr(sb, B_RG_FULL + i)); if (i < 3) mbar_arrive_n(bar_addr(sb, B_RG_EMPTY + i), 8); }
        for (int i = 0; i < 4; i++) { mbar_init(bar_addr(sb, B_S2_FULL + i), 4); mbar_init(bar_addr(sb, B_S2_EMPTY + i), 1); }
        for (int i = 0; i < 2; i++) { mbar_init(bar_addr(sb, B_QFREE + i), 4); mbar_init(bar_addr(sb, B_CTXF + i), 1); }
        asm volatile("fence.mbarrier_init.release.cluster;" ::: "memory");
        ST(3);
      }
      __syncwarp();
      named_arrive(0, NTHREADS);
    } else {
      named_sync(0, NTHREADS);
    }
    if (threadIdx.x == 96) ST(4);
    if (warp == 0) {
      if (lane == 0) producer_main(p, sb);
    } else if (warp < 3) {
      storer_main(p, sb);
    } else {
      const unsigned epoch = load_epoch();
      mbar_wait(bar_addr(sb, B_P1_FULL + 3), 0);
      __nanosleep(SIDE_DELAY_NS);
      ssm_side_work(p, sb, epoch);
    }
  } else {
    if (attn) {
      asm volatile("setmaxnreg.inc.sync.aligned.u32 232;");
      if (threadIdx.x == 256) ST(5);
      if (one) consumer_main(p, sb, xs, one);
    } else {
      asm volatile("setmaxnreg.inc.sync.aligned.u32 216;");
      if (threadIdx.x == 128) { GT(12); PT(10); }
      if (one) { ssm::init(sb); ssm::conv_warp(p, sb, cta - NMAIN, fresh_warp() - 4); }
      if (threadIdx.x == 128) { PT(9); GT(13); }
    }
  }
}

typedef CUresult (*EncodeTiledFn)(CUtensorMap*, CUtensorMapDataType, cuuint32_t, void*, const cuuint64_t*, const cuuint64_t*,
                                  const cuuint32_t*, const cuuint32_t*, CUtensorMapInterleave, CUtensorMapSwizzle,
                                  CUtensorMapL2promotion, CUtensorMapFloatOOBfill);

void make_map(EncodeTiledFn enc, CUtensorMap* m, const void* ptr, int rank, const uint64_t* dims, const uint64_t* strides, const uint32_t* box) {
  cuuint64_t d[3], s[2]; cuuint32_t b[3], e[3] = {1, 1, 1};
  for (int i = 0; i < rank; i++) { d[i] = dims[i]; b[i] = box[i]; if (i) s[i - 1] = strides[i - 1]; }
  enc(m, CU_TENSOR_MAP_DATA_TYPE_BFLOAT16, rank, const_cast<void*>(ptr), d, s, b, e, CU_TENSOR_MAP_INTERLEAVE_NONE,
      CU_TENSOR_MAP_SWIZZLE_128B, CU_TENSOR_MAP_L2_PROMOTION_L2_256B, CU_TENSOR_MAP_FLOAT_OOB_FILL_NONE);
}
void map2(EncodeTiledFn enc, CUtensorMap* m, const void* ptr, uint64_t cols, uint64_t rows, uint32_t bc, uint32_t br) {
  const uint64_t dims[2] = {cols, rows}, st[1] = {cols * 2}; const uint32_t box[2] = {bc, br};
  make_map(enc, m, ptr, 2, dims, st, box);
}
void map2_plain(EncodeTiledFn enc, CUtensorMap* m, const void* ptr, uint64_t cols, uint64_t rows, uint32_t bc, uint32_t br) {
  cuuint64_t d[2] = {cols, rows}, st[1] = {cols * 2}; cuuint32_t b[2] = {bc, br}, e[2] = {1, 1};
  enc(m, CU_TENSOR_MAP_DATA_TYPE_BFLOAT16, 2, const_cast<void*>(ptr), d, st, b, e, CU_TENSOR_MAP_INTERLEAVE_NONE,
      CU_TENSOR_MAP_SWIZZLE_NONE, CU_TENSOR_MAP_L2_PROMOTION_L2_128B, CU_TENSOR_MAP_FLOAT_OOB_FILL_NONE);
}
void map3(EncodeTiledFn enc, CUtensorMap* m, const void* ptr, uint64_t rows, uint32_t nblk) {
  const uint64_t dims[3] = {64, rows, 64}, st[2] = {8192, 128}; const uint32_t box[3] = {64, 64, nblk};
  make_map(enc, m, ptr, 3, dims, st, box);
}

}

extern "C" void kernel_launch(void* const* d_in, const int* in_sizes, int n_in, void* d_out, int out_size) {
  (void)in_sizes; (void)n_in; (void)out_size;
  static EncodeTiledFn enc = nullptr;
  static void *kv_ptr = nullptr, *acc_ptr = nullptr, *xs_ptr = nullptr;
  if (!enc) {
    void* fn = nullptr; cudaDriverEntryPointQueryResult qr;
    cudaGetDriverEntryPoint("cuTensorMapEncodeTiled", &fn, cudaEnableDefault, &qr);
    enc = (EncodeTiledFn)fn;
    cudaGetSymbolAddress(&kv_ptr, g_kv);
    cudaGetSymbolAddress(&acc_ptr, g_ctx);
    cudaGetSymbolAddress(&xs_ptr, g_xs);
    cudaFuncSetAttribute(concat_heads__ssm_conv_h3__compressed_kv_cla__prompt_kernel, cudaFuncAttributeMaxDynamicSharedMemorySize, SMEM_BYTES);
  }
  Params p;
  p.a_q = (const bf16*)d_in[0]; p.a_k = (const bf16*)d_in[1]; p.a_v = (const bf16*)d_in[2];
  map2_plain(enc, &p.aq, d_in[0], DA, SEQ, 8, 256);
  map2_plain(enc, &p.ak, d_in[1], DA, SEQ, 8, 256);
  map2_plain(enc, &p.ak8, d_in[1], DA, SEQ, 8, 8);
  map2_plain(enc, &p.av, d_in[2], DA, SEQ, 8, 256);
  map2_plain(enc, &p.ao, d_out, OUTW, SEQ, 8, 256);
  p.a_shift = (const bf16*)d_in[3]; p.a_ssmk = (const bf16*)d_in[4]; p.a_D = (const bf16*)d_in[5];
  p.out = (bf16*)d_out; p.b_x = (const bf16*)d_in[6]; p.b_wo = (const bf16*)d_in[11];
  map2(enc, &p.x, d_in[6], DM, SEQ, 64, 128);
  map2(enc, &p.ckv, d_in[7], DC, SEQ, 64, 128);
  map3(enc, &p.wq, d_in[8], DM, 4);
  map2_plain(enc, &p.wqp, d_in[8], NH * HD, DM, 256, 4);
  map3(enc, &p.wuk, d_in[9], DC, 4);
  map3(enc, &p.wuv, d_in[10], DC, 4);
  map2(enc, &p.wo, d_in[11], DM, NH * HD, 64, 256);
  map2(enc, &p.part, d_out, OUTW, SEQ, 64, 64);
  p.kv = (uint8_t*)kv_ptr; p.ctx = (uint8_t*)acc_ptr;
  concat_heads__ssm_conv_h3__compressed_kv_cla__prompt_kernel<<<NCTA, NTHREADS, SMEM_BYTES>>>((uint8_t*)xs_ptr, 1u, p);
}
```

```cpp
#include <cuda_runtime.h>
#include <cuda_bf16.h>
#include <cuda.h>
#include <stdint.h>

namespace {

typedef __nv_bfloat16 bf16;

constexpr int SEQ  = 2048;
constexpr int DA   = 448;
constexpr int NH   = 16;
constexpr int HD   = 256;
constexpr int DM   = 448;
constexpr int DC   = 1024;
constexpr int OUTW = DA + DM;
constexpr int NMAIN = 128;
constexpr int NCONV = 4;
constexpr int NCTA  = NMAIN + NCONV;
constexpr int NTHREADS = 384;
constexpr int D_SPARE = 320;

__device__ __align__(1024) bf16 g_kv[2ull * SEQ * NH * HD];
__device__ __align__(1024) bf16 g_ctx[(size_t)NMAIN * 128 * HD];
constexpr uint32_t CV_HE = 272 * 16, CV_HCOPY = 4160, CV_D = CV_HE + 4144, CV_BYTES = CV_HE + 2 * CV_HCOPY;
__device__ __align__(128) uint8_t g_xs[NMAIN * CV_BYTES];
struct alignas(128) Flag { unsigned v; unsigned pad[31]; };
struct Flags {
  Flag kv_ready[3 * NH];
  Flag ctx_ready[NMAIN * 2];
  Flag out_ready[16 * 2];
  Flag xs_ready[NH];
  Flag zs_ready[NH];
  alignas(128) unsigned long long done;
};
__device__ Flags g_flags;
#define TS(i)
#define TSG(i)
#define GT(i)
#define PT(i)
#define WHICH_TS 0
#define PCLK(var)
#define PACC(acc, t0)
#define PDECL
#define PDUMP()

#define CP_DECL
#define CP()
#define ST(i)
#define STG_(i)
#define TR_DECL
#define TR(tag)
#define TR_END()
#define TRG(tag)

struct alignas(64) Params {
  CUtensorMap ckv;
  CUtensorMap wuk;
  CUtensorMap wuv;
  CUtensorMap x;
  CUtensorMap wq;
  CUtensorMap wqp;
  CUtensorMap part;
  CUtensorMap wo;
  CUtensorMap ak, ak8, av, aq, ao;
  const bf16 *a_q, *a_k, *a_v, *a_shift, *a_ssmk, *a_D, *b_x, *b_wo;
  bf16* out;
  uint8_t *kv, *ctx;
};

constexpr uint32_t P1_STAGE = 49152;
constexpr uint32_t P1_STG   = 196608;
constexpr uint32_t SLOT     = 32768;
constexpr int      NSLOT    = 5;
constexpr uint32_t QREG     = 163840;
constexpr uint32_t CV_X = 4 * SLOT + 16384, CV_R = 3 * SLOT;
static_assert(CV_BYTES <= 16384 && CV_BYTES % 128 == 0, "SSM operands");
constexpr uint32_t BARS     = 229376;
constexpr uint32_t SMEM_BYTES = BARS + 512 + 1024;
enum : uint32_t {
  B_P1_FULL = 0, B_P1_EMPTY = 4, B_RG_FULL = 8, B_RG_EMPTY = 13, B_ST_FULL = 18, B_ST_EMPTY = 20,
  B_XS = 22, B_S2_FULL = 28, B_S2_EMPTY = 32, B_QFREE = 36, B_CTXF = 38, B_KV = 40, B_GATE = 43, B_CTXS = 44, B_GFREE = 52, B_CONV = 53, B_COUNT = 54
};

__device__ __forceinline__ uint32_t smem_u32(const void* p) { return (uint32_t)__cvta_generic_to_shared(p); }
__device__ __forceinline__ void mbar_init(uint32_t bar, uint32_t cnt) {
  asm volatile("mbarrier.init.shared::cta.b64 [%0], %1;" :: "r"(bar), "r"(cnt) : "memory");
}
__device__ __forceinline__ void mbar_expect_tx(uint32_t bar, uint32_t bytes) {
  asm volatile("mbarrier.arrive.expect_tx.shared::cta.b64 _, [%0], %1;" :: "r"(bar), "r"(bytes) : "memory");
}
__device__ __forceinline__ void mbar_arrive(uint32_t bar) {
  asm volatile("mbarrier.arrive.shared::cta.b64 _, [%0];" :: "r"(bar) : "memory");
}
__device__ __forceinline__ void mbar_arrive_n(uint32_t bar, uint32_t n) {
  asm volatile("mbarrier.arrive.shared::cta.b64 _, [%0], %1;" :: "r"(bar), "r"(n) : "memory");
}
__device__ __forceinline__ void lane0_arrive(uint32_t bar, uint32_t n, int lane) {
  asm volatile("{\n.reg .pred p;\nsetp.eq.s32 p, %2, 0;\n@p mbarrier.arrive.shared::cta.b64 _, [%0], %1;\n}" :: "r"(bar), "r"(n), "r"(lane) : "memory");
}
__device__ __forceinline__ bool mbar_try(uint32_t bar, uint32_t parity) {
  uint32_t ok;
  asm volatile("{\n.reg .pred p;\nmbarrier.try_wait.parity.shared::cta.b64 p, [%1], %2;\nselp.u32 %0, 1, 0, p;\n}"
               : "=r"(ok) : "r"(bar), "r"(parity) : "memory");
  return ok;
}
#define FLAG_NS 100
#define NAP_NS 100
constexpr uint32_t SPIN_LIMIT = 1u << 24;
__device__ __forceinline__ void mbar_wait(uint32_t bar, uint32_t parity) {
  if (mbar_try(bar, parity)) return;
  uint32_t n = 0;
  while (!mbar_try(bar, parity)) { if (++n > SPIN_LIMIT) __trap(); }
}
__device__ __forceinline__ void mbar_wait_nap(uint32_t bar, uint32_t parity) {
  uint32_t n = 0;
  while (!mbar_try(bar, parity)) { if (++n > (SPIN_LIMIT >> 2)) __trap(); __nanosleep(NAP_NS); }
}
__device__ __forceinline__ void mbar_wait_slow(uint32_t bar, uint32_t parity) {
  uint32_t n = 0;
  while (!mbar_try(bar, parity)) { if (++n > (SPIN_LIMIT >> 4)) __trap(); __nanosleep(500); }
}
__device__ __forceinline__ unsigned load_epoch() {
  unsigned long long e; asm volatile("ld.relaxed.gpu.global.u64 %0, [%1];" : "=l"(e) : "l"(&g_flags.done) : "memory"); return (unsigned)(e / NMAIN);
}
__device__ __forceinline__ void flag_wait(const unsigned* f, unsigned count, unsigned epoch) {
  const unsigned target = (epoch + 1) * count;
  uint32_t n = 0;
  while (true) {
    unsigned v;
    asm volatile("ld.acquire.gpu.global.u32 %0, [%1];" : "=r"(v) : "l"(f) : "memory");
    if ((int)(v - target) >= 0) break;
    if (++n > SPIN_LIMIT) __trap();
    __nanosleep(FLAG_NS);
  }
}
__device__ __forceinline__ void fence_async_all() { asm volatile("fence.proxy.async;" ::: "memory"); }
__device__ __forceinline__ void flag_signal(unsigned* f) {
  asm volatile("fence.acq_rel.gpu;" ::: "memory");
  asm volatile("red.relaxed.gpu.global.add.u32 [%0], 1;" :: "l"(f) : "memory");
}
__device__ __forceinline__ void flag_signal_after_bulk(unsigned* f) {
  asm volatile("red.relaxed.gpu.global.add.u32 [%0], 1;" :: "l"(f) : "memory");
}
__device__ __forceinline__ void fence_async_smem() { asm volatile("fence.proxy.async.shared::cta;" ::: "memory"); }
__device__ __forceinline__ void tma_ld2(uint32_t dst, const CUtensorMap* m, uint32_t bar, int c0, int c1) {
  asm volatile("cp.async.bulk.tensor.2d.shared::cluster.global.mbarrier::complete_tx::bytes [%0], [%1, {%3, %4}], [%2];"
               :: "r"(dst), "l"(m), "r"(bar), "r"(c0), "r"(c1) : "memory");
}
__device__ __forceinline__ void tma_ld3(uint32_t dst, const CUtensorMap* m, uint32_t bar, int c0, int c1, int c2) {
  asm volatile("cp.async.bulk.tensor.3d.shared::cluster.global.mbarrier::complete_tx::bytes [%0], [%1, {%3, %4, %5}], [%2];"
               :: "r"(dst), "l"(m), "r"(bar), "r"(c0), "r"(c1), "r"(c2) : "memory");
}
__device__ __forceinline__ void bulk_ld(uint32_t dst, const void* src, uint32_t bytes, uint32_t bar) {
  asm volatile("cp.async.bulk.shared::cluster.global.mbarrier::complete_tx::bytes [%0], [%1], %2, [%3];"
               :: "r"(dst), "l"(src), "r"(bytes), "r"(bar) : "memory");
}
__device__ __forceinline__ void bulk_st(void* dst, uint32_t src, uint32_t bytes) {
  asm volatile("cp.async.bulk.global.shared::cta.bulk_group [%0], [%1], %2;" :: "l"(dst), "r"(src), "r"(bytes) : "memory");
}
__device__ __forceinline__ void tma_st2(const CUtensorMap* m, uint32_t src, int c0, int c1) {
  asm volatile("cp.async.bulk.tensor.2d.global.shared::cta.bulk_group [%0, {%2, %3}], [%1];"
               :: "l"(m), "r"(src), "r"(c0), "r"(c1) : "memory");
}
__device__ __forceinline__ void tma_red2(const CUtensorMap* m, uint32_t src, int c0, int c1) {
  asm volatile("cp.reduce.async.bulk.tensor.2d.global.shared::cta.add.tile.bulk_group [%0, {%2, %3}], [%1];"
               :: "l"(m), "r"(src), "r"(c0), "r"(c1) : "memory");
}
__device__ __forceinline__ void tma_pf2(const CUtensorMap* m, int c0, int c1) {
  asm volatile("cp.async.bulk.prefetch.tensor.2d.L2.global.tile [%0, {%1, %2}];" :: "l"(m), "r"(c0), "r"(c1) : "memory");
}
__device__ __forceinline__ void bulk_prefetch(const void* src, uint32_t bytes) {
  asm volatile("cp.async.bulk.prefetch.L2.global [%0], %1;" :: "l"(src), "r"(bytes) : "memory");
}
__device__ __forceinline__ void bulk_commit() { asm volatile("cp.async.bulk.commit_group;" ::: "memory"); }
__device__ __forceinline__ void bulk_wait_read() { asm volatile("cp.async.bulk.wait_group.read 0;" ::: "memory"); }
__device__ __forceinline__ void bulk_wait_all() { asm volatile("cp.async.bulk.wait_group 0;" ::: "memory"); }
__device__ __forceinline__ void prefetch_map(const CUtensorMap* m) { asm volatile("prefetch.tensormap [%0];" :: "l"(m) : "memory"); }
__device__ __forceinline__ void wg_fence() { asm volatile("wgmma.fence.sync.aligned;" ::: "memory"); }
__device__ __forceinline__ void wg_commit() { asm volatile("wgmma.commit_group.sync.aligned;" ::: "memory"); }
template <int N> __device__ __forceinline__ void wg_wait() { asm volatile("wgmma.wait_group.sync.aligned %0;" :: "n"(N) : "memory"); }
template <int N> __device__ __forceinline__ void reg_fence(float (&d)[N]) {
#pragma unroll
  for (int i = 0; i < N; i++) asm volatile("" : "+f"(d[i]) :: "memory");
}
template <int N> __device__ __forceinline__ void reg_fence(uint32_t (&d)[N]) {
#pragma unroll
  for (int i = 0; i < N; i++) asm volatile("" : "+r"(d[i]) :: "memory");
}
__device__ __forceinline__ uint32_t fresh_tid() { uint32_t t; asm volatile("mov.u32 %0, %%tid.x;" : "=r"(t)); return t; }
__device__ __forceinline__ uint32_t lane_base16() {
  const uint32_t t = fresh_tid(), lane = t & 31, wq = (t >> 5) & 3;
  return (16 * wq + (lane & 7) + 8 * ((lane >> 3) & 1)) * 128 + (((lane >> 4) ^ (lane & 7)) << 4);
}
__device__ __forceinline__ void named_sync(int id, int n) { asm volatile("bar.sync %0, %1;" :: "r"(id), "r"(n) : "memory"); }
__device__ __forceinline__ void named_arrive(int id, int n) { asm volatile("bar.arrive %0, %1;" :: "r"(id), "r"(n) : "memory"); }
__device__ __forceinline__ uint32_t pack_bf16(float lo, float hi) {
  uint32_t r; asm("cvt.rn.bf16x2.f32 %0, %1, %2;" : "=r"(r) : "f"(hi), "f"(lo)); return r;
}
__device__ __forceinline__ float ex2(float x) { float y; asm("ex2.approx.ftz.f32 %0, %1;" : "=f"(y) : "f"(x)); return y; }
__device__ __forceinline__ void stsm4(uint32_t addr, uint32_t a, uint32_t b, uint32_t c, uint32_t d) {
  asm volatile("stmatrix.sync.aligned.m8n8.x4.shared.b16 [%0], {%1, %2, %3, %4};" :: "r"(addr), "r"(a), "r"(b), "r"(c), "r"(d) : "memory");
}
__device__ __forceinline__ void stsm4t(uint32_t addr, uint32_t a, uint32_t b, uint32_t c, uint32_t d) {
  asm volatile("stmatrix.sync.aligned.m8n8.x4.trans.shared.b16 [%0], {%1, %2, %3, %4};" :: "r"(addr), "r"(a), "r"(b), "r"(c), "r"(d) : "memory");
}
__device__ __forceinline__ uint64_t mk_desc(uint32_t addr, uint32_t lbo, uint32_t sbo) {
  return (uint64_t)(((addr & 0x3FFFF) >> 4) | ((lbo >> 4) << 16)) | ((uint64_t)((sbo >> 4) | (1u << 30)) << 32);
}
__device__ __forceinline__ uint64_t desc_k(uint32_t addr)  { return mk_desc(addr, 16, 1024); }
__device__ __forceinline__ uint64_t desc_mn(uint32_t addr) { return mk_desc(addr, 8192, 1024); }
__device__ __forceinline__ uint64_t desc_add(uint64_t d, uint32_t bytes) { return d + (bytes >> 4); }

__device__ __forceinline__ void wgmma_ss_n256_tb(float (&d)[128], uint64_t da, uint64_t db, int sd) {
  asm volatile("{\n.reg .pred p;\nsetp.ne.b32 p, %130, 0;\n"
    "wgmma.mma_async.sync.aligned.m64n256k16.f32.bf16.bf16 "
    "{%0, %1, %2, %3, %4, %5, %6, %7, %8, %9, %10, %11, %12, %13, %14, %15, "
    "%16, %17, %18, %19, %20, %21, %22, %23, %24, %25, %26, %27, %28, %29, %30, %31, "
    "%32, %33, %34, %35, %36, %37, %38, %39, %40, %41, %42, %43, %44, %45, %46, %47, "
    "%48, %49, %50, %51, %52, %53, %54, %55, %56, %57, %58, %59, %60, %61, %62, %63, "
    "%64, %65, %66, %67, %68, %69, %70, %71, %72, %73, %74, %75, %76, %77, %78, %79, "
    "%80, %81, %82, %83, %84, %85, %86, %87, %88, %89, %90, %91, %92, %93, %94, %95, "
    "%96, %97, %98, %99, %100, %101, %102, %103, %104, %105, %106, %107, %108, %109, %110, %111, "
    "%112, %113, %114, %115, %116, %117, %118, %119, %120, %121, %122, %123, %124, %125, %126, %127}, "
    "%128, %129, p, 1, 1, 0, 1;\n}"
    : "+f"(d[0]), "+f"(d[1]), "+f"(d[2]), "+f"(d[3]), "+f"(d[4]), "+f"(d[5]), "+f"(d[6]), "+f"(d[7]),
      "+f"(d[8]), "+f"(d[9]), "+f"(d[10]), "+f"(d[11]), "+f"(d[12]), "+f"(d[13]), "+f"(d[14]), "+f"(d[15]),
      "+f"(d[16]), "+f"(d[17]), "+f"(d[18]), "+f"(d[19]), "+f"(d[20]), "+f"(d[21]), "+f"(d[22]), "+f"(d[23]),
      "+f"(d[24]), "+f"(d[25]), "+f"(d[26]), "+f"(d[27]), "+f"(d[28]), "+f"(d[29]), "+f"(d[30]), "+f"(d[31]),
      "+f"(d[32]), "+f"(d[33]), "+f"(d[34]), "+f"(d[35]), "+f"(d[36]), "+f"(d[37]), "+f"(d[38]), "+f"(d[39]),
      "+f"(d[40]), "+f"(d[41]), "+f"(d[42]), "+f"(d[43]), "+f"(d[44]), "+f"(d[45]), "+f"(d[46]), "+f"(d[47]),
      "+f"(d[48]), "+f"(d[49]), "+f"(d[50]), "+f"(d[51]), "+f"(d[52]), "+f"(d[53]), "+f"(d[54]), "+f"(d[55]),
      "+f"(d[56]), "+f"(d[57]), "+f"(d[58]), "+f"(d[59]), "+f"(d[60]), "+f"(d[61]), "+f"(d[62]), "+f"(d[63]),
      "+f"(d[64]), "+f"(d[65]), "+f"(d[66]), "+f"(d[67]), "+f"(d[68]), "+f"(d[69]), "+f"(d[70]), "+f"(d[71]),
      "+f"(d[72]), "+f"(d[73]), "+f"(d[74]), "+f"(d[75]), "+f"(d[76]), "+f"(d[77]), "+f"(d[78]), "+f"(d[79]),
      "+f"(d[80]), "+f"(d[81]), "+f"(d[82]), "+f"(d[83]), "+f"(d[84]), "+f"(d[85]), "+f"(d[86]), "+f"(d[87]),
      "+f"(d[88]), "+f"(d[89]), "+f"(d[90]), "+f"(d[91]), "+f"(d[92]), "+f"(d[93]), "+f"(d[94]), "+f"(d[95]),
      "+f"(d[96]), "+f"(d[97]), "+f"(d[98]), "+f"(d[99]), "+f"(d[100]), "+f"(d[101]), "+f"(d[102]), "+f"(d[103]),
      "+f"(d[104]), "+f"(d[105]), "+f"(d[106]), "+f"(d[107]), "+f"(d[108]), "+f"(d[109]), "+f"(d[110]), "+f"(d[111]),
      "+f"(d[112]), "+f"(d[113]), "+f"(d[114]), "+f"(d[115]), "+f"(d[116]), "+f"(d[117]), "+f"(d[118]), "+f"(d[119]),
      "+f"(d[120]), "+f"(d[121]), "+f"(d[122]), "+f"(d[123]), "+f"(d[124]), "+f"(d[125]), "+f"(d[126]), "+f"(d[127])
    : "l"(da), "l"(db), "r"(sd));
}
__device__ __forceinline__ void wgmma_ss_n64(float (&d)[32], uint64_t da, uint64_t db, int sd) {
  asm volatile("{\n.reg .pred p;\nsetp.ne.b32 p, %34, 0;\n"
    "wgmma.mma_async.sync.aligned.m64n64k16.f32.bf16.bf16 "
    "{%0, %1, %2, %3, %4, %5, %6, %7, %8, %9, %10, %11, %12, %13, %14, %15, "
    "%16, %17, %18, %19, %20, %21, %22, %23, %24, %25, %26, %27, %28, %29, %30, %31}, "
    "%32, %33, p, 1, 1, 0, 0;\n}"
    : "+f"(d[0]), "+f"(d[1]), "+f"(d[2]), "+f"(d[3]), "+f"(d[4]), "+f"(d[5]), "+f"(d[6]), "+f"(d[7]),
      "+f"(d[8]), "+f"(d[9]), "+f"(d[10]), "+f"(d[11]), "+f"(d[12]), "+f"(d[13]), "+f"(d[14]), "+f"(d[15]),
      "+f"(d[16]), "+f"(d[17]), "+f"(d[18]), "+f"(d[19]), "+f"(d[20]), "+f"(d[21]), "+f"(d[22]), "+f"(d[23]),
      "+f"(d[24]), "+f"(d[25]), "+f"(d[26]), "+f"(d[27]), "+f"(d[28]), "+f"(d[29]), "+f"(d[30]), "+f"(d[31])
    : "l"(da), "l"(db), "r"(sd));
}
__device__ __forceinline__ void wgmma_rs_n256_tb(float (&d)[128], uint32_t a0, uint32_t a1, uint32_t a2, uint32_t a3, uint64_t db, int sd) {
  asm volatile("{\n.reg .pred p;\nsetp.ne.b32 p, %133, 0;\n"
    "wgmma.mma_async.sync.aligned.m64n256k16.f32.bf16.bf16 "
    "{%0, %1, %2, %3, %4, %5, %6, %7, %8, %9, %10, %11, %12, %13, %14, %15, "
    "%16, %17, %18, %19, %20, %21, %22, %23, %24, %25, %26, %27, %28, %29, %30, %31, "
    "%32, %33, %34, %35, %36, %37, %38, %39, %40, %41, %42, %43, %44, %45, %46, %47, "
    "%48, %49, %50, %51, %52, %53, %54, %55, %56, %57, %58, %59, %60, %61, %62, %63, "
    "%64, %65, %66, %67, %68, %69, %70, %71, %72, %73, %74, %75, %76, %77, %78, %79, "
    "%80, %81, %82, %83, %84, %85, %86, %87, %88, %89, %90, %91, %92, %93, %94, %95, "
    "%96, %97, %98, %99, %100, %101, %102, %103, %104, %105, %106, %107, %108, %109, %110, %111, "
    "%112, %113, %114, %115, %116, %117, %118, %119, %120, %121, %122, %123, %124, %125, %126, %127}, "
    "{%128, %129, %130, %131}, %132, p, 1, 1, 1;\n}"
    : "+f"(d[0]), "+f"(d[1]), "+f"(d[2]), "+f"(d[3]), "+f"(d[4]), "+f"(d[5]), "+f"(d[6]), "+f"(d[7]),
      "+f"(d[8]), "+f"(d[9]), "+f"(d[10]), "+f"(d[11]), "+f"(d[12]), "+f"(d[13]), "+f"(d[14]), "+f"(d[15]),
      "+f"(d[16]), "+f"(d[17]), "+f"(d[18]), "+f"(d[19]), "+f"(d[20]), "+f"(d[21]), "+f"(d[22]), "+f"(d[23]),
      "+f"(d[24]), "+f"(d[25]), "+f"(d[26]), "+f"(d[27]), "+f"(d[28]), "+f"(d[29]), "+f"(d[30]), "+f"(d[31]),
      "+f"(d[32]), "+f"(d[33]), "+f"(d[34]), "+f"(d[35]), "+f"(d[36]), "+f"(d[37]), "+f"(d[38]), "+f"(d[39]),
      "+f"(d[40]), "+f"(d[41]), "+f"(d[42]), "+f"(d[43]), "+f"(d[44]), "+f"(d[45]), "+f"(d[46]), "+f"(d[47]),
      "+f"(d[48]), "+f"(d[49]), "+f"(d[50]), "+f"(d[51]), "+f"(d[52]), "+f"(d[53]), "+f"(d[54]), "+f"(d[55]),
      "+f"(d[56]), "+f"(d[57]), "+f"(d[58]), "+f"(d[59]), "+f"(d[60]), "+f"(d[61]), "+f"(d[62]), "+f"(d[63]),
      "+f"(d[64]), "+f"(d[65]), "+f"(d[66]), "+f"(d[67]), "+f"(d[68]), "+f"(d[69]), "+f"(d[70]), "+f"(d[71]),
      "+f"(d[72]), "+f"(d[73]), "+f"(d[74]), "+f"(d[75]), "+f"(d[76]), "+f"(d[77]), "+f"(d[78]), "+f"(d[79]),
      "+f"(d[80]), "+f"(d[81]), "+f"(d[82]), "+f"(d[83]), "+f"(d[84]), "+f"(d[85]), "+f"(d[86]), "+f"(d[87]),
      "+f"(d[88]), "+f"(d[89]), "+f"(d[90]), "+f"(d[91]), "+f"(d[92]), "+f"(d[93]), "+f"(d[94]), "+f"(d[95]),
      "+f"(d[96]), "+f"(d[97]), "+f"(d[98]), "+f"(d[99]), "+f"(d[100]), "+f"(d[101]), "+f"(d[102]), "+f"(d[103]),
      "+f"(d[104]), "+f"(d[105]), "+f"(d[106]), "+f"(d[107]), "+f"(d[108]), "+f"(d[109]), "+f"(d[110]), "+f"(d[111]),
      "+f"(d[112]), "+f"(d[113]), "+f"(d[114]), "+f"(d[115]), "+f"(d[116]), "+f"(d[117]), "+f"(d[118]), "+f"(d[119]),
      "+f"(d[120]), "+f"(d[121]), "+f"(d[122]), "+f"(d[123]), "+f"(d[124]), "+f"(d[125]), "+f"(d[126]), "+f"(d[127])
    : "r"(a0), "r"(a1), "r"(a2), "r"(a3), "l"(db), "r"(sd));
}
__device__ __forceinline__ void wgmma_rs_n64_tb(float (&d)[32], uint32_t a0, uint32_t a1, uint32_t a2, uint32_t a3, uint64_t db, int sd) {
  asm volatile("{\n.reg .pred p;\nsetp.ne.b32 p, %37, 0;\n"
    "wgmma.mma_async.sync.aligned.m64n64k16.f32.bf16.bf16 "
    "{%0, %1, %2, %3, %4, %5, %6, %7, %8, %9, %10, %11, %12, %13, %14, %15, "
    "%16, %17, %18, %19, %20, %21, %22, %23, %24, %25, %26, %27, %28, %29, %30, %31}, "
    "{%32, %33, %34, %35}, %36, p, 1, 1, 1;\n}"
    : "+f"(d[0]), "+f"(d[1]), "+f"(d[2]), "+f"(d[3]), "+f"(d[4]), "+f"(d[5]), "+f"(d[6]), "+f"(d[7]),
      "+f"(d[8]), "+f"(d[9]), "+f"(d[10]), "+f"(d[11]), "+f"(d[12]), "+f"(d[13]), "+f"(d[14]), "+f"(d[15]),
      "+f"(d[16]), "+f"(d[17]), "+f"(d[18]), "+f"(d[19]), "+f"(d[20]), "+f"(d[21]), "+f"(d[22]), "+f"(d[23]),
      "+f"(d[24]), "+f"(d[25]), "+f"(d[26]), "+f"(d[27]), "+f"(d[28]), "+f"(d[29]), "+f"(d[30]), "+f"(d[31])
    : "r"(a0), "r"(a1), "r"(a2), "r"(a3), "l"(db), "r"(sd));
}
__device__ __forceinline__ void wgmma_rs_n64(float (&d)[32], uint32_t a0, uint32_t a1, uint32_t a2, uint32_t a3, uint64_t db, int sd) {
  asm volatile("{\n.reg .pred p;\nsetp.ne.b32 p, %37, 0;\n"
    "wgmma.mma_async.sync.aligned.m64n64k16.f32.bf16.bf16 "
    "{%0, %1, %2, %3, %4, %5, %6, %7, %8, %9, %10, %11, %12, %13, %14, %15, "
    "%16, %17, %18, %19, %20, %21, %22, %23, %24, %25, %26, %27, %28, %29, %30, %31}, "
    "{%32, %33, %34, %35}, %36, p, 1, 1, 0;\n}"
    : "+f"(d[0]), "+f"(d[1]), "+f"(d[2]), "+f"(d[3]), "+f"(d[4]), "+f"(d[5]), "+f"(d[6]), "+f"(d[7]),
      "+f"(d[8]), "+f"(d[9]), "+f"(d[10]), "+f"(d[11]), "+f"(d[12]), "+f"(d[13]), "+f"(d[14]), "+f"(d[15]),
      "+f"(d[16]), "+f"(d[17]), "+f"(d[18]), "+f"(d[19]), "+f"(d[20]), "+f"(d[21]), "+f"(d[22]), "+f"(d[23]),
      "+f"(d[24]), "+f"(d[25]), "+f"(d[26]), "+f"(d[27]), "+f"(d[28]), "+f"(d[29]), "+f"(d[30]), "+f"(d[31])
    : "r"(a0), "r"(a1), "r"(a2), "r"(a3), "l"(db), "r"(sd));
}

__device__ __forceinline__ uint4 lds16(uint32_t a) {
  uint4 v; asm volatile("ld.shared.v4.u32 {%0, %1, %2, %3}, [%4];" : "=r"(v.x), "=r"(v.y), "=r"(v.z), "=r"(v.w) : "r"(a) : "memory"); return v;
}
__device__ __forceinline__ void sts16(uint32_t a, uint32_t x, uint32_t y, uint32_t z, uint32_t w) {
  asm volatile("st.shared.v4.u32 [%0], {%1, %2, %3, %4};" :: "r"(a), "r"(x), "r"(y), "r"(z), "r"(w) : "memory");
}
__device__ __forceinline__ uint32_t lds4(uint32_t a) { uint32_t v; asm volatile("ld.shared.u32 %0, [%1];" : "=r"(v) : "r"(a) : "memory"); return v; }
__device__ __forceinline__ uint32_t lds4v(uint32_t a) { uint32_t v; asm volatile("ld.volatile.shared.u32 %0, [%1];" : "=r"(v) : "r"(a) : "memory"); return v; }
__device__ __forceinline__ uint32_t bmul(uint32_t a, uint32_t b) { uint32_t r; asm("mul.rn.bf16x2 %0, %1, %2;" : "=r"(r) : "r"(a), "r"(b)); return r; }
__device__ __forceinline__ uint32_t bfma(uint32_t a, uint32_t b, uint32_t c) { uint32_t r; asm("fma.rn.bf16x2 %0, %1, %2, %3;" : "=r"(r) : "r"(a), "r"(b), "r"(c)); return r; }
__device__ __forceinline__ uint32_t badd(uint32_t a, uint32_t b) { uint32_t r; asm("add.rn.bf16x2 %0, %1, %2;" : "=r"(r) : "r"(a), "r"(b)); return r; }

__device__ __forceinline__ void ldsm4(uint32_t (&r)[4], uint32_t a) {
  asm volatile("ldmatrix.sync.aligned.m8n8.x4.shared.b16 {%0, %1, %2, %3}, [%4];" : "=r"(r[0]), "=r"(r[1]), "=r"(r[2]), "=r"(r[3]) : "r"(a) : "memory");
}
__device__ __forceinline__ void ldsm4t(uint32_t (&r)[4], uint32_t a) {
  asm volatile("ldmatrix.sync.aligned.m8n8.x4.trans.shared.b16 {%0, %1, %2, %3}, [%4];" : "=r"(r[0]), "=r"(r[1]), "=r"(r[2]), "=r"(r[3]) : "r"(a) : "memory");
}
__device__ __forceinline__ uint32_t transpose8(uint32_t a) { uint32_t d; asm volatile("movmatrix.sync.aligned.m8n8.trans.b16 %0, %1;" : "=r"(d) : "r"(a)); return d; }

__device__ __forceinline__ void mma16816(float (&d)[4], const uint32_t (&a)[4], uint32_t b0, uint32_t b1) {
  asm volatile("mma.sync.aligned.m16n8k16.row.col.f32.bf16.bf16.f32 {%0, %1, %2, %3}, {%4, %5, %6, %7}, {%8, %9}, {%0, %1, %2, %3};"
               : "+f"(d[0]), "+f"(d[1]), "+f"(d[2]), "+f"(d[3]) : "r"(a[0]), "r"(a[1]), "r"(a[2]), "r"(a[3]), "r"(b0), "r"(b1));
}

#define STG_K1 2
#define STG_K2 10
#define STG_Q1 1
#define STG_Q2 5
#define PACE_A 400
#define PACE_B 100
#define PF_QA 48
#define PF_CV 64
#define PF_X 8
#define PF_WO 11
#define Q_PRE 2
#define CV_SER -1
#define CV_QX 0
#define CV_FX 1
#define TAIL_WAIT 0
#define ARRIVE_KK 12
#define SIDE_DELAY_NS 4000
#define HEAD_MAP 2
#define EARLY_LD 2
#define HI_ORDER 9
constexpr int CV_BAR = 5;
constexpr int PP_BAR = 3;
template <int V> struct Int { static constexpr int value = V; };
struct Ring {
  uint32_t slot, phase;
  __device__ __forceinline__ void next() { if (++slot == NSLOT) { slot = 0; phase ^= 1; } }
};
__device__ __forceinline__ uint32_t bar_addr(uint32_t sb, uint32_t i) { return sb + BARS + 8 * i; }
__device__ __forceinline__ uint32_t q_region(uint32_t sb, int w) { return sb + QREG + (w ^ 1) * 32768; }

struct Role { int h, j; };
__device__ __forceinline__ Role get_role() {
  int cta; asm volatile("mov.u32 %0, %%ctaid.x;" : "=r"(cta));
  const int c = cta >> 1;
  int h, u;
  const int a = c - 4, b = c - 36, q = (b * 37) >> 8;
  h = a < 0 ? (HEAD_MAP == 2 ? 8 : 15) : b < 0 ? a & 7 : (HEAD_MAP == 2 ? 9 : 8) + b - 7 * q;
  u = a < 0 ? c : b < 0 ? a >> 3 : q;
  return Role{h, 2 * u + (cta & 1)};
}
__device__ __forceinline__ int fresh_warp() { return __shfl_sync(0xffffffffu, fresh_tid() >> 5, 0); }

__device__ __forceinline__ int q_tile(int h, int j, int which) { return ((h < 8) == (which == 0)) ? 15 - j : j; }

__device__ __forceinline__ int o_chunk(int h, int c) { const int x = c + (h & 7); return x % 7; }

__device__ __forceinline__ int kv_block(int j, int t) { return j + 8 * ((HI_ORDER >> t) & 1); }
__device__ __forceinline__ uint8_t* kv_tile(const Params& p, int v, int h, int tile) {
  return p.kv + (size_t)((v * NH + h) * 32 + tile) * 32768;
}

__device__ __forceinline__ void ring_acquire(uint32_t sb, Ring& r, uint32_t bytes) {
  mbar_wait(bar_addr(sb, B_RG_EMPTY + r.slot), r.phase ^ 1);
  mbar_expect_tx(bar_addr(sb, B_RG_FULL + r.slot), bytes);
}
__device__ __forceinline__ void producer_main(const Params& p, uint32_t sb) {
  const Role ro = get_role();
  const int h = ro.h, j = ro.j;
  TR_DECL;
  CP_DECL;
  ST(11);
  for (int it = EARLY_LD; it < 71; it++) {
    const int t = it >> 4, k = it & 15, s = it & 3;
    mbar_wait(bar_addr(sb, B_P1_EMPTY + s), ((it >> 2) & 1) ^ 1);
    const uint32_t full = bar_addr(sb, B_P1_FULL + s), dst = sb + s * P1_STAGE;
    mbar_expect_tx(full, P1_STAGE);
    if ((it & 7) == 4) TRG(it);
    if (t < 4) {
      tma_ld2(dst, &p.ckv, full, k * 64, kv_block(j, t) * 128);
      tma_ld3(dst + 16384, (t >> 1) ? &p.wuv : &p.wuk, full, 0, k * 64, h * 4);
    } else {
      tma_ld2(dst, &p.x, full, k * 64, q_tile(h, j, 0) * 128);
      tma_ld3(dst + 16384, &p.wq, full, 0, k * 64, h * 4);
    }
    CP();
    if (it >= PF_QA && it < PF_QA + 14) {
      const int i = it - PF_QA;
      bulk_prefetch(p.b_x + (size_t)(q_tile(h, j, 0) * 128 + (h & 7) * 16) * DM + i * 512, 1024);
      tma_pf2(&p.wqp, h * HD, (i * 8 + j) * 4);
    }
    if (it >= PF_CV && it < PF_CV + 3) {
      mbar_wait(bar_addr(sb, B_XS), 0);
      bulk_prefetch(g_xs + (size_t)(h * 8 + j) * CV_BYTES + (it - PF_CV) * (CV_BYTES / 3), CV_BYTES / 3);
    }
  }
  mbar_wait(bar_addr(sb, B_P1_EMPTY + 3), 0);
  mbar_wait(bar_addr(sb, B_XS), 0);
  mbar_expect_tx(bar_addr(sb, B_RG_FULL + 4), CV_BYTES);
  bulk_ld(sb + CV_X, g_xs + (size_t)(h * 8 + j) * CV_BYTES, CV_BYTES, bar_addr(sb, B_RG_FULL + 4));
  Ring r{0, 1};
  auto prefetch_wo = [&](int left) {
    const int i = PF_WO - left;
    if (PF_WO && i >= 0 && i < 8) bulk_prefetch(p.b_wo + (size_t)(h * HD + j * 32 + 4 * i) * DM, 4 * DM * 2);
  };
  mbar_wait(bar_addr(sb, B_KV), 0);
  for (int which = 0; which < 2; which++) {
    const int qt = q_tile(h, j, which);
    if (which == 1) {
      for (int kc = 0; kc < 7; kc++) {
        prefetch_wo(4 * qt + 4 + 7 - kc);
        ring_acquire(sb, r, 32768);
        tma_ld3(sb + r.slot * SLOT, &p.wq, bar_addr(sb, B_RG_FULL + r.slot), 0, kc * 64, h * 4);
        r.next();
        if (kc == 0 || (kc & 1)) {
          ring_acquire(sb, r, kc == 0 ? 16384 : 32768);
          const uint32_t full = bar_addr(sb, B_RG_FULL + r.slot), dst = sb + r.slot * SLOT;
          tma_ld2(dst, &p.x, full, kc * 64, qt * 128);
          if (kc > 0) tma_ld2(dst + 16384, &p.x, full, kc * 64 + 64, qt * 128);
          r.next();
        }
      }
    }
    const int n = 2 * qt + 2;
    for (int f = 0; f < 2 * n; f++) {
      if (which == 0) {
        const int i = f - max(2 * n - PF_X, 0);
        if (PF_X && i >= 0 && i < 4) bulk_prefetch(p.b_x + (size_t)((15 - qt) * 128 + (h & 7) * 16 + 4 * i) * DM, 4 * DM * 2);
      } else prefetch_wo(2 * n - f);
      const bool isK = (f == 0) || ((f & 1) && f < 2 * n - 1);
      const int i = isK ? (f + 1) >> 1 : (f == 2 * n - 1 ? n - 1 : (f >> 1) - 1);
      const int tile = which ? n - 1 - i : i;
      if (!isK) mbar_wait(bar_addr(sb, B_KV + 1 + ((tile >> 4) ^ ((HI_ORDER >> 2) & 1))), 0);
      if (which == 0 && f < 2) mbar_wait(bar_addr(sb, B_P1_EMPTY + f), 1);
      ring_acquire(sb, r, 32768);
      if (isK && (tile & 3) == 0) TRG(100 + 50 * which + tile);
      bulk_ld(sb + r.slot * SLOT, kv_tile(p, !isK, h, tile), 32768, bar_addr(sb, B_RG_FULL + r.slot));
      r.next();
      CP();
    }
  }
  for (int i = 0; i < 14; i++) {
    ring_acquire(sb, r, 32768);
    if ((i & 3) == 0) TRG(200 + i);
    if (i == 13) TR_END();
    tma_ld2(sb + r.slot * SLOT, &p.wo, bar_addr(sb, B_RG_FULL + r.slot), o_chunk(h, i >> 1) * 64, ((i & 1) ? h ^ 8 : h) * HD);
    r.next();
    CP();
  }
}

__device__ __forceinline__ void storer_main(const Params& p, uint32_t sb) {
  const Role ro = get_role();
  const int h = ro.h, j = ro.j, w = fresh_warp() - 1;
  const uint32_t full = bar_addr(sb, B_ST_FULL + w), empty = bar_addr(sb, B_ST_EMPTY + w);
  const int lane = threadIdx.x & 31;
  const unsigned epoch = load_epoch();
  if (lane == 0) {
    for (int job = 0; job < 8; job++) {
      const int t = job >> 1;
      uint8_t* dst = kv_tile(p, t >> 1, h, 2 * kv_block(j, t) + w) + (job & 1) * 16384;
      mbar_wait_nap(full, job & 1);
      for (int i = 0; i < 8; i++) {
        if (i) __nanosleep(job < 6 ? PACE_A : PACE_B);
        bulk_st(dst + i * 2048, sb + P1_STG + w * 16384 + i * 2048, 2048);
      }
      bulk_commit();
      bulk_wait_read();
      mbar_arrive(empty);
      if (job >= 3 && (job & 1)) { bulk_wait_all(); flag_signal(&g_flags.kv_ready[3 * h + t - 1].v); }
    }
  }
  __syncwarp();
  const int cta = h * 8 + j, qt = q_tile(h, j, 1);
  const uint32_t qreg = q_region(sb, w);
  {
    mbar_wait_nap(bar_addr(sb, B_CTXS + 4 * w), 0);
    uint4* z = reinterpret_cast<uint4*>(p.out + (size_t)(qt * 128 + w * 64 + (h & 7) * 8 + (lane >> 2)) * OUTW + DA) + (lane & 3);
#pragma unroll
    for (int i = 0; i < 14; i++) z[4 * i] = make_uint4(0, 0, 0, 0);
    __syncwarp();
    if (lane != 0) return;
    for (int b = 0; b < 4; b++) {
      mbar_wait(bar_addr(sb, B_CTXS + 4 * w + b), 0);
      bulk_st(p.ctx + (size_t)(cta * 2 + w) * 32768 + b * 8192, qreg + b * 8192, 8192);
      bulk_commit();
    }
    bulk_wait_read();
    mbar_arrive(empty);
    bulk_wait_all();
    flag_signal(&g_flags.ctx_ready[cta * 2 + w].v);
    flag_signal_after_bulk(&g_flags.out_ready[qt * 2 + w].v);
  }
  {
    const int wx = w ^ 1;
    flag_wait(&g_flags.ctx_ready[(cta ^ 64) * 2 + wx].v, 1, epoch);
    flag_wait(&g_flags.out_ready[qt * 2 + wx].v, 8, epoch);
    fence_async_all();
    mbar_wait_nap(bar_addr(sb, B_QFREE + w), 0);
    mbar_expect_tx(bar_addr(sb, B_CTXF + w), 32768);
    bulk_ld(qreg, p.ctx + (size_t)((cta ^ 64) * 2 + wx) * 32768, 32768, bar_addr(sb, B_CTXF + w));
    for (int ch = 0; ch < 7; ch++) {
      const int b = ch & 1;
      mbar_wait(bar_addr(sb, B_S2_FULL + w * 2 + b), (ch >> 1) & 1);
      tma_red2(&p.part, qreg + b * 8192, DA + o_chunk(h, ch) * 64, qt * 128 + wx * 64);
      bulk_commit();
      if (ch == 0 && w == 1) mbar_arrive(bar_addr(sb, B_GFREE));
      bulk_wait_read();
      mbar_arrive(bar_addr(sb, B_S2_EMPTY + w * 2 + b));
    }
    GT(48 + w);
    if (TAIL_WAIT) bulk_wait_all();
    GT(50 + w); GT(52 + w); GT(56);
    if (w == 0) { ST(12); STG_(13); }
  }
}

template <int OFF, int NB, int NREG>
__device__ __forceinline__ void store_blocks(uint32_t base, uint32_t lanebase, const uint32_t (&pk)[NREG]) {
#pragma unroll
  for (int J = 0; J < NB * 8; J += 2) {
    const uint32_t a = base + (J >> 3) * 8192 + (lanebase ^ ((J & 7) << 4));
    stsm4(a, pk[OFF + 2 * J], pk[OFF + 2 * J + 1], pk[OFF + 2 * J + 2], pk[OFF + 2 * J + 3]);
  }
}
__device__ __forceinline__ void warp_arrive(uint32_t bar, int lane) { __syncwarp(); if (lane == 0) mbar_arrive(bar); }
__device__ __forceinline__ void release(uint32_t bar, int lane) { lane0_arrive(bar, 1, lane); }

template <int W> __device__ __forceinline__ constexpr int cv_tile(int u) { return 2 * u + ((u ^ W) & 1); }
__device__ __forceinline__ uint32_t cv_x_lane(uint32_t lane) { return (16 + (lane & 15) - (lane >> 4)) * 16; }
__device__ __forceinline__ uint32_t cv_h_lane(uint32_t lane, uint32_t hE, uint32_t hO) {
  const uint32_t g = lane >> 2, c = lane & 3;
  return (g & 1) ? hO + (15 + 2 * c - g) * 2 : hE + (16 + 2 * c - g) * 2;
}
template <int W>
__device__ __forceinline__ void conv_mma(float (&ca)[8][4], uint32_t xa, uint32_t ha, uint32_t sb, uint32_t lb, const uint32_t (&pk)[64]) {
  constexpr int N = 16 - W;
  uint32_t fx[N][4], fh[N][2];
  auto ld_h = [&](int i, int rr) { fh[i][0] = lds4(ha + i * 256 + rr * 32); fh[i][1] = lds4(ha + i * 256 + rr * 32 + 16); };
  if (CV_SER >= 0 && W == 0) named_sync(CV_BAR, 256);
  ldsm4(fx[0], xa);
#pragma unroll
  for (int u = 0; u < 8; u++) ld_h(cv_tile<W>(u), 0);
  ldsm4(fx[1], xa + 256);
#pragma unroll
  for (int u = 0; u < 8; u++) if (cv_tile<W ^ 1>(u) < N) ld_h(cv_tile<W ^ 1>(u), 0);
#pragma unroll
  for (int i = 2; i < N; i++) ldsm4(fx[i], xa + i * 256);
#pragma unroll
  for (int sx = 0; sx < N; sx++) {
#pragma unroll
    for (int u = 0; u < 8; u++) {
      const int jj = cv_tile<W>(u) - sx;
      if (jj >= 0) mma16816(ca[u], fx[sx], fh[jj < 0 ? 0 : jj][0], fh[jj < 0 ? 0 : jj][1]);
    }
    ldsm4(fx[sx], xa + sx * 256 - 32);
    ld_h(N - 1 - sx, 1);
    if (W == 1 && sx == CV_SER) named_arrive(CV_BAR, 256);
  }
  mbar_wait(bar_addr(sb, B_P1_EMPTY + 2), 1);
  if (W == 0) { mbar_wait(bar_addr(sb, B_ST_EMPTY), 1); mbar_wait(bar_addr(sb, B_ST_EMPTY + 1), 1); }
#pragma unroll
  for (int jj = 15; jj >= 0; jj--) {
    if (W == 0 || CV_QX) stsm4(q_region(sb, W) + (jj >> 2) * 8192 + (lb ^ ((jj & 3) << 5)), pk[4 * jj], pk[4 * jj + 1], pk[4 * jj + 2], pk[4 * jj + 3]);
#pragma unroll
    for (int u = 0; u < 8; u++) {
      const int sx = cv_tile<W>(u) - jj;
      if (sx >= 0) mma16816(ca[u], fx[sx < 0 ? 0 : sx], fh[jj < N ? jj : 0][0], fh[jj < N ? jj : 0][1]);
    }
  }
}

__device__ __forceinline__ void consumer_main(const Params& p, uint32_t sb, uint8_t* xs_base, uint32_t one) {
  const int lane = fresh_tid() & 31, w = (fresh_warp() >> 2) - 1;
  const uint32_t lb = lane_base16();
  int qt, cc;
  { const Role ro = get_role(); qt = q_tile(ro.h, ro.j, 0); cc = ro.h * 8 + ro.j; }
  const uint32_t st_full = bar_addr(sb, B_ST_FULL + w), st_empty = bar_addr(sb, B_ST_EMPTY + w);
  const uint32_t stg = sb + P1_STG + w * 16384;

  auto turn_begin = [&]() { named_sync(PP_BAR + w, 256); };
  auto turn_end = [&]() { named_arrive(PP_BAR + (w ^ 1), 256); };
  float acc[128];
#pragma unroll
  for (int i = 0; i < 128; i++) acc[i] = 0.f;
  uint32_t pk[64];
#pragma unroll
  for (int i = 0; i < 64; i++) pk[i] = 0;
  if (fresh_warp() != 4) named_sync(0, NTHREADS);
  PDECL;
  TR_DECL;
  TR(0);
  TSG(0); TS(1);
  const uint32_t qreg = q_region(sb, w);
  for (int t = 0; t < 5; t++) {
    const int nk = t < 4 ? 16 : 7;
#pragma unroll 1
    for (int k = 0; k < nk; k++) {
      const int it = t * 16 + k, s = k & 3;
      if (it == 0) { mbar_wait(bar_addr(sb, B_P1_FULL), 0); turn_begin(); }
      TR(1);
      const uint64_t da = desc_k(sb + s * P1_STAGE + w * 8192), db = desc_mn(sb + s * P1_STAGE + 16384);
      wg_fence();
#pragma unroll
      for (int kk = 0; kk < 4; kk++) wgmma_ss_n256_tb(acc, desc_add(da, kk * 32), desc_add(db, kk * 2048), (k | kk) != 0);
      wg_commit();
      turn_end();
      TR(3);
      wg_wait<1>();
      if (k > 0) release(bar_addr(sb, B_P1_EMPTY + ((k - 1) & 3)), lane);
      const int k1 = t < 4 ? STG_K1 : STG_Q1, k2 = t < 4 ? STG_K2 : STG_Q2;
      if (t > 0 && (k == k1 || k == k2)) {
        const int job = 2 * (t - 1) + (k != k1);
        if (job > 0) mbar_wait(st_empty, (job - 1) & 1);
        if (k == k1) store_blocks<0, 2>(stg, lb, pk); else store_blocks<32, 2>(stg, lb, pk);
      }
      if (t > 0 && (k == k1 + 1 || k == k2 + 1)) { fence_async_smem(); warp_arrive(st_full, lane); }
      TR(5);
      if (it < 70) { mbar_wait(bar_addr(sb, B_P1_FULL + ((k + 1) & 3)), ((it + 1) >> 2) & 1); turn_begin(); }
      else mbar_wait(bar_addr(sb, B_RG_FULL + 4), 0);
    }
    wg_wait<0>();
    TR(6);
    reg_fence(acc);
    release(bar_addr(sb, B_P1_EMPTY + ((nk - 1) & 3)), lane);
#pragma unroll
    for (int i = 0; i < 64; i++) pk[i] = pack_bf16(acc[2 * i], acc[2 * i + 1]);
    TS(t < 4 ? 2 + t : 60);
  }
  TS(6);
  {
    const uint32_t wq = lb >> 11, ln = lane, cx = sb + CV_X;
    float ca[8][4];
#pragma unroll
    for (int i = 0; i < 8; i++) { ca[i][0] = 0.f; ca[i][1] = 0.f; ca[i][2] = 0.f; ca[i][3] = 0.f; }
    const uint32_t xa = cx + cv_x_lane(ln) - wq * 64, ha = cv_h_lane(ln, cx + CV_HE, cx + CV_HE + CV_HCOPY) + wq * 64;
    TR(7); TS(19); TS(20);
    if (w) conv_mma<1>(ca, xa, ha, sb, lb, pk); else conv_mma<0>(ca, xa, ha, sb, lb, pk);
    TR(8); TS(21);
    const uint32_t ex = sb + CV_R + w * 16384 + ln * 16;
#pragma unroll
    for (int u = 0; u < 8; u++)
      sts16(ex + (wq * 8 + u) * 512, __float_as_uint(ca[u][0]), __float_as_uint(ca[u][1]), __float_as_uint(ca[u][2]), __float_as_uint(ca[u][3]));
  }
  auto conv_finish = [&]() {
    const uint32_t wq = lb >> 11, cx = sb + CV_X, ex = sb + CV_R + w * 16384 + lane * 16;
    uint8_t* gz = xs_base + (size_t)cc * CV_BYTES;
    const uint32_t Dd = lds4(cx + CV_D);
    uint32_t z[2][2];
#pragma unroll
    for (int e = 0; e < 2; e++) {
      const uint32_t u = 2 * wq + e, nt = 2 * u + ((e ^ w) & 1);
      float y[4] = {0.f, 0.f, 0.f, 0.f};
#pragma unroll
      for (int v = 0; v < 4; v++) {
        const uint4 t = lds16(ex + (v * 8 + u) * 512);
        y[0] += __uint_as_float(t.x); y[1] += __uint_as_float(t.y); y[2] += __uint_as_float(t.z); y[3] += __uint_as_float(t.w);
      }
      const uint32_t o = (16 + 16 * nt) * 16 + lane * 4;
      *reinterpret_cast<uint32_t*>(gz + o)       = badd(pack_bf16(y[0], y[1]), bmul(lds4(cx + o), Dd));
      *reinterpret_cast<uint32_t*>(gz + o + 128) = badd(pack_bf16(y[2], y[3]), bmul(lds4(cx + o + 128), Dd));
    }
    __syncwarp();
    release(bar_addr(sb, B_RG_EMPTY + 3), lane);
    release(bar_addr(sb, B_RG_EMPTY + 4), lane);
    if (lane == 0) mbar_arrive(bar_addr(sb, B_CONV));
  };
  TS(15);
  TR(10);
  Ring r{0, 1};
  auto take = [&]() { const uint32_t sl = r.slot; mbar_wait(bar_addr(sb, B_RG_FULL + sl), r.phase); r.next(); return sl; };
  constexpr float SC = 0.0625f * 1.4426950408889634f;
  uint32_t ws;
#pragma unroll 1
  for (int which = 0;; which++) {
    float s[32];
#pragma unroll
    for (int i = 0; i < 32; i++) s[i] = 0.f;
    uint32_t pa[16];
    float b0, b1, l0, l1;
    const uint64_t dq = desc_k(qreg);
    uint64_t dk = 0, dqq = 0, dv = 0;
    auto prep_qk = [&](uint32_t kaddr) { dk = desc_k(kaddr); dqq = dq + (kaddr >> 31); asm volatile("" : "+l"(dk), "+l"(dqq)); };
    auto prep_pv = [&](uint32_t vaddr) { dv = desc_mn(vaddr); asm volatile("" : "+l"(dv)); };
    auto issue_qk = [&]() {
#pragma unroll
      for (int kk = 0; kk < 16; kk++)
        wgmma_ss_n64(s, desc_add(dqq, (kk >> 2) * 8192 + (kk & 3) * 32), desc_add(dk, (kk >> 2) * 8192 + (kk & 3) * 32), kk != 0);
    };
    auto issue_pv = [&](int accumulate) {
#pragma unroll
      for (int kk = 0; kk < 4; kk++)
        wgmma_rs_n256_tb(acc, pa[4 * kk], pa[4 * kk + 1], pa[4 * kk + 2], pa[4 * kk + 3], desc_add(dv, kk * 2048), accumulate | kk);
    };
    auto mask_diag = [&]() {
      const int d = (int)((lb >> 11) << 4) + (lane >> 2) - 2 * (lane & 3);
#pragma unroll
      for (int jj = 0; jj < 8; jj++) {
        if (8 * jj > d)     s[4 * jj]     = -INFINITY;
        if (8 * jj + 1 > d) s[4 * jj + 1] = -INFINITY;
        if (8 * jj - 8 > d) s[4 * jj + 2] = -INFINITY;
        if (8 * jj - 7 > d) s[4 * jj + 3] = -INFINITY;
      }
    };
    auto row_max = [&](float& x0, float& x1) {
      x0 = fmaxf(s[0], s[1]); x1 = fmaxf(s[2], s[3]);
#pragma unroll
      for (int jj = 1; jj < 8; jj++) {
        x0 = fmaxf(x0, fmaxf(s[4 * jj], s[4 * jj + 1]));
        x1 = fmaxf(x1, fmaxf(s[4 * jj + 2], s[4 * jj + 3]));
      }
      x0 = fmaxf(x0, __shfl_xor_sync(0xffffffffu, x0, 1));
      x1 = fmaxf(x1, __shfl_xor_sync(0xffffffffu, x1, 1));
      x0 = fmaxf(x0, __shfl_xor_sync(0xffffffffu, x0, 2));
      x1 = fmaxf(x1, __shfl_xor_sync(0xffffffffu, x1, 2));
    };
    auto exps = [&](uint32_t (&pp)[16], float& r0, float& r1) {
      float t0, t1, t2, t3;
#pragma unroll
      for (int jj = 0; jj < 8; jj++) {
        const float e0 = ex2(fmaf(s[4 * jj], SC, b0)), e1 = ex2(fmaf(s[4 * jj + 1], SC, b0));
        const float e2 = ex2(fmaf(s[4 * jj + 2], SC, b1)), e3 = ex2(fmaf(s[4 * jj + 3], SC, b1));
        if (jj == 0) { t0 = e0; t1 = e1; t2 = e2; t3 = e3; } else { t0 += e0; t1 += e1; t2 += e2; t3 += e3; }
        pp[2 * jj] = pack_bf16(e0, e1); pp[2 * jj + 1] = pack_bf16(e2, e3);
      }
      r0 = t0 + t1; r1 = t2 + t3;
    };

    const bool up = w == which;
    const int n = 2 * qt + 2, nw = n - up;
    int fd = which ? 0 : 2 * n - 1;
    const int dir = which ? 1 : -1;
    auto skip = [&]() { r.next(); fd += dir; };
    auto give = [&](uint32_t sl, int d) {
      lane0_arrive(bar_addr(sb, B_RG_EMPTY + sl), (d & ~2) == 0 ? 2 : 1, lane);
    };
    if (which && up) skip();
    uint32_t ks = take();
    TS(62 + which);
    TR(20);
    prep_qk(sb + ks * SLOT);
    turn_begin();
    wg_fence();
#pragma unroll
    for (int kk = 0; kk < 16; kk++)
      wgmma_rs_n64(s, pk[4 * kk], pk[4 * kk + 1], pk[4 * kk + 2], pk[4 * kk + 3], desc_add(dk, (kk >> 2) * 8192 + (kk & 3) * 32), kk != 0);
    wg_commit();
    turn_end();
    TR(21);
    if (!which && (up || !CV_FX)) conv_finish();
    TR(23);
    if (which) mbar_wait(st_empty, 0);
    if ((which || !CV_QX) && !up) store_blocks<0, Q_PRE>(qreg, lb, pk);
    TR(24);
    wg_wait<0>();
    TR(22);
    reg_fence(s);
    reg_fence(pk);
    give(ks, fd);
    fd += dir;
    if (which && up) { skip(); store_blocks<0, 4>(qreg, lb, pk); }
    if (which || nw == 1) mask_diag();
    row_max(b0, b1);
    if ((which || !CV_QX) && !up) store_blocks<16 * Q_PRE, 4 - Q_PRE>(qreg + Q_PRE * 8192, lb, pk);
    b0 *= -SC; b1 *= -SC;
#pragma unroll
    for (int i = 0; i < 128; i++) acc[i] = 0.f;
    exps(pa, l0, l1);
    if (CV_FX && !which && !up) conv_finish();
    if (which && nw == 1) { fence_async_smem(); warp_arrive(bar_addr(sb, B_QFREE + w), lane); }
#pragma unroll 1
    for (int jj = 1; jj < nw; jj++) {
      ks = take();
      const uint32_t vs = take();
      if (jj == 1) fence_async_smem();
      TR(30);
#pragma unroll
      for (int i = 0; i < 32; i++) s[i] = 0.f;
      prep_qk(sb + ks * SLOT);
      prep_pv(sb + vs * SLOT);
      turn_begin();
      wg_fence();
      issue_qk();
      wg_commit();
      issue_pv(1);
      wg_commit();
      turn_end();
      TR(31);
      wg_wait<1>();
      TR(32);
      reg_fence(s);
      give(ks, fd);
      if (jj == nw - 1) {
        if (!which) mask_diag();
        else if (lane == 0) mbar_arrive(bar_addr(sb, B_QFREE + w));
      }
      uint32_t pn[16];
      float t0, t1, a0 = 1.f, a1 = 1.f;
      exps(pn, t0, t1);
      const bool redo = __any_sync(0xffffffffu, !(t0 + t1 <= 65536.f));
      if (redo) {
        row_max(a0, a1);
        const float c0 = fminf(b0, -SC * a0), c1 = fminf(b1, -SC * a1);
        a0 = ex2(c0 - b0); a1 = ex2(c1 - b1);
        b0 = c0; b1 = c1;
        l0 *= a0; l1 *= a1;
        exps(pn, t0, t1);
      }
      l0 += t0; l1 += t1;
      wg_wait<0>();
      reg_fence(acc);
      reg_fence(pa);
      give(vs, fd + dir);
      fd += 2 * dir;
      if (redo) {
#pragma unroll
        for (int i = 0; i < 32; i++) { acc[4 * i] *= a0; acc[4 * i + 1] *= a0; acc[4 * i + 2] *= a1; acc[4 * i + 3] *= a1; }
      }
#pragma unroll
      for (int i = 0; i < 16; i++) pa[i] = (i & 1) ? pn[i] ^ (one - 1) : pn[i] * one;
    }
    if (!which && up) skip();
    const uint32_t vs = take();
    TR(40);
    prep_pv(sb + vs * SLOT);
    turn_begin();
    wg_fence();
    issue_pv(1);
    wg_commit();
    turn_end();
    TR(41);
    if (!which && up) r.next();
    ws = take();
    l0 += __shfl_xor_sync(0xffffffffu, l0, 1); l1 += __shfl_xor_sync(0xffffffffu, l1, 1);
    l0 += __shfl_xor_sync(0xffffffffu, l0, 2); l1 += __shfl_xor_sync(0xffffffffu, l1, 2);
    float i0, i1;
    asm volatile("rcp.approx.ftz.f32 %0, %1;" : "=f"(i0) : "f"(l0));
    asm volatile("rcp.approx.ftz.f32 %0, %1;" : "=f"(i1) : "f"(l1));
    uint32_t xs = 0;
    if (!which) xs = take();
    wg_wait<0>();
    TR(42);
    reg_fence(acc);
    reg_fence(pa);
    give(vs, fd);
    TS(7 + 3 * which);
#pragma unroll
    for (int i = 0; i < 32; i++) {
      pk[2 * i]     = pack_bf16(acc[4 * i] * i0, acc[4 * i + 1] * i0);
      pk[2 * i + 1] = pack_bf16(acc[4 * i + 2] * i1, acc[4 * i + 3] * i1);
    }
    TS(8 + 3 * which); TR(46);
    if (which) break;
    TS(31);
    uint32_t xaddr = sb + xs * SLOT + (w ^ 1) * 8192;
#pragma unroll 1
    for (int kc = 0;; kc++) {
      TR(11);
      const uint64_t da = desc_k(xaddr), db = desc_mn(sb + ws * SLOT);
      turn_begin();
      wg_fence();
#pragma unroll
      for (int kk = 0; kk < 4; kk++) wgmma_ss_n256_tb(acc, desc_add(da, kk * 32), desc_add(db, kk * 2048), (kc | kk) != 0);
      wg_commit();
      turn_end();
      TR(13);
      const int cb = kc;
      if (cb >= 1 && cb <= 4) { fence_async_smem(); warp_arrive(bar_addr(sb, B_CTXS + 4 * w + cb - 1), lane); }
      if ((unsigned)cb < 4) {
        if (cb & 2) { if (cb & 1) store_blocks<48, 1>(qreg + 24576, lb, pk); else store_blocks<32, 1>(qreg + 16384, lb, pk); }
        else        { if (cb & 1) store_blocks<16, 1>(qreg + 8192, lb, pk);  else store_blocks<0, 1>(qreg, lb, pk); }
      }
      TR(15);
      wg_wait<0>();
      release(bar_addr(sb, B_RG_EMPTY + ws), lane);
      if (!(kc & 1)) release(bar_addr(sb, B_RG_EMPTY + xs), lane);
      if (kc == 6) break;
      ws = take();
      if (!(kc & 1)) { xs = take(); xaddr = sb + xs * SLOT + (w ^ 1) * 8192; } else xaddr += 16384;
    }
    reg_fence(acc);
    TS(61); TR(16);
#pragma unroll
    for (int i = 0; i < 64; i++) pk[i] = pack_bf16(acc[2 * i], acc[2 * i + 1]);
    TS(9); TR(19);
    qt = 15 - qt;
  }

  {
    float oa[32], ob[32];
#pragma unroll
    for (int i = 0; i < 32; i++) { oa[i] = 0.f; ob[i] = 0.f; }
    auto stage_o = [&](float (&o)[32], int ch) {
      reg_fence(o);
      uint32_t q[16];
#pragma unroll
      for (int i = 0; i < 16; i++) q[i] = pack_bf16(o[2 * i], o[2 * i + 1]);
      if (ch >= 2) mbar_wait(bar_addr(sb, B_S2_EMPTY + w * 2 + (ch & 1)), ((ch >> 1) - 1) & 1);
      store_blocks<0, 1>(qreg + (ch & 1) * 8192, lb, q);
    };
    auto hand_over = [&](int ch) {
      fence_async_smem();
      warp_arrive(bar_addr(sb, B_S2_FULL + w * 2 + (ch & 1)), lane);
    };
    uint32_t pk2[64];
    uint32_t p2 = 0;
    auto chunk = [&](int ch, auto first, float (&o)[32], float (&oprev)[32]) {
      constexpr bool FIRST = decltype(first)::value;
      const uint32_t s1 = FIRST ? ws : take();
      TR(50);
      const uint64_t d1 = desc_mn(sb + s1 * SLOT);
      turn_begin();
      wg_fence();
#pragma unroll
      for (int kk = 0; kk < 16; kk++) {
        wgmma_rs_n64_tb(o, pk[4 * kk], pk[4 * kk + 1], pk[4 * kk + 2], pk[4 * kk + 3], desc_add(d1, kk * 2048), kk != 0);
        if (kk == ARRIVE_KK) turn_end();
      }
      wg_commit();
      TR(51);
      if constexpr (!FIRST) {
        wg_wait<1>();
        release(bar_addr(sb, B_RG_EMPTY + p2), lane);
        stage_o(oprev, ch - 1);
      } else {
        mbar_wait(bar_addr(sb, B_CTXF + w), 0);
#pragma unroll
        for (int kk = 0; kk < 16; kk++) {
          uint32_t f[4];
          ldsm4(f, qreg + (kk >> 2) * 8192 + (lb ^ ((kk & 3) << 5)));
          pk2[4 * kk] = f[0]; pk2[4 * kk + 1] = f[1]; pk2[4 * kk + 2] = f[2]; pk2[4 * kk + 3] = f[3];
        }
      }
      const uint32_t s2 = take();
      TR(53);
      const uint64_t d2 = desc_mn(sb + s2 * SLOT);
      turn_begin();
      wg_fence();
#pragma unroll
      for (int kk = 0; kk < 16; kk++) {
        wgmma_rs_n64_tb(o, pk2[4 * kk], pk2[4 * kk + 1], pk2[4 * kk + 2], pk2[4 * kk + 3], desc_add(d2, kk * 2048), 1);
        if (kk == ARRIVE_KK && (ch < 6 || w == 1)) turn_end();
      }
      wg_commit();
      TR(54);
      if (!FIRST) hand_over(ch - 1);
      wg_wait<1>();
      TR(55);
      release(bar_addr(sb, B_RG_EMPTY + s1), lane);
      p2 = s2;
    };
    chunk(0, Int<1>(), oa, ob);
#pragma unroll 1
    for (int ch = 1; ch < 7; ch += 2) { chunk(ch, Int<0>(), ob, oa); chunk(ch + 1, Int<0>(), oa, ob); }
    wg_wait<0>();
    TR(58);
    reg_fence(pk);
    reg_fence(pk2);
    stage_o(oa, 6);
    hand_over(6);
  }
  TS(12); TR(59);
  if (threadIdx.x == 128) ST(14);
  if ((threadIdx.x & 127) == 0) GT(54 + w);

  TS(16); TS(18); TS(17);
  TR(99); TR_END();
  TS(13); TSG(14);
}

#define CONV_STAGGER_NS 1200
namespace ssm {
#define CONV_GROUPS (D_SPARE / 8 / NCONV)
constexpr int GROUPS = CONV_GROUPS;
constexpr uint32_t ZROWS = 16;
constexpr uint32_t CHAN = (ZROWS + 256 + 1) * 16;
constexpr uint32_t XBUF = 8 * CHAN;
constexpr uint32_t OFF_X = 0;
constexpr uint32_t HCOPY = 4160;
constexpr uint32_t OFF_H = 2 * XBUF;
constexpr uint32_t HWARP = 3 * HCOPY;
constexpr uint32_t IO_K = 128, IO_V = IO_K + 4096, IO_Q = IO_V + 4096, IOBUF = IO_Q + 4096;
constexpr uint32_t OFF_IO = (OFF_H + 8 * HWARP + 127) / 128 * 128;
constexpr uint32_t END = OFF_IO + 4 * IOBUF;
static_assert(IOBUF % 128 == 0 && OFF_H % 16 == 0, "TMA destination alignment");
static_assert(END <= BARS, "smem");
enum : uint32_t { B_XREADY = 0, B_ZDONE = 2, B_KV = 4, B_Q = 8, B_HRAW = 12, B_QLAST = 20 };
constexpr int CW_BAR = 4;

__device__ __forceinline__ int group_d0(int cidx, int grp) { return (grp * NCONV + cidx) * 8; }
__device__ __forceinline__ uint32_t x_lane(int lane) { return (lane & 7) * CHAN + (ZROWS + (lane >> 3)) * 16; }
__device__ __forceinline__ uint32_t t_lane(int lane) { return (uint32_t)(8 * (lane >> 3) + 7 - (lane & 7)) * 16; }
struct Taps { uint32_t s[4]; };
__device__ __forceinline__ Taps load_taps(const Params& p, int d0, int c) {
  const uint2 s0 = __ldg(reinterpret_cast<const uint2*>(p.a_shift + (d0 + 2 * c) * 4)), s1 = __ldg(reinterpret_cast<const uint2*>(p.a_shift + (d0 + 2 * c + 1) * 4));
  return Taps{{__byte_perm(s0.x, s1.x, 0x5410), __byte_perm(s0.x, s1.x, 0x7632), __byte_perm(s0.y, s1.y, 0x5410), __byte_perm(s0.y, s1.y, 0x7632)}};
}
__device__ __forceinline__ uint32_t short_conv(const Taps& t, uint32_t k0, uint32_t k1, uint32_t k2, uint32_t k3, uint32_t v) {
  return bmul(bfma(k3, t.s[0], bfma(k2, t.s[1], bfma(k1, t.s[2], bmul(k0, t.s[3])))), v);
}
__device__ __forceinline__ void gate_chunk(uint32_t xa, uint32_t qa) {
#pragma unroll 4
  for (int i = 0; i < 8; i++) {
    uint32_t zz[4], qq[4];
    ldsm4t(zz, xa + i * 64);
    ldsm4(qq, qa + i * 512);
    stsm4(qa + i * 512, bmul(qq[0], zz[0]), bmul(qq[1], zz[1]), bmul(qq[2], zz[2]), bmul(qq[3], zz[3]));
  }
}

__device__ __forceinline__ void io_warp(const Params& p, uint32_t sb, int cidx, int wq) {
  const int lane = threadIdx.x & 31;
  const uint32_t io = sb + OFF_IO + wq * IOBUF, bkv = bar_addr(sb, B_KV + wq), bq = bar_addr(sb, B_Q + wq);
  auto load_kv = [&](int e) {
    __syncwarp();
    if (lane != 0) return;
    const int d0 = group_d0(cidx, e >> 1), row = (2 * wq + (e & 1)) * 256;
    if (e < 2 * GROUPS) {
      mbar_expect_tx(bkv, IO_Q);
      tma_ld2(io, &p.ak8, bkv, d0, row - 8);
      tma_ld2(io + IO_K, &p.ak, bkv, d0, row);
      tma_ld2(io + IO_V, &p.av, bkv, d0, row);
    } else {
      const uint32_t bar = bar_addr(sb, B_QLAST + 2 * wq + 1);
      mbar_expect_tx(bar, 4096);
      tma_ld2(io + IO_K, &p.aq, bar, group_d0(cidx, GROUPS - 1), row + 256);
    }
  };
  auto load_q = [&](int e) {
    __syncwarp();
    if (lane != 0) return;
    const uint32_t bar = e < 2 * GROUPS - 2 ? bq : bar_addr(sb, B_QLAST + 2 * wq);
    mbar_expect_tx(bar, 4096);
    tma_ld2(io + IO_Q, &p.aq, bar, group_d0(cidx, e >> 1), (2 * wq + (e & 1)) * 256);
  };
  TR_DECL;
  TR(0);
  load_kv(0);
  const uint32_t xl = sb + OFF_X + x_lane(lane) + wq * 1024, tl = io + t_lane(lane);
#pragma unroll 1
  for (int grp = -2; grp + 1 < GROUPS; grp++) {
    const bool more = grp + 2 < GROUPS;
    const Taps taps = load_taps(p, group_d0(cidx, more ? grp + 2 : 0), lane & 3);
    PCLK(c0);
    if (grp >= 0) mbar_wait_nap(bar_addr(sb, B_ZDONE + (grp & 1)), (grp >> 1) & 1);
    PACC(tp, c0);
    PCLK(c1);
    TR(80);
#pragma unroll 1
    for (int i = 0; i < 2; i++) {
      const uint32_t xa = xl + (grp & 1) * XBUF + i * 512;
      if (grp >= 0) {
        mbar_wait_nap(bq, i);
        TR(81);
        gate_chunk(xa, tl + IO_Q);
      }
      if (more) {
        TR(82);
        mbar_wait_nap(bkv, i);
        TR(83);
#pragma unroll 2
        for (int u = 0; u < 8; u++) {
          const uint32_t ka = tl + IO_K + u * 512;
          uint32_t k0[4], k1[4], k2[4], k3[4], vv[4];
          ldsm4(k0, ka - 48); ldsm4(k1, ka - 32); ldsm4(k2, ka - 16); ldsm4(k3, ka); ldsm4(vv, ka + 4096);
          stsm4t(xa + u * 64, short_conv(taps, k0[0], k1[0], k2[0], k3[0], vv[0]), short_conv(taps, k0[1], k1[1], k2[1], k3[1], vv[1]),
                 short_conv(taps, k0[2], k1[2], k2[2], k3[2], vv[2]), short_conv(taps, k0[3], k1[3], k2[3], k3[3], vv[3]));
        }
        load_kv(2 * (grp + 2) + i + 1);
        TR(84);
        if (i == 1) warp_arrive(bar_addr(sb, B_XREADY + (grp & 1)), lane);
      }
      if (grp >= 0) {
        fence_async_smem();
        __syncwarp();
        if (lane == 0) {
          tma_st2(&p.ao, io + IO_Q, group_d0(cidx, grp), (2 * wq + i) * 256);
          bulk_commit();
          bulk_wait_read();
        }
      }
      if (2 * grp + i + 1 >= 0) load_q(2 * grp + i + 1);
      TR(85);
    }
    PACC(te, c1);
  }
  if (lane == 0) bulk_wait_all();
  TR(99); TR_END();
}

__device__ __forceinline__ void conv_warp(const Params& p, uint32_t sb, int cidx, int ch) {
  const int lane = threadIdx.x & 31;
  const uint32_t hE0 = sb + OFF_H + ch * HWARP, hO = hE0 + HCOPY;
  const uint32_t hbar = bar_addr(sb, B_HRAW + ch);
  auto fetch_h = [&](int grp) {
    if (lane == 0) {
      mbar_expect_tx(hbar, 4096);
      asm volatile("cp.async.bulk.shared::cluster.global.mbarrier::complete_tx::bytes [%0], [%1], %2, [%3];"
                   :: "r"(hE0 + (grp & 1) * 2 * HCOPY + 32), "l"(p.a_ssmk + (size_t)(group_d0(cidx, grp) + ch) * SEQ), "r"(4096), "r"(hbar) : "memory");
    }
  };
  TR_DECL;
  TR(0);
  fetch_h(0);
#pragma unroll 1
  for (int grp = 0; grp < GROUPS; grp++) {
    const uint32_t xc = sb + OFF_X + (grp & 1) * XBUF + ch * CHAN;
    const uint32_t Dd = (uint32_t)__ldg(reinterpret_cast<const unsigned short*>(p.a_D + group_d0(cidx, grp) + ch)) * 0x10001u;
    PCLK(k0);
    mbar_wait(hbar, grp & 1);
    const uint32_t hE = hE0 + (grp & 1) * 2 * HCOPY;
    if (grp + 1 < GROUPS) fetch_h(grp + 1);
#pragma unroll
    for (int i = 0; i < 8; i++) {
      const uint32_t o = 32 + (i * 32 + lane) * 16;
      const uint4 w = lds16(hE + o);
      const uint32_t nx = lds4(hE + o + 16);
      sts16(hO + o, __byte_perm(w.x, w.y, 0x5432), __byte_perm(w.y, w.z, 0x5432), __byte_perm(w.z, w.w, 0x5432), __byte_perm(w.w, nx, 0x5432));
      if (o == 32) asm volatile("st.shared.u32 [%0], %1;" :: "r"(hO + 28), "r"(w.x << 16) : "memory");
    }
    __syncwarp();
    const uint32_t ha = cv_h_lane(lane, hE, hO), xa = xc + cv_x_lane(lane);
    TR(71);
    mbar_wait(bar_addr(sb, B_XREADY + (grp & 1)), (grp >> 1) & 1);
    TR(72);
    if (grp == 0 && ch >= 4) __nanosleep(CONV_STAGGER_NS);
    PACC(tw, k0);
    PCLK(k1);
    float acc[16][4];
#pragma unroll
    for (int i = 0; i < 16; i++) { acc[i][0] = 0.f; acc[i][1] = 0.f; acc[i][2] = 0.f; acc[i][3] = 0.f; }
#pragma unroll 1
    for (int r = 0; r < 8; r++) {
      uint32_t fx[16][4], fh[16][2];
#pragma unroll
      for (int i = 0; i < 16; i++) { fh[i][0] = lds4(ha + i * 256 + r * 32); fh[i][1] = lds4(ha + i * 256 + r * 32 + 16); }
#pragma unroll
      for (int i = 0; i < 16; i++) ldsm4(fx[i], xa + i * 256 - r * 32);
#pragma unroll
      for (int sx = 0; sx < 16; sx++)
#pragma unroll
        for (int jj = 0; jj < 16 - sx; jj++) mma16816(acc[jj + sx], fx[sx], fh[jj][0], fh[jj][1]);
    }
    PACC(tm, k1);
    PCLK(k2);
    TR(73);
#pragma unroll
    for (int i = 0; i < 8; i++) {
      uint32_t x[4];
      const uint32_t ad = xc + (ZROWS + lane) * 16 + i * 512;
      ldsm4(x, ad);
      stsm4(ad, badd(pack_bf16(acc[2 * i][0], acc[2 * i][1]), bmul(x[0], Dd)), badd(pack_bf16(acc[2 * i][2], acc[2 * i][3]), bmul(x[1], Dd)),
            badd(pack_bf16(acc[2 * i + 1][0], acc[2 * i + 1][1]), bmul(x[2], Dd)), badd(pack_bf16(acc[2 * i + 1][2], acc[2 * i + 1][3]), bmul(x[3], Dd)));
    }
    if (grp + 1 < GROUPS) warp_arrive(bar_addr(sb, B_ZDONE + (grp & 1)), lane);
    PACC(tr, k2);
    TR(74);
  }
  {
    mbar_wait(bar_addr(sb, B_QLAST + ch), 0);
    named_sync(CW_BAR, 256);
    TR(75);
    const uint32_t qb = sb + OFF_IO + (ch >> 1) * IOBUF + ((ch & 1) ? IO_K : IO_Q);
    gate_chunk(sb + OFF_X + ((GROUPS - 1) & 1) * XBUF + x_lane(lane) + ch * 512, qb + t_lane(lane));
    fence_async_smem();
    __syncwarp();
    if (lane == 0) { tma_st2(&p.ao, qb, group_d0(cidx, GROUPS - 1), ch * 256); bulk_commit(); bulk_wait_all(); }
    TR(99); TR_END();
  }
}

__device__ __forceinline__ void init(uint32_t sb) {
  if (threadIdx.x < 16 * ZROWS) sts16(sb + OFF_X + (threadIdx.x >> 4) * CHAN + (threadIdx.x & 15) * 16, 0, 0, 0, 0);
  if (threadIdx.x < 96) sts16(sb + OFF_H + (threadIdx.x >> 2) * HCOPY + (threadIdx.x & 1) * 16 + ((threadIdx.x & 2) ? 4128 : 0), 0, 0, 0, 0);
  if (threadIdx.x == 0) {
    for (int i = 0; i < 2; i++) { mbar_init(bar_addr(sb, B_XREADY + i), 4); mbar_init(bar_addr(sb, B_ZDONE + i), 8); }
    for (int i = 0; i < 4; i++) { mbar_init(bar_addr(sb, B_KV + i), 1); mbar_init(bar_addr(sb, B_Q + i), 1); }
    for (int i = 0; i < 8; i++) { mbar_init(bar_addr(sb, B_HRAW + i), 1); mbar_init(bar_addr(sb, B_QLAST + i), 1); }
    fence_async_smem();
  }
  named_sync(0, NTHREADS);
}
}

__device__ __forceinline__ void ssm_side_work(const Params& p, uint32_t sb, unsigned epoch) {
  const Role ro = get_role();
  const int h = ro.h, j = ro.j;
  const int lane = threadIdx.x & 31, g = lane >> 2, c = lane & 3;
  const int d0 = D_SPARE + 8 * h;
  uint8_t* xs = g_xs + (size_t)(h * 8 + g) * CV_BYTES + c * 4;
  auto xrow = [&](int beta) { return xs + (16 + beta) * 16; };
  {
    const uint4* hp = reinterpret_cast<const uint4*>(p.a_ssmk + (size_t)(d0 + j) * SEQ) + lane;
    uint8_t* he = g_xs + (size_t)(h * 8 + j) * CV_BYTES + CV_HE;
#pragma unroll 2
    for (int i = 0; i < 8; i++) {
      const uint4 wv = __ldg(hp + i * 32);
      const uint32_t nx = i * 32 + lane < 255 ? __ldg(reinterpret_cast<const uint32_t*>(hp + i * 32 + 1)) : 0u;
      const uint32_t o = 32 + (i * 32 + lane) * 16;
      *reinterpret_cast<uint4*>(he + o) = wv;
      *reinterpret_cast<uint4*>(he + CV_HCOPY + o) =
          make_uint4(__byte_perm(wv.x, wv.y, 0x5432), __byte_perm(wv.y, wv.z, 0x5432), __byte_perm(wv.z, wv.w, 0x5432), __byte_perm(wv.w, nx, 0x5432));
      if (o == 32) *reinterpret_cast<uint32_t*>(he + CV_HCOPY + 28) = wv.x << 16;
    }
    if (lane == 0) *reinterpret_cast<uint32_t*>(he + CV_D - CV_HE) = (uint32_t)__ldg(reinterpret_cast<const unsigned short*>(p.a_D + d0 + j)) * 0x10001u;
  }
  {
    const ssm::Taps taps = ssm::load_taps(p, d0, c);
    const uint32_t* kp = reinterpret_cast<const uint32_t*>(p.a_k + (size_t)(256 * j + 7 - g) * DA + d0) + c;
    const uint32_t* vp = reinterpret_cast<const uint32_t*>(p.a_v + (size_t)(256 * j + 7 - g) * DA + d0) + c;
    uint32_t kprev = j > 0 ? __ldg(kp - 8 * (DA / 2)) : 0u;
#pragma unroll 1
    for (int i0 = 0; i0 < 32; i0 += 8) {
      uint32_t kk[8], vv[8];
#pragma unroll
      for (int i = 0; i < 8; i++) { kk[i] = __ldg(kp + (i0 + i) * 8 * (DA / 2)); vv[i] = __ldg(vp + (i0 + i) * 8 * (DA / 2)); }
#pragma unroll
      for (int i = 0; i < 8; i++) {
        const uint32_t k2 = __shfl_sync(0xffffffffu, g < 1 ? kprev : kk[i], (lane + 4) & 31);
        const uint32_t k1 = __shfl_sync(0xffffffffu, g < 2 ? kprev : kk[i], (lane + 8) & 31);
        const uint32_t k0 = __shfl_sync(0xffffffffu, g < 3 ? kprev : kk[i], (lane + 12) & 31);
        *reinterpret_cast<uint32_t*>(xrow(32 * j + i0 + i)) = transpose8(ssm::short_conv(taps, k0, k1, k2, kk[i], vv[i]));
        kprev = kk[i];
      }
    }
    __syncwarp();
    if (lane == 0) {
      flag_signal(&g_flags.xs_ready[h].v);
      flag_wait(&g_flags.xs_ready[h].v, 8, epoch);
      fence_async_all();
      mbar_arrive(bar_addr(sb, B_XS));
    }
  }
  if (lane == 0) {
    for (int i = 0; i < 3; i++) {
      flag_wait(&g_flags.kv_ready[3 * h + i].v, 16, epoch);
      fence_async_all();
      mbar_arrive(bar_addr(sb, B_KV + i));
    }
    mbar_wait_nap(bar_addr(sb, B_CONV), 0);
    flag_signal(&g_flags.zs_ready[h].v);
    flag_wait(&g_flags.zs_ready[h].v, 8, epoch);
    asm volatile("red.relaxed.gpu.global.add.u64 [%0], 1;" :: "l"(&g_flags.done) : "memory");
  }
  __syncwarp();
  fence_async_all();
  const uint32_t qb = q_region(sb, 1) + 16384, zb = qb + 4096, bar = bar_addr(sb, B_GATE);
  constexpr uint32_t ZCH = 528;
  mbar_wait_slow(bar_addr(sb, B_GFREE), 0);
  if (lane == 0) { mbar_expect_tx(bar, 8192); tma_ld2(qb, &p.aq, bar, d0, 256 * j); }
  __syncwarp();
  if (lane < 8) bulk_ld(zb + lane * ZCH, g_xs + (size_t)(h * 8 + lane) * CV_BYTES + (16 + 32 * j) * 16, 512, bar);
  mbar_wait(bar, 0);
  ssm::gate_chunk(zb + (lane & 7) * ZCH + (lane >> 3) * 16, qb + ssm::t_lane(lane));
  fence_async_smem();
  __syncwarp();
  if (lane == 0) { tma_st2(&p.ao, qb, d0, 256 * j); bulk_commit(); bulk_wait_all(); }
}

__global__ void __cluster_dims__(2, 1, 1) __launch_bounds__(NTHREADS, 1)
concat_heads__ssm_conv_h3__compressed_kv_cla__prompt_kernel(uint8_t* xs, uint32_t one, const __grid_constant__ Params p) {
  if (threadIdx.x == 0) { prefetch_map(&p.wuk); prefetch_map(&p.ckv); }
  extern __shared__ uint8_t smem_raw[];
  if (threadIdx.x == 96) { ST(0); STG_(10); }
  const uint32_t sb = (smem_u32(smem_raw) + 1023) & ~1023u;
  const int warp = __shfl_sync(0xffffffffu, threadIdx.x >> 5, 0);
  const int wg = warp >> 2;
  const int cta = blockIdx.x;
  const bool attn = cta < NMAIN;
  if (attn && (threadIdx.x >> 5) == 4) {
    const Role ro = get_role();
    auto load = [&](int k) {
      const uint32_t full = bar_addr(sb, B_P1_FULL + k), dst = sb + k * P1_STAGE;
      mbar_expect_tx(full, P1_STAGE);
      tma_ld2(dst, &p.ckv, full, k * 64, kv_block(ro.j, 0) * 128);
      tma_ld3(dst + 16384, &p.wuk, full, 0, k * 64, ro.h * 4);
    };
    if (threadIdx.x == 128) {
      for (int i = 0; i < 4; i++) mbar_init(bar_addr(sb, B_P1_FULL + i), 1);
      asm volatile("fence.mbarrier_init.release.cluster;" ::: "memory");
      ST(1);
      load(0);
    }
    __syncwarp();
    named_arrive(0, NTHREADS);
    if (threadIdx.x == 128) {
      for (int k = 1; k < EARLY_LD; k++) load(k);
      ST(2);
    }
    __syncwarp();
  }
  const int lane = threadIdx.x & 31;
  if (wg == 0) {
    if (!attn) {
      asm volatile("setmaxnreg.dec.sync.aligned.u32 72;");
      if (threadIdx.x == 0) GT(0);
      if (one) { ssm::init(sb); ssm::io_warp(p, sb, cta - NMAIN, fresh_warp()); }
      if (threadIdx.x == 0) GT(14);
      return;
    }
    asm volatile("setmaxnreg.dec.sync.aligned.u32 40;");
    named_arrive(PP_BAR + 1, 256);
    if (warp == 2) {
      if (lane == 0) {
        for (int i = 0; i < 4; i++) mbar_init(bar_addr(sb, B_P1_EMPTY + i), 8);
        for (int i = 0; i < NSLOT; i++) {
          mbar_init(bar_addr(sb, B_RG_FULL + i), 1); mbar_init(bar_addr(sb, B_RG_EMPTY + i), 8);
        }
        for (int i = 0; i < 2; i++) { mbar_init(bar_addr(sb, B_ST_FULL + i), 4); mbar_init(bar_addr(sb, B_ST_EMPTY + i), 1); }
        mbar_init(bar_addr(sb, B_XS), 1); mbar_init(bar_addr(sb, B_CONV), 8); mbar_init(bar_addr(sb, B_GATE), 1); mbar_init(bar_addr(sb, B_GFREE), 1);
        for (int i = 0; i < 3; i++) mbar_init(bar_addr(sb, B_KV + i), 1);
        for (int i = 0; i < 8; i++) mbar_init(bar_addr(sb, B_CTXS + i), 4);
        for (int i = 0; i < 4; i++) { mbar_arrive(bar_addr(sb, B_RG_FULL + i)); if (i < 3) mbar_arrive_n(bar_addr(sb, B_RG_EMPTY + i), 8); }
        for (int i = 0; i < 4; i++) { mbar_init(bar_addr(sb, B_S2_FULL + i), 4); mbar_init(bar_addr(sb, B_S2_EMPTY + i), 1); }
        for (int i = 0; i < 2; i++) { mbar_init(bar_addr(sb, B_QFREE + i), 4); mbar_init(bar_addr(sb, B_CTXF + i), 1); }
        asm volatile("fence.mbarrier_init.release.cluster;" ::: "memory");
        ST(3);
      }
      __syncwarp();
      named_arrive(0, NTHREADS);
    } else {
      named_sync(0, NTHREADS);
    }
    if (threadIdx.x == 96) ST(4);
    if (warp == 0) {
      if (lane == 0) producer_main(p, sb);
    } else if (warp < 3) {
      storer_main(p, sb);
    } else {
      const unsigned epoch = load_epoch();
      mbar_wait(bar_addr(sb, B_P1_FULL + 3), 0);
      __nanosleep(SIDE_DELAY_NS);
      ssm_side_work(p, sb, epoch);
    }
  } else {
    if (attn) {
      asm volatile("setmaxnreg.inc.sync.aligned.u32 232;");
      if (threadIdx.x == 256) ST(5);
      if (one) consumer_main(p, sb, xs, one);
    } else {
      asm volatile("setmaxnreg.inc.sync.aligned.u32 216;");
      if (threadIdx.x == 128) { GT(12); PT(10); }
      if (one) { ssm::init(sb); ssm::conv_warp(p, sb, cta - NMAIN, fresh_warp() - 4); }
      if (threadIdx.x == 128) { PT(9); GT(13); }
    }
  }
}

typedef CUresult (*EncodeTiledFn)(CUtensorMap*, CUtensorMapDataType, cuuint32_t, void*, const cuuint64_t*, const cuuint64_t*,
                                  const cuuint32_t*, const cuuint32_t*, CUtensorMapInterleave, CUtensorMapSwizzle,
                                  CUtensorMapL2promotion, CUtensorMapFloatOOBfill);

void make_map(EncodeTiledFn enc, CUtensorMap* m, const void* ptr, int rank, const uint64_t* dims, const uint64_t* strides, const uint32_t* box) {
  cuuint64_t d[3], s[2]; cuuint32_t b[3], e[3] = {1, 1, 1};
  for (int i = 0; i < rank; i++) { d[i] = dims[i]; b[i] = box[i]; if (i) s[i - 1] = strides[i - 1]; }
  enc(m, CU_TENSOR_MAP_DATA_TYPE_BFLOAT16, rank, const_cast<void*>(ptr), d, s, b, e, CU_TENSOR_MAP_INTERLEAVE_NONE,
      CU_TENSOR_MAP_SWIZZLE_128B, CU_TENSOR_MAP_L2_PROMOTION_L2_256B, CU_TENSOR_MAP_FLOAT_OOB_FILL_NONE);
}
void map2(EncodeTiledFn enc, CUtensorMap* m, const void* ptr, uint64_t cols, uint64_t rows, uint32_t bc, uint32_t br) {
  const uint64_t dims[2] = {cols, rows}, st[1] = {cols * 2}; const uint32_t box[2] = {bc, br};
  make_map(enc, m, ptr, 2, dims, st, box);
}
void map2_plain(EncodeTiledFn enc, CUtensorMap* m, const void* ptr, uint64_t cols, uint64_t rows, uint32_t bc, uint32_t br) {
  cuuint64_t d[2] = {cols, rows}, st[1] = {cols * 2}; cuuint32_t b[2] = {bc, br}, e[2] = {1, 1};
  enc(m, CU_TENSOR_MAP_DATA_TYPE_BFLOAT16, 2, const_cast<void*>(ptr), d, st, b, e, CU_TENSOR_MAP_INTERLEAVE_NONE,
      CU_TENSOR_MAP_SWIZZLE_NONE, CU_TENSOR_MAP_L2_PROMOTION_L2_128B, CU_TENSOR_MAP_FLOAT_OOB_FILL_NONE);
}
void map3(EncodeTiledFn enc, CUtensorMap* m, const void* ptr, uint64_t rows, uint32_t nblk) {
  const uint64_t dims[3] = {64, rows, 64}, st[2] = {8192, 128}; const uint32_t box[3] = {64, 64, nblk};
  make_map(enc, m, ptr, 3, dims, st, box);
}

}

extern "C" void kernel_launch(void* const* d_in, const int* in_sizes, int n_in, void* d_out, int out_size) {
  (void)in_sizes; (void)n_in; (void)out_size;
  static EncodeTiledFn enc = nullptr;
  static void *kv_ptr = nullptr, *acc_ptr = nullptr, *xs_ptr = nullptr;
  if (!enc) {
    void* fn = nullptr; cudaDriverEntryPointQueryResult qr;
    cudaGetDriverEntryPoint("cuTensorMapEncodeTiled", &fn, cudaEnableDefault, &qr);
    enc = (EncodeTiledFn)fn;
    cudaGetSymbolAddress(&kv_ptr, g_kv);
    cudaGetSymbolAddress(&acc_ptr, g_ctx);
    cudaGetSymbolAddress(&xs_ptr, g_xs);
    cudaFuncSetAttribute(concat_heads__ssm_conv_h3__compressed_kv_cla__prompt_kernel, cudaFuncAttributeMaxDynamicSharedMemorySize, SMEM_BYTES);
  }
  Params p;
  p.a_q = (const bf16*)d_in[0]; p.a_k = (const bf16*)d_in[1]; p.a_v = (const bf16*)d_in[2];
  map2_plain(enc, &p.aq, d_in[0], DA, SEQ, 8, 256);
  map2_plain(enc, &p.ak, d_in[1], DA, SEQ, 8, 256);
  map2_plain(enc, &p.ak8, d_in[1], DA, SEQ, 8, 8);
  map2_plain(enc, &p.av, d_in[2], DA, SEQ, 8, 256);
  map2_plain(enc, &p.ao, d_out, OUTW, SEQ, 8, 256);
  p.a_shift = (const bf16*)d_in[3]; p.a_ssmk = (const bf16*)d_in[4]; p.a_D = (const bf16*)d_in[5];
  p.out = (bf16*)d_out; p.b_x = (const bf16*)d_in[6]; p.b_wo = (const bf16*)d_in[11];
  map2(enc, &p.x, d_in[6], DM, SEQ, 64, 128);
  map2(enc, &p.ckv, d_in[7], DC, SEQ, 64, 128);
  map3(enc, &p.wq, d_in[8], DM, 4);
  map2_plain(enc, &p.wqp, d_in[8], NH * HD, DM, 256, 4);
  map3(enc, &p.wuk, d_in[9], DC, 4);
  map3(enc, &p.wuv, d_in[10], DC, 4);
  map2(enc, &p.wo, d_in[11], DM, NH * HD, 64, 256);
  map2(enc, &p.part, d_out, OUTW, SEQ, 64, 64);
  p.kv = (uint8_t*)kv_ptr; p.ctx = (uint8_t*)acc_ptr;
  concat_heads__ssm_conv_h3__compressed_kv_cla__prompt_kernel<<<NCTA, NTHREADS, SMEM_BYTES>>>((uint8_t*)xs_ptr, 1u, p);
}
```

```cpp
#include <cuda_runtime.h>
#include <cuda_bf16.h>
#include <cuda.h>
#include <stdint.h>

namespace {

typedef __nv_bfloat16 bf16;

constexpr int SEQ  = 2048;
constexpr int DA   = 448;
constexpr int NH   = 16;
constexpr int HD   = 256;
constexpr int DM   = 448;
constexpr int DC   = 1024;
constexpr int OUTW = DA + DM;
constexpr int NMAIN = 128;
constexpr int NCONV = 4;
constexpr int NCTA  = NMAIN + NCONV;
constexpr int NTHREADS = 384;
constexpr int D_SPARE = 320;

__device__ __align__(1024) bf16 g_kv[2ull * SEQ * NH * HD];
__device__ __align__(1024) bf16 g_ctx[(size_t)NMAIN * 128 * HD];
constexpr uint32_t CV_HE = 272 * 16, CV_HCOPY = 4160, CV_D = CV_HE + 4144, CV_BYTES = CV_HE + 2 * CV_HCOPY;
__device__ __align__(128) uint8_t g_xs[NMAIN * CV_BYTES];
struct alignas(128) Flag { unsigned v; unsigned pad[31]; };
struct Flags {
  Flag kv_ready[3 * NH];
  Flag ctx_ready[NMAIN * 2];
  Flag out_ready[16 * 2];
  Flag xs_ready[NH];
  Flag zs_ready[NH];
  alignas(128) unsigned long long done;
};
__device__ Flags g_flags;
#define TS(i)
#define TSG(i)
#define GT(i)
#define PT(i)
#define WHICH_TS 0
#define PCLK(var)
#define PACC(acc, t0)
#define PDECL
#define PDUMP()

#define CP_DECL
#define CP()
#define ST(i)
#define STG_(i)
#define TR_DECL
#define TR(tag)
#define TR_END()
#define TRG(tag)

struct alignas(64) Params {
  CUtensorMap ckv;
  CUtensorMap wuk;
  CUtensorMap wuv;
  CUtensorMap x;
  CUtensorMap wq;
  CUtensorMap wqp;
  CUtensorMap part;
  CUtensorMap wo;
  CUtensorMap ak, ak8, av, aq, ao;
  const bf16 *a_q, *a_k, *a_v, *a_shift, *a_ssmk, *a_D, *b_x, *b_wo;
  bf16* out;
  uint8_t *kv, *ctx;
};

constexpr uint32_t P1_STAGE = 49152;
constexpr uint32_t P1_STG   = 196608;
constexpr uint32_t SLOT     = 32768;
constexpr int      NSLOT    = 5;
constexpr uint32_t QREG     = 163840;
constexpr uint32_t CV_X = 4 * SLOT + 16384, CV_R = 3 * SLOT;
static_assert(CV_BYTES <= 16384 && CV_BYTES % 128 == 0, "SSM operands");
constexpr uint32_t BARS     = 229376;
constexpr uint32_t SMEM_BYTES = BARS + 512 + 1024;
enum : uint32_t {
  B_P1_FULL = 0, B_P1_EMPTY = 4, B_RG_FULL = 8, B_RG_EMPTY = 13, B_ST_FULL = 18, B_ST_EMPTY = 20,
  B_XS = 22, B_S2_FULL = 28, B_S2_EMPTY = 32, B_QFREE = 36, B_CTXF = 38, B_KV = 40, B_GATE = 43, B_CTXS = 44, B_GFREE = 52, B_CONV = 53, B_COUNT = 54
};

__device__ __forceinline__ uint32_t smem_u32(const void* p) { return (uint32_t)__cvta_generic_to_shared(p); }
__device__ __forceinline__ void mbar_init(uint32_t bar, uint32_t cnt) {
  asm volatile("mbarrier.init.shared::cta.b64 [%0], %1;" :: "r"(bar), "r"(cnt) : "memory");
}
__device__ __forceinline__ void mbar_expect_tx(uint32_t bar, uint32_t bytes) {
  asm volatile("mbarrier.arrive.expect_tx.shared::cta.b64 _, [%0], %1;" :: "r"(bar), "r"(bytes) : "memory");
}
__device__ __forceinline__ void mbar_arrive(uint32_t bar) {
  asm volatile("mbarrier.arrive.shared::cta.b64 _, [%0];" :: "r"(bar) : "memory");
}
__device__ __forceinline__ void mbar_arrive_n(uint32_t bar, uint32_t n) {
  asm volatile("mbarrier.arrive.shared::cta.b64 _, [%0], %1;" :: "r"(bar), "r"(n) : "memory");
}
__device__ __forceinline__ void lane0_arrive(uint32_t bar, uint32_t n, int lane) {
  asm volatile("{\n.reg .pred p;\nsetp.eq.s32 p, %2, 0;\n@p mbarrier.arrive.shared::cta.b64 _, [%0], %1;\n}" :: "r"(bar), "r"(n), "r"(lane) : "memory");
}
__device__ __forceinline__ bool mbar_try(uint32_t bar, uint32_t parity) {
  uint32_t ok;
  asm volatile("{\n.reg .pred p;\nmbarrier.try_wait.parity.shared::cta.b64 p, [%1], %2;\nselp.u32 %0, 1, 0, p;\n}"
               : "=r"(ok) : "r"(bar), "r"(parity) : "memory");
  return ok;
}
#define FLAG_NS 100
#define NAP_NS 100
constexpr uint32_t SPIN_LIMIT = 1u << 24;
__device__ __forceinline__ void mbar_wait(uint32_t bar, uint32_t parity) {
  if (mbar_try(bar, parity)) return;
  uint32_t n = 0;
  while (!mbar_try(bar, parity)) { if (++n > SPIN_LIMIT) __trap(); }
}
__device__ __forceinline__ void mbar_wait_nap(uint32_t bar, uint32_t parity) {
  uint32_t n = 0;
  while (!mbar_try(bar, parity)) { if (++n > (SPIN_LIMIT >> 2)) __trap(); __nanosleep(NAP_NS); }
}
__device__ __forceinline__ void mbar_wait_slow(uint32_t bar, uint32_t parity) {
  uint32_t n = 0;
  while (!mbar_try(bar, parity)) { if (++n > (SPIN_LIMIT >> 4)) __trap(); __nanosleep(500); }
}
__device__ __forceinline__ unsigned load_epoch() {
  unsigned long long e; asm volatile("ld.relaxed.gpu.global.u64 %0, [%1];" : "=l"(e) : "l"(&g_flags.done) : "memory"); return (unsigned)(e / NMAIN);
}
__device__ __forceinline__ void flag_wait(const unsigned* f, unsigned count, unsigned epoch) {
  const unsigned target = (epoch + 1) * count;
  uint32_t n = 0;
  while (true) {
    unsigned v;
    asm volatile("ld.acquire.gpu.global.u32 %0, [%1];" : "=r"(v) : "l"(f) : "memory");
    if ((int)(v - target) >= 0) break;
    if (++n > SPIN_LIMIT) __trap();
    __nanosleep(FLAG_NS);
  }
}
__device__ __forceinline__ void fence_async_all() { asm volatile("fence.proxy.async;" ::: "memory"); }
__device__ __forceinline__ void flag_signal(unsigned* f) {
  asm volatile("fence.acq_rel.gpu;" ::: "memory");
  asm volatile("red.relaxed.gpu.global.add.u32 [%0], 1;" :: "l"(f) : "memory");
}
__device__ __forceinline__ void flag_signal_after_bulk(unsigned* f) {
  asm volatile("red.relaxed.gpu.global.add.u32 [%0], 1;" :: "l"(f) : "memory");
}
__device__ __forceinline__ void fence_async_smem() { asm volatile("fence.proxy.async.shared::cta;" ::: "memory"); }
__device__ __forceinline__ void tma_ld2(uint32_t dst, const CUtensorMap* m, uint32_t bar, int c0, int c1) {
  asm volatile("cp.async.bulk.tensor.2d.shared::cluster.global.mbarrier::complete_tx::bytes [%0], [%1, {%3, %4}], [%2];"
               :: "r"(dst), "l"(m), "r"(bar), "r"(c0), "r"(c1) : "memory");
}
__device__ __forceinline__ void tma_ld3(uint32_t dst, const CUtensorMap* m, uint32_t bar, int c0, int c1, int c2) {
  asm volatile("cp.async.bulk.tensor.3d.shared::cluster.global.mbarrier::complete_tx::bytes [%0], [%1, {%3, %4, %5}], [%2];"
               :: "r"(dst), "l"(m), "r"(bar), "r"(c0), "r"(c1), "r"(c2) : "memory");
}
__device__ __forceinline__ void bulk_ld(uint32_t dst, const void* src, uint32_t bytes, uint32_t bar) {
  asm volatile("cp.async.bulk.shared::cluster.global.mbarrier::complete_tx::bytes [%0], [%1], %2, [%3];"
               :: "r"(dst), "l"(src), "r"(bytes), "r"(bar) : "memory");
}
__device__ __forceinline__ void bulk_st(void* dst, uint32_t src, uint32_t bytes) {
  asm volatile("cp.async.bulk.global.shared::cta.bulk_group [%0], [%1], %2;" :: "l"(dst), "r"(src), "r"(bytes) : "memory");
}
__device__ __forceinline__ void tma_st2(const CUtensorMap* m, uint32_t src, int c0, int c1) {
  asm volatile("cp.async.bulk.tensor.2d.global.shared::cta.bulk_group [%0, {%2, %3}], [%1];"
               :: "l"(m), "r"(src), "r"(c0), "r"(c1) : "memory");
}
__device__ __forceinline__ void tma_red2(const CUtensorMap* m, uint32_t src, int c0, int c1) {
  asm volatile("cp.reduce.async.bulk.tensor.2d.global.shared::cta.add.tile.bulk_group [%0, {%2, %3}], [%1];"
               :: "l"(m), "r"(src), "r"(c0), "r"(c1) : "memory");
}
__device__ __forceinline__ void tma_pf2(const CUtensorMap* m, int c0, int c1) {
  asm volatile("cp.async.bulk.prefetch.tensor.2d.L2.global.tile [%0, {%1, %2}];" :: "l"(m), "r"(c0), "r"(c1) : "memory");
}
__device__ __forceinline__ void bulk_prefetch(const void* src, uint32_t bytes) {
  asm volatile("cp.async.bulk.prefetch.L2.global [%0], %1;" :: "l"(src), "r"(bytes) : "memory");
}
__device__ __forceinline__ void bulk_commit() { asm volatile("cp.async.bulk.commit_group;" ::: "memory"); }
__device__ __forceinline__ void bulk_wait_read() { asm volatile("cp.async.bulk.wait_group.read 0;" ::: "memory"); }
__device__ __forceinline__ void bulk_wait_all() { asm volatile("cp.async.bulk.wait_group 0;" ::: "memory"); }
__device__ __forceinline__ void prefetch_map(const CUtensorMap* m) { asm volatile("prefetch.tensormap [%0];" :: "l"(m) : "memory"); }
__device__ __forceinline__ void wg_fence() { asm volatile("wgmma.fence.sync.aligned;" ::: "memory"); }
__device__ __forceinline__ void wg_commit() { asm volatile("wgmma.commit_group.sync.aligned;" ::: "memory"); }
template <int N> __device__ __forceinline__ void wg_wait() { asm volatile("wgmma.wait_group.sync.aligned %0;" :: "n"(N) : "memory"); }
template <int N> __device__ __forceinline__ void reg_fence(float (&d)[N]) {
#pragma unroll
  for (int i = 0; i < N; i++) asm volatile("" : "+f"(d[i]) :: "memory");
}
template <int N> __device__ __forceinline__ void reg_fence(uint32_t (&d)[N]) {
#pragma unroll
  for (int i = 0; i < N; i++) asm volatile("" : "+r"(d[i]) :: "memory");
}
__device__ __forceinline__ uint32_t fresh_tid() { uint32_t t; asm volatile("mov.u32 %0, %%tid.x;" : "=r"(t)); return t; }
__device__ __forceinline__ uint32_t lane_base16() {
  const uint32_t t = fresh_tid(), lane = t & 31, wq = (t >> 5) & 3;
  return (16 * wq + (lane & 7) + 8 * ((lane >> 3) & 1)) * 128 + (((lane >> 4) ^ (lane & 7)) << 4);
}
__device__ __forceinline__ void named_sync(int id, int n) { asm volatile("bar.sync %0, %1;" :: "r"(id), "r"(n) : "memory"); }
__device__ __forceinline__ void named_arrive(int id, int n) { asm volatile("bar.arrive %0, %1;" :: "r"(id), "r"(n) : "memory"); }
__device__ __forceinline__ uint32_t pack_bf16(float lo, float hi) {
  uint32_t r; asm("cvt.rn.bf16x2.f32 %0, %1, %2;" : "=r"(r) : "f"(hi), "f"(lo)); return r;
}
__device__ __forceinline__ float ex2(float x) { float y; asm("ex2.approx.ftz.f32 %0, %1;" : "=f"(y) : "f"(x)); return y; }
__device__ __forceinline__ void stsm4(uint32_t addr, uint32_t a, uint32_t b, uint32_t c, uint32_t d) {
  asm volatile("stmatrix.sync.aligned.m8n8.x4.shared.b16 [%0], {%1, %2, %3, %4};" :: "r"(addr), "r"(a), "r"(b), "r"(c), "r"(d) : "memory");
}
__device__ __forceinline__ void stsm4t(uint32_t addr, uint32_t a, uint32_t b, uint32_t c, uint32_t d) {
  asm volatile("stmatrix.sync.aligned.m8n8.x4.trans.shared.b16 [%0], {%1, %2, %3, %4};" :: "r"(addr), "r"(a), "r"(b), "r"(c), "r"(d) : "memory");
}
__device__ __forceinline__ uint64_t mk_desc(uint32_t addr, uint32_t lbo, uint32_t sbo) {
  return (uint64_t)(((addr & 0x3FFFF) >> 4) | ((lbo >> 4) << 16)) | ((uint64_t)((sbo >> 4) | (1u << 30)) << 32);
}
__device__ __forceinline__ uint64_t desc_k(uint32_t addr)  { return mk_desc(addr, 16, 1024); }
__device__ __forceinline__ uint64_t desc_mn(uint32_t addr) { return mk_desc(addr, 8192, 1024); }
__device__ __forceinline__ uint64_t desc_add(uint64_t d, uint32_t bytes) { return d + (bytes >> 4); }

__device__ __forceinline__ void wgmma_ss_n256_tb(float (&d)[128], uint64_t da, uint64_t db, int sd) {
  asm volatile("{\n.reg .pred p;\nsetp.ne.b32 p, %130, 0;\n"
    "wgmma.mma_async.sync.aligned.m64n256k16.f32.bf16.bf16 "
    "{%0, %1, %2, %3, %4, %5, %6, %7, %8, %9, %10, %11, %12, %13, %14, %15, "
    "%16, %17, %18, %19, %20, %21, %22, %23, %24, %25, %26, %27, %28, %29, %30, %31, "
    "%32, %33, %34, %35, %36, %37, %38, %39, %40, %41, %42, %43, %44, %45, %46, %47, "
    "%48, %49, %50, %51, %52, %53, %54, %55, %56, %57, %58, %59, %60, %61, %62, %63, "
    "%64, %65, %66, %67, %68, %69, %70, %71, %72, %73, %74, %75, %76, %77, %78, %79, "
    "%80, %81, %82, %83, %84, %85, %86, %87, %88, %89, %90, %91, %92, %93, %94, %95, "
    "%96, %97, %98, %99, %100, %101, %102, %103, %104, %105, %106, %107, %108, %109, %110, %111, "
    "%112, %113, %114, %115, %116, %117, %118, %119, %120, %121, %122, %123, %124, %125, %126, %127}, "
    "%128, %129, p, 1, 1, 0, 1;\n}"
    : "+f"(d[0]), "+f"(d[1]), "+f"(d[2]), "+f"(d[3]), "+f"(d[4]), "+f"(d[5]), "+f"(d[6]), "+f"(d[7]),
      "+f"(d[8]), "+f"(d[9]), "+f"(d[10]), "+f"(d[11]), "+f"(d[12]), "+f"(d[13]), "+f"(d[14]), "+f"(d[15]),
      "+f"(d[16]), "+f"(d[17]), "+f"(d[18]), "+f"(d[19]), "+f"(d[20]), "+f"(d[21]), "+f"(d[22]), "+f"(d[23]),
      "+f"(d[24]), "+f"(d[25]), "+f"(d[26]), "+f"(d[27]), "+f"(d[28]), "+f"(d[29]), "+f"(d[30]), "+f"(d[31]),
      "+f"(d[32]), "+f"(d[33]), "+f"(d[34]), "+f"(d[35]), "+f"(d[36]), "+f"(d[37]), "+f"(d[38]), "+f"(d[39]),
      "+f"(d[40]), "+f"(d[41]), "+f"(d[42]), "+f"(d[43]), "+f"(d[44]), "+f"(d[45]), "+f"(d[46]), "+f"(d[47]),
      "+f"(d[48]), "+f"(d[49]), "+f"(d[50]), "+f"(d[51]), "+f"(d[52]), "+f"(d[53]), "+f"(d[54]), "+f"(d[55]),
      "+f"(d[56]), "+f"(d[57]), "+f"(d[58]), "+f"(d[59]), "+f"(d[60]), "+f"(d[61]), "+f"(d[62]), "+f"(d[63]),
      "+f"(d[64]), "+f"(d[65]), "+f"(d[66]), "+f"(d[67]), "+f"(d[68]), "+f"(d[69]), "+f"(d[70]), "+f"(d[71]),
      "+f"(d[72]), "+f"(d[73]), "+f"(d[74]), "+f"(d[75]), "+f"(d[76]), "+f"(d[77]), "+f"(d[78]), "+f"(d[79]),
      "+f"(d[80]), "+f"(d[81]), "+f"(d[82]), "+f"(d[83]), "+f"(d[84]), "+f"(d[85]), "+f"(d[86]), "+f"(d[87]),
      "+f"(d[88]), "+f"(d[89]), "+f"(d[90]), "+f"(d[91]), "+f"(d[92]), "+f"(d[93]), "+f"(d[94]), "+f"(d[95]),
      "+f"(d[96]), "+f"(d[97]), "+f"(d[98]), "+f"(d[99]), "+f"(d[100]), "+f"(d[101]), "+f"(d[102]), "+f"(d[103]),
      "+f"(d[104]), "+f"(d[105]), "+f"(d[106]), "+f"(d[107]), "+f"(d[108]), "+f"(d[109]), "+f"(d[110]), "+f"(d[111]),
      "+f"(d[112]), "+f"(d[113]), "+f"(d[114]), "+f"(d[115]), "+f"(d[116]), "+f"(d[117]), "+f"(d[118]), "+f"(d[119]),
      "+f"(d[120]), "+f"(d[121]), "+f"(d[122]), "+f"(d[123]), "+f"(d[124]), "+f"(d[125]), "+f"(d[126]), "+f"(d[127])
    : "l"(da), "l"(db), "r"(sd));
}
__device__ __forceinline__ void wgmma_ss_n64(float (&d)[32], uint64_t da, uint64_t db, int sd) {
  asm volatile("{\n.reg .pred p;\nsetp.ne.b32 p, %34, 0;\n"
    "wgmma.mma_async.sync.aligned.m64n64k16.f32.bf16.bf16 "
    "{%0, %1, %2, %3, %4, %5, %6, %7, %8, %9, %10, %11, %12, %13, %14, %15, "
    "%16, %17, %18, %19, %20, %21, %22, %23, %24, %25, %26, %27, %28, %29, %30, %31}, "
    "%32, %33, p, 1, 1, 0, 0;\n}"
    : "+f"(d[0]), "+f"(d[1]), "+f"(d[2]), "+f"(d[3]), "+f"(d[4]), "+f"(d[5]), "+f"(d[6]), "+f"(d[7]),
      "+f"(d[8]), "+f"(d[9]), "+f"(d[10]), "+f"(d[11]), "+f"(d[12]), "+f"(d[13]), "+f"(d[14]), "+f"(d[15]),
      "+f"(d[16]), "+f"(d[17]), "+f"(d[18]), "+f"(d[19]), "+f"(d[20]), "+f"(d[21]), "+f"(d[22]), "+f"(d[23]),
      "+f"(d[24]), "+f"(d[25]), "+f"(d[26]), "+f"(d[27]), "+f"(d[28]), "+f"(d[29]), "+f"(d[30]), "+f"(d[31])
    : "l"(da), "l"(db), "r"(sd));
}
__device__ __forceinline__ void wgmma_rs_n256_tb(float (&d)[128], uint32_t a0, uint32_t a1, uint32_t a2, uint32_t a3, uint64_t db, int sd) {
  asm volatile("{\n.reg .pred p;\nsetp.ne.b32 p, %133, 0;\n"
    "wgmma.mma_async.sync.aligned.m64n256k16.f32.bf16.bf16 "
    "{%0, %1, %2, %3, %4, %5, %6, %7, %8, %9, %10, %11, %12, %13, %14, %15, "
    "%16, %17, %18, %19, %20, %21, %22, %23, %24, %25, %26, %27, %28, %29, %30, %31, "
    "%32, %33, %34, %35, %36, %37, %38, %39, %40, %41, %42, %43, %44, %45, %46, %47, "
    "%48, %49, %50, %51, %52, %53, %54, %55, %56, %57, %58, %59, %60, %61, %62, %63, "
    "%64, %65, %66, %67, %68, %69, %70, %71, %72, %73, %74, %75, %76, %77, %78, %79, "
    "%80, %81, %82, %83, %84, %85, %86, %87, %88, %89, %90, %91, %92, %93, %94, %95, "
    "%96, %97, %98, %99, %100, %101, %102, %103, %104, %105, %106, %107, %108, %109, %110, %111, "
    "%112, %113, %114, %115, %116, %117, %118, %119, %120, %121, %122, %123, %124, %125, %126, %127}, "
    "{%128, %129, %130, %131}, %132, p, 1, 1, 1;\n}"
    : "+f"(d[0]), "+f"(d[1]), "+f"(d[2]), "+f"(d[3]), "+f"(d[4]), "+f"(d[5]), "+f"(d[6]), "+f"(d[7]),
      "+f"(d[8]), "+f"(d[9]), "+f"(d[10]), "+f"(d[11]), "+f"(d[12]), "+f"(d[13]), "+f"(d[14]), "+f"(d[15]),
      "+f"(d[16]), "+f"(d[17]), "+f"(d[18]), "+f"(d[19]), "+f"(d[20]), "+f"(d[21]), "+f"(d[22]), "+f"(d[23]),
      "+f"(d[24]), "+f"(d[25]), "+f"(d[26]), "+f"(d[27]), "+f"(d[28]), "+f"(d[29]), "+f"(d[30]), "+f"(d[31]),
      "+f"(d[32]), "+f"(d[33]), "+f"(d[34]), "+f"(d[35]), "+f"(d[36]), "+f"(d[37]), "+f"(d[38]), "+f"(d[39]),
      "+f"(d[40]), "+f"(d[41]), "+f"(d[42]), "+f"(d[43]), "+f"(d[44]), "+f"(d[45]), "+f"(d[46]), "+f"(d[47]),
      "+f"(d[48]), "+f"(d[49]), "+f"(d[50]), "+f"(d[51]), "+f"(d[52]), "+f"(d[53]), "+f"(d[54]), "+f"(d[55]),
      "+f"(d[56]), "+f"(d[57]), "+f"(d[58]), "+f"(d[59]), "+f"(d[60]), "+f"(d[61]), "+f"(d[62]), "+f"(d[63]),
      "+f"(d[64]), "+f"(d[65]), "+f"(d[66]), "+f"(d[67]), "+f"(d[68]), "+f"(d[69]), "+f"(d[70]), "+f"(d[71]),
      "+f"(d[72]), "+f"(d[73]), "+f"(d[74]), "+f"(d[75]), "+f"(d[76]), "+f"(d[77]), "+f"(d[78]), "+f"(d[79]),
      "+f"(d[80]), "+f"(d[81]), "+f"(d[82]), "+f"(d[83]), "+f"(d[84]), "+f"(d[85]), "+f"(d[86]), "+f"(d[87]),
      "+f"(d[88]), "+f"(d[89]), "+f"(d[90]), "+f"(d[91]), "+f"(d[92]), "+f"(d[93]), "+f"(d[94]), "+f"(d[95]),
      "+f"(d[96]), "+f"(d[97]), "+f"(d[98]), "+f"(d[99]), "+f"(d[100]), "+f"(d[101]), "+f"(d[102]), "+f"(d[103]),
      "+f"(d[104]), "+f"(d[105]), "+f"(d[106]), "+f"(d[107]), "+f"(d[108]), "+f"(d[109]), "+f"(d[110]), "+f"(d[111]),
      "+f"(d[112]), "+f"(d[113]), "+f"(d[114]), "+f"(d[115]), "+f"(d[116]), "+f"(d[117]), "+f"(d[118]), "+f"(d[119]),
      "+f"(d[120]), "+f"(d[121]), "+f"(d[122]), "+f"(d[123]), "+f"(d[124]), "+f"(d[125]), "+f"(d[126]), "+f"(d[127])
    : "r"(a0), "r"(a1), "r"(a2), "r"(a3), "l"(db), "r"(sd));
}
__device__ __forceinline__ void wgmma_rs_n64_tb(float (&d)[32], uint32_t a0, uint32_t a1, uint32_t a2, uint32_t a3, uint64_t db, int sd) {
  asm volatile("{\n.reg .pred p;\nsetp.ne.b32 p, %37, 0;\n"
    "wgmma.mma_async.sync.aligned.m64n64k16.f32.bf16.bf16 "
    "{%0, %1, %2, %3, %4, %5, %6, %7, %8, %9, %10, %11, %12, %13, %14, %15, "
    "%16, %17, %18, %19, %20, %21, %22, %23, %24, %25, %26, %27, %28, %29, %30, %31}, "
    "{%32, %33, %34, %35}, %36, p, 1, 1, 1;\n}"
    : "+f"(d[0]), "+f"(d[1]), "+f"(d[2]), "+f"(d[3]), "+f"(d[4]), "+f"(d[5]), "+f"(d[6]), "+f"(d[7]),
      "+f"(d[8]), "+f"(d[9]), "+f"(d[10]), "+f"(d[11]), "+f"(d[12]), "+f"(d[13]), "+f"(d[14]), "+f"(d[15]),
      "+f"(d[16]), "+f"(d[17]), "+f"(d[18]), "+f"(d[19]), "+f"(d[20]), "+f"(d[21]), "+f"(d[22]), "+f"(d[23]),
      "+f"(d[24]), "+f"(d[25]), "+f"(d[26]), "+f"(d[27]), "+f"(d[28]), "+f"(d[29]), "+f"(d[30]), "+f"(d[31])
    : "r"(a0), "r"(a1), "r"(a2), "r"(a3), "l"(db), "r"(sd));
}
__device__ __forceinline__ void wgmma_rs_n64(float (&d)[32], uint32_t a0, uint32_t a1, uint32_t a2, uint32_t a3, uint64_t db, int sd) {
  asm volatile("{\n.reg .pred p;\nsetp.ne.b32 p, %37, 0;\n"
    "wgmma.mma_async.sync.aligned.m64n64k16.f32.bf16.bf16 "
    "{%0, %1, %2, %3, %4, %5, %6, %7, %8, %9, %10, %11, %12, %13, %14, %15, "
    "%16, %17, %18, %19, %20, %21, %22, %23, %24, %25, %26, %27, %28, %29, %30, %31}, "
    "{%32, %33, %34, %35}, %36, p, 1, 1, 0;\n}"
    : "+f"(d[0]), "+f"(d[1]), "+f"(d[2]), "+f"(d[3]), "+f"(d[4]), "+f"(d[5]), "+f"(d[6]), "+f"(d[7]),
      "+f"(d[8]), "+f"(d[9]), "+f"(d[10]), "+f"(d[11]), "+f"(d[12]), "+f"(d[13]), "+f"(d[14]), "+f"(d[15]),
      "+f"(d[16]), "+f"(d[17]), "+f"(d[18]), "+f"(d[19]), "+f"(d[20]), "+f"(d[21]), "+f"(d[22]), "+f"(d[23]),
      "+f"(d[24]), "+f"(d[25]), "+f"(d[26]), "+f"(d[27]), "+f"(d[28]), "+f"(d[29]), "+f"(d[30]), "+f"(d[31])
    : "r"(a0), "r"(a1), "r"(a2), "r"(a3), "l"(db), "r"(sd));
}

__device__ __forceinline__ uint4 lds16(uint32_t a) {
  uint4 v; asm volatile("ld.shared.v4.u32 {%0, %1, %2, %3}, [%4];" : "=r"(v.x), "=r"(v.y), "=r"(v.z), "=r"(v.w) : "r"(a) : "memory"); return v;
}
__device__ __forceinline__ void sts16(uint32_t a, uint32_t x, uint32_t y, uint32_t z, uint32_t w) {
  asm volatile("st.shared.v4.u32 [%0], {%1, %2, %3, %4};" :: "r"(a), "r"(x), "r"(y), "r"(z), "r"(w) : "memory");
}
__device__ __forceinline__ uint32_t lds4(uint32_t a) { uint32_t v; asm volatile("ld.shared.u32 %0, [%1];" : "=r"(v) : "r"(a) : "memory"); return v; }
__device__ __forceinline__ uint32_t lds4v(uint32_t a) { uint32_t v; asm volatile("ld.volatile.shared.u32 %0, [%1];" : "=r"(v) : "r"(a) : "memory"); return v; }
__device__ __forceinline__ uint32_t bmul(uint32_t a, uint32_t b) { uint32_t r; asm("mul.rn.bf16x2 %0, %1, %2;" : "=r"(r) : "r"(a), "r"(b)); return r; }
__device__ __forceinline__ uint32_t bfma(uint32_t a, uint32_t b, uint32_t c) { uint32_t r; asm("fma.rn.bf16x2 %0, %1, %2, %3;" : "=r"(r) : "r"(a), "r"(b), "r"(c)); return r; }
__device__ __forceinline__ uint32_t badd(uint32_t a, uint32_t b) { uint32_t r; asm("add.rn.bf16x2 %0, %1, %2;" : "=r"(r) : "r"(a), "r"(b)); return r; }

#define FUSED 0
__device__ __forceinline__ uint32_t add_skip(uint32_t y, uint32_t x, uint32_t d) { return (FUSED & 2) ? bfma(x, d, y) : badd(y, bmul(x, d)); }
__device__ __forceinline__ void ldsm4(uint32_t (&r)[4], uint32_t a) {
  asm volatile("ldmatrix.sync.aligned.m8n8.x4.shared.b16 {%0, %1, %2, %3}, [%4];" : "=r"(r[0]), "=r"(r[1]), "=r"(r[2]), "=r"(r[3]) : "r"(a) : "memory");
}
__device__ __forceinline__ void ldsm4t(uint32_t (&r)[4], uint32_t a) {
  asm volatile("ldmatrix.sync.aligned.m8n8.x4.trans.shared.b16 {%0, %1, %2, %3}, [%4];" : "=r"(r[0]), "=r"(r[1]), "=r"(r[2]), "=r"(r[3]) : "r"(a) : "memory");
}
__device__ __forceinline__ uint32_t transpose8(uint32_t a) { uint32_t d; asm volatile("movmatrix.sync.aligned.m8n8.trans.b16 %0, %1;" : "=r"(d) : "r"(a)); return d; }

__device__ __forceinline__ void mma16816(float (&d)[4], const uint32_t (&a)[4], uint32_t b0, uint32_t b1) {
  asm volatile("mma.sync.aligned.m16n8k16.row.col.f32.bf16.bf16.f32 {%0, %1, %2, %3}, {%4, %5, %6, %7}, {%8, %9}, {%0, %1, %2, %3};"
               : "+f"(d[0]), "+f"(d[1]), "+f"(d[2]), "+f"(d[3]) : "r"(a[0]), "r"(a[1]), "r"(a[2]), "r"(a[3]), "r"(b0), "r"(b1));
}

#define STG_K1 2
#define STG_K2 10
#define STG_Q1 1
#define STG_Q2 5
#define PACE_A 400
#define PACE_B 100
#define PF_QA 48
#define PF_CV 64
#define PF_X 8
#define PF_WO 11
#define Q_PRE 2
#define CV_SER -1
#define CV_QX 0
#define CV_FX 1
#define TAIL_WAIT 0
#define NOCV 0
#define CV_MOV 1
#define ARRIVE_KK 12
#define SIDE_DELAY_NS 4000
#define HEAD_MAP 2
#define EARLY_LD 2
#define HI_ORDER 9
constexpr int CV_BAR = 5;
constexpr int PP_BAR = 3;
template <int V> struct Int { static constexpr int value = V; };
struct Ring {
  uint32_t slot, phase;
  __device__ __forceinline__ void next() { if (++slot == NSLOT) { slot = 0; phase ^= 1; } }
};
__device__ __forceinline__ uint32_t bar_addr(uint32_t sb, uint32_t i) { return sb + BARS + 8 * i; }
__device__ __forceinline__ uint32_t q_region(uint32_t sb, int w) { return sb + QREG + (w ^ 1) * 32768; }

struct Role { int h, j; };
__device__ __forceinline__ Role get_role() {
  int cta; asm volatile("mov.u32 %0, %%ctaid.x;" : "=r"(cta));
  const int c = cta >> 1;
  int h, u;
  const int a = c - 4, b = c - 36, q = (b * 37) >> 8;
  h = a < 0 ? (HEAD_MAP == 2 ? 8 : 15) : b < 0 ? a & 7 : (HEAD_MAP == 2 ? 9 : 8) + b - 7 * q;
  u = a < 0 ? c : b < 0 ? a >> 3 : q;
  return Role{h, 2 * u + (cta & 1)};
}
__device__ __forceinline__ int fresh_warp() { return __shfl_sync(0xffffffffu, fresh_tid() >> 5, 0); }

__device__ __forceinline__ int q_tile(int h, int j, int which) { return ((h < 8) == (which == 0)) ? 15 - j : j; }

__device__ __forceinline__ int o_chunk(int h, int c) { const int x = c + (h & 7); return x % 7; }

__device__ __forceinline__ int kv_block(int j, int t) { return j + 8 * ((HI_ORDER >> t) & 1); }
__device__ __forceinline__ uint8_t* kv_tile(const Params& p, int v, int h, int tile) {
  return p.kv + (size_t)((v * NH + h) * 32 + tile) * 32768;
}

__device__ __forceinline__ void ring_acquire(uint32_t sb, Ring& r, uint32_t bytes) {
  mbar_wait(bar_addr(sb, B_RG_EMPTY + r.slot), r.phase ^ 1);
  mbar_expect_tx(bar_addr(sb, B_RG_FULL + r.slot), bytes);
}
__device__ __forceinline__ void producer_main(const Params& p, uint32_t sb) {
  const Role ro = get_role();
  const int h = ro.h, j = ro.j;
  TR_DECL;
  CP_DECL;
  ST(11);
  for (int it = EARLY_LD; it < 71; it++) {
    const int t = it >> 4, k = it & 15, s = it & 3;
    mbar_wait(bar_addr(sb, B_P1_EMPTY + s), ((it >> 2) & 1) ^ 1);
    const uint32_t full = bar_addr(sb, B_P1_FULL + s), dst = sb + s * P1_STAGE;
    mbar_expect_tx(full, P1_STAGE);
    if ((it & 7) == 4) TRG(it);
    if (t < 4) {
      tma_ld2(dst, &p.ckv, full, k * 64, kv_block(j, t) * 128);
      tma_ld3(dst + 16384, (t >> 1) ? &p.wuv : &p.wuk, full, 0, k * 64, h * 4);
    } else {
      tma_ld2(dst, &p.x, full, k * 64, q_tile(h, j, 0) * 128);
      tma_ld3(dst + 16384, &p.wq, full, 0, k * 64, h * 4);
    }
    CP();
    if (it >= PF_QA && it < PF_QA + 14) {
      const int i = it - PF_QA;
      bulk_prefetch(p.b_x + (size_t)(q_tile(h, j, 0) * 128 + (h & 7) * 16) * DM + i * 512, 1024);
      tma_pf2(&p.wqp, h * HD, (i * 8 + j) * 4);
    }
    if (it >= PF_CV && it < PF_CV + 3) {
      mbar_wait(bar_addr(sb, B_XS), 0);
      bulk_prefetch(g_xs + (size_t)(h * 8 + j) * CV_BYTES + (it - PF_CV) * (CV_BYTES / 3), CV_BYTES / 3);
    }
  }
  mbar_wait(bar_addr(sb, B_P1_EMPTY + 3), 0);
  mbar_wait(bar_addr(sb, B_XS), 0);
  mbar_expect_tx(bar_addr(sb, B_RG_FULL + 4), CV_BYTES);
  bulk_ld(sb + CV_X, g_xs + (size_t)(h * 8 + j) * CV_BYTES, CV_BYTES, bar_addr(sb, B_RG_FULL + 4));
  Ring r{0, 1};
  auto prefetch_wo = [&](int left) {
    const int i = PF_WO - left;
    if (PF_WO && i >= 0 && i < 8) bulk_prefetch(p.b_wo + (size_t)(h * HD + j * 32 + 4 * i) * DM, 4 * DM * 2);
  };
  mbar_wait(bar_addr(sb, B_KV), 0);
  for (int which = 0; which < 2; which++) {
    const int qt = q_tile(h, j, which);
    if (which == 1) {
      for (int kc = 0; kc < 7; kc++) {
        prefetch_wo(4 * qt + 4 + 7 - kc);
        ring_acquire(sb, r, 32768);
        tma_ld3(sb + r.slot * SLOT, &p.wq, bar_addr(sb, B_RG_FULL + r.slot), 0, kc * 64, h * 4);
        r.next();
        if (kc == 0 || (kc & 1)) {
          ring_acquire(sb, r, kc == 0 ? 16384 : 32768);
          const uint32_t full = bar_addr(sb, B_RG_FULL + r.slot), dst = sb + r.slot * SLOT;
          tma_ld2(dst, &p.x, full, kc * 64, qt * 128);
          if (kc > 0) tma_ld2(dst + 16384, &p.x, full, kc * 64 + 64, qt * 128);
          r.next();
        }
      }
    }
    const int n = 2 * qt + 2;
    for (int f = 0; f < 2 * n; f++) {
      if (which == 0) {
        const int i = f - max(2 * n - PF_X, 0);
        if (PF_X && i >= 0 && i < 4) bulk_prefetch(p.b_x + (size_t)((15 - qt) * 128 + (h & 7) * 16 + 4 * i) * DM, 4 * DM * 2);
      } else prefetch_wo(2 * n - f);
      const bool isK = (f == 0) || ((f & 1) && f < 2 * n - 1);
      const int i = isK ? (f + 1) >> 1 : (f == 2 * n - 1 ? n - 1 : (f >> 1) - 1);
      const int tile = which ? n - 1 - i : i;
      if (!isK) mbar_wait(bar_addr(sb, B_KV + 1 + ((tile >> 4) ^ ((HI_ORDER >> 2) & 1))), 0);
      if (which == 0 && f < 2) mbar_wait(bar_addr(sb, B_P1_EMPTY + f), 1);
      ring_acquire(sb, r, 32768);
      if (isK && (tile & 3) == 0) TRG(100 + 50 * which + tile);
      bulk_ld(sb + r.slot * SLOT, kv_tile(p, !isK, h, tile), 32768, bar_addr(sb, B_RG_FULL + r.slot));
      r.next();
      CP();
    }
  }
  for (int i = 0; i < 14; i++) {
    ring_acquire(sb, r, 32768);
    if ((i & 3) == 0) TRG(200 + i);
    if (i == 13) TR_END();
    tma_ld2(sb + r.slot * SLOT, &p.wo, bar_addr(sb, B_RG_FULL + r.slot), o_chunk(h, i >> 1) * 64, ((i & 1) ? h ^ 8 : h) * HD);
    r.next();
    CP();
  }
}

__device__ __forceinline__ void storer_main(const Params& p, uint32_t sb) {
  const Role ro = get_role();
  const int h = ro.h, j = ro.j, w = fresh_warp() - 1;
  const uint32_t full = bar_addr(sb, B_ST_FULL + w), empty = bar_addr(sb, B_ST_EMPTY + w);
  const int lane = threadIdx.x & 31;
  const unsigned epoch = load_epoch();
  if (lane == 0) {
    for (int job = 0; job < 8; job++) {
      const int t = job >> 1;
      uint8_t* dst = kv_tile(p, t >> 1, h, 2 * kv_block(j, t) + w) + (job & 1) * 16384;
      mbar_wait_nap(full, job & 1);
      for (int i = 0; i < 8; i++) {
        if (i) __nanosleep(job < 6 ? PACE_A : PACE_B);
        bulk_st(dst + i * 2048, sb + P1_STG + w * 16384 + i * 2048, 2048);
      }
      bulk_commit();
      bulk_wait_read();
      mbar_arrive(empty);
      if (job >= 3 && (job & 1)) { bulk_wait_all(); flag_signal(&g_flags.kv_ready[3 * h + t - 1].v); }
    }
  }
  __syncwarp();
  const int cta = h * 8 + j, qt = q_tile(h, j, 1);
  const uint32_t qreg = q_region(sb, w);
  {
    mbar_wait_nap(bar_addr(sb, B_CTXS + 4 * w), 0);
    uint4* z = reinterpret_cast<uint4*>(p.out + (size_t)(qt * 128 + w * 64 + (h & 7) * 8 + (lane >> 2)) * OUTW + DA) + (lane & 3);
#pragma unroll
    for (int i = 0; i < 14; i++) z[4 * i] = make_uint4(0, 0, 0, 0);
    __syncwarp();
    if (lane != 0) return;
    for (int b = 0; b < 4; b++) {
      mbar_wait(bar_addr(sb, B_CTXS + 4 * w + b), 0);
      bulk_st(p.ctx + (size_t)(cta * 2 + w) * 32768 + b * 8192, qreg + b * 8192, 8192);
      bulk_commit();
    }
    bulk_wait_read();
    mbar_arrive(empty);
    bulk_wait_all();
    flag_signal(&g_flags.ctx_ready[cta * 2 + w].v);
    flag_signal_after_bulk(&g_flags.out_ready[qt * 2 + w].v);
  }
  {
    const int wx = w ^ 1;
    flag_wait(&g_flags.ctx_ready[(cta ^ 64) * 2 + wx].v, 1, epoch);
    flag_wait(&g_flags.out_ready[qt * 2 + wx].v, 8, epoch);
    fence_async_all();
    mbar_wait_nap(bar_addr(sb, B_QFREE + w), 0);
    mbar_expect_tx(bar_addr(sb, B_CTXF + w), 32768);
    bulk_ld(qreg, p.ctx + (size_t)((cta ^ 64) * 2 + wx) * 32768, 32768, bar_addr(sb, B_CTXF + w));
    for (int ch = 0; ch < 7; ch++) {
      const int b = ch & 1;
      mbar_wait(bar_addr(sb, B_S2_FULL + w * 2 + b), (ch >> 1) & 1);
      tma_red2(&p.part, qreg + b * 8192, DA + o_chunk(h, ch) * 64, qt * 128 + wx * 64);
      bulk_commit();
      if (ch == 0 && w == 1) mbar_arrive(bar_addr(sb, B_GFREE));
      bulk_wait_read();
      mbar_arrive(bar_addr(sb, B_S2_EMPTY + w * 2 + b));
    }
    GT(48 + w);
    if (TAIL_WAIT) bulk_wait_all();
    GT(50 + w); GT(52 + w); GT(56);
    if (w == 0) { ST(12); STG_(13); }
  }
}

template <int OFF, int NB, int NREG>
__device__ __forceinline__ void store_blocks(uint32_t base, uint32_t lanebase, const uint32_t (&pk)[NREG]) {
#pragma unroll
  for (int J = 0; J < NB * 8; J += 2) {
    const uint32_t a = base + (J >> 3) * 8192 + (lanebase ^ ((J & 7) << 4));
    stsm4(a, pk[OFF + 2 * J], pk[OFF + 2 * J + 1], pk[OFF + 2 * J + 2], pk[OFF + 2 * J + 3]);
  }
}
__device__ __forceinline__ void warp_arrive(uint32_t bar, int lane) { __syncwarp(); if (lane == 0) mbar_arrive(bar); }
__device__ __forceinline__ void release(uint32_t bar, int lane) { lane0_arrive(bar, 1, lane); }

template <int W> __device__ __forceinline__ constexpr int cv_tile(int u) { return 2 * u + ((u ^ W) & 1); }
__device__ __forceinline__ uint32_t cv_x_lane(uint32_t lane) { return (16 + (lane & 15) - (lane >> 4)) * 16; }
__device__ __forceinline__ uint32_t cv_h_lane(uint32_t lane, uint32_t hE, uint32_t hO) {
  const uint32_t g = lane >> 2, c = lane & 3;
  return (g & 1) ? hO + (15 + 2 * c - g) * 2 : hE + (16 + 2 * c - g) * 2;
}
template <int W>
__device__ __forceinline__ void conv_mma(float (&ca)[8][4], uint32_t xa, uint32_t ha, uint32_t sb, uint32_t lb, const uint32_t (&pk)[64], uint32_t one) {
  constexpr int N = 16 - W;
  uint32_t fx[N][4], fh[N][2];
  auto ld_h = [&](int i, int rr) { fh[i][0] = lds4(ha + i * 256 + rr * (CV_MOV ? 128 : 32)); fh[i][1] = lds4(ha + i * 256 + rr * (CV_MOV ? 128 : 32) + 16); };
  uint32_t c1 = 0, c3 = 0;
  if (CV_SER >= 0 && W == 0) named_sync(CV_BAR, 256);
  ldsm4(fx[0], xa);
#pragma unroll
  for (int u = 0; u < 8; u++) ld_h(cv_tile<W>(u), 0);
  ldsm4(fx[1], xa + 256);
#pragma unroll
  for (int u = 0; u < 8; u++) if (cv_tile<W ^ 1>(u) < N) ld_h(cv_tile<W ^ 1>(u), 0);
#pragma unroll
  for (int i = 2; i < N; i++) ldsm4(fx[i], xa + i * 256);
#pragma unroll
  for (int sx = 0; sx < N; sx++) {
#pragma unroll
    for (int u = 0; u < 8; u++) {
      const int jj = cv_tile<W>(u) - sx;
      if (jj >= 0) mma16816(ca[u], fx[sx], fh[jj < 0 ? 0 : jj][0], fh[jj < 0 ? 0 : jj][1]);
    }
    if (CV_MOV) {
      const uint32_t t1 = fx[sx][1], t3 = fx[sx][3];
      fx[sx][1] = fx[sx][0] * one; fx[sx][3] = fx[sx][2] ^ (one - 1); fx[sx][0] = c1 * one; fx[sx][2] = c3 ^ (one - 1);
      c1 = t1; c3 = t3;
    } else ldsm4(fx[sx], xa + sx * 256 - 32);
    ld_h(N - 1 - sx, 1);
    if (W == 1 && sx == CV_SER) named_arrive(CV_BAR, 256);
  }
  mbar_wait(bar_addr(sb, B_P1_EMPTY + 2), 1);
  if (W == 0) { mbar_wait(bar_addr(sb, B_ST_EMPTY), 1); mbar_wait(bar_addr(sb, B_ST_EMPTY + 1), 1); }
#pragma unroll
  for (int jj = 15; jj >= 0; jj--) {
    if (W == 0 || CV_QX) stsm4(q_region(sb, W) + (jj >> 2) * 8192 + (lb ^ ((jj & 3) << 5)), pk[4 * jj], pk[4 * jj + 1], pk[4 * jj + 2], pk[4 * jj + 3]);
#pragma unroll
    for (int u = 0; u < 8; u++) {
      const int sx = cv_tile<W>(u) - jj;
      if (sx >= 0) mma16816(ca[u], fx[sx < 0 ? 0 : sx], fh[jj < N ? jj : 0][0], fh[jj < N ? jj : 0][1]);
    }
  }
}

__device__ __forceinline__ void consumer_main(const Params& p, uint32_t sb, uint8_t* xs_base, uint32_t one) {
  const int lane = fresh_tid() & 31, w = (fresh_warp() >> 2) - 1;
  const uint32_t lb = lane_base16();
  int qt, cc;
  { const Role ro = get_role(); qt = q_tile(ro.h, ro.j, 0); cc = ro.h * 8 + ro.j; }
  const uint32_t st_full = bar_addr(sb, B_ST_FULL + w), st_empty = bar_addr(sb, B_ST_EMPTY + w);
  const uint32_t stg = sb + P1_STG + w * 16384;

  auto turn_begin = [&]() { named_sync(PP_BAR + w, 256); };
  auto turn_end = [&]() { named_arrive(PP_BAR + (w ^ 1), 256); };
  float acc[128];
#pragma unroll
  for (int i = 0; i < 128; i++) acc[i] = 0.f;
  uint32_t pk[64];
#pragma unroll
  for (int i = 0; i < 64; i++) pk[i] = 0;
  if (fresh_warp() != 4) named_sync(0, NTHREADS);
  PDECL;
  TR_DECL;
  TR(0);
  TSG(0); TS(1);
  const uint32_t qreg = q_region(sb, w);
  for (int t = 0; t < 5; t++) {
    const int nk = t < 4 ? 16 : 7;
#pragma unroll 1
    for (int k = 0; k < nk; k++) {
      const int it = t * 16 + k, s = k & 3;
      if (it == 0) { mbar_wait(bar_addr(sb, B_P1_FULL), 0); turn_begin(); }
      TR(1);
      const uint64_t da = desc_k(sb + s * P1_STAGE + w * 8192), db = desc_mn(sb + s * P1_STAGE + 16384);
      wg_fence();
#pragma unroll
      for (int kk = 0; kk < 4; kk++) wgmma_ss_n256_tb(acc, desc_add(da, kk * 32), desc_add(db, kk * 2048), (k | kk) != 0);
      wg_commit();
      turn_end();
      TR(3);
      wg_wait<1>();
      if (k > 0) release(bar_addr(sb, B_P1_EMPTY + ((k - 1) & 3)), lane);
      const int k1 = t < 4 ? STG_K1 : STG_Q1, k2 = t < 4 ? STG_K2 : STG_Q2;
      if (t > 0 && (k == k1 || k == k2)) {
        const int job = 2 * (t - 1) + (k != k1);
        if (job > 0) mbar_wait(st_empty, (job - 1) & 1);
        if (k == k1) store_blocks<0, 2>(stg, lb, pk); else store_blocks<32, 2>(stg, lb, pk);
      }
      if (t > 0 && (k == k1 + 1 || k == k2 + 1)) { fence_async_smem(); warp_arrive(st_full, lane); }
      TR(5);
      if (it < 70) { mbar_wait(bar_addr(sb, B_P1_FULL + ((k + 1) & 3)), ((it + 1) >> 2) & 1); turn_begin(); }
      else mbar_wait(bar_addr(sb, B_RG_FULL + 4), 0);
    }
    wg_wait<0>();
    TR(6);
    reg_fence(acc);
    release(bar_addr(sb, B_P1_EMPTY + ((nk - 1) & 3)), lane);
#pragma unroll
    for (int i = 0; i < 64; i++) pk[i] = pack_bf16(acc[2 * i], acc[2 * i + 1]);
    TS(t < 4 ? 2 + t : 60);
  }
  TS(6);
  {
    const uint32_t wq = lb >> 11, ln = lane, cx = sb + CV_X;
    float ca[8][4];
#pragma unroll
    for (int i = 0; i < 8; i++) { ca[i][0] = 0.f; ca[i][1] = 0.f; ca[i][2] = 0.f; ca[i][3] = 0.f; }
    const uint32_t xa = cx + cv_x_lane(ln) - wq * (CV_MOV ? 32 : 64), ha = cv_h_lane(ln, cx + CV_HE, cx + CV_HE + CV_HCOPY) + wq * (CV_MOV ? 32 : 64);
    TR(7); TS(19); TS(20);
    if (w) conv_mma<1>(ca, xa, ha, sb, lb, pk, one); else conv_mma<0>(ca, xa, ha, sb, lb, pk, one);
    TR(8); TS(21);
    const uint32_t ex = sb + CV_R + w * 16384 + ln * 16;
#pragma unroll
    for (int u = 0; u < (NOCV ? 0 : 8); u++)
      sts16(ex + (wq * 8 + u) * 512, __float_as_uint(ca[u][0]), __float_as_uint(ca[u][1]), __float_as_uint(ca[u][2]), __float_as_uint(ca[u][3]));
  }
  auto conv_finish = [&]() {
    const uint32_t wq = lb >> 11, cx = sb + CV_X, ex = sb + CV_R + w * 16384 + lane * 16;
    uint8_t* gz = xs_base + (size_t)cc * CV_BYTES;
    const uint32_t Dd = lds4(cx + CV_D);
    uint32_t z[2][2];
#pragma unroll
    for (int e = 0; e < (NOCV ? 0 : 2); e++) {
      const uint32_t u = 2 * wq + e, nt = 2 * u + ((e ^ w) & 1);
      float y[4] = {0.f, 0.f, 0.f, 0.f};
#pragma unroll
      for (int v = 0; v < 4; v++) {
        const uint4 t = lds16(ex + (v * 8 + u) * 512);
        y[0] += __uint_as_float(t.x); y[1] += __uint_as_float(t.y); y[2] += __uint_as_float(t.z); y[3] += __uint_as_float(t.w);
      }
      const uint32_t o = (16 + 16 * nt) * 16 + lane * 4;
      *reinterpret_cast<uint32_t*>(gz + o)       = badd(pack_bf16(y[0], y[1]), bmul(lds4(cx + o), Dd));
      *reinterpret_cast<uint32_t*>(gz + o + 128) = badd(pack_bf16(y[2], y[3]), bmul(lds4(cx + o + 128), Dd));
    }
    __syncwarp();
    release(bar_addr(sb, B_RG_EMPTY + 3), lane);
    release(bar_addr(sb, B_RG_EMPTY + 4), lane);
    if (lane == 0) mbar_arrive(bar_addr(sb, B_CONV));
  };
  TS(15);
  TR(10);
  Ring r{0, 1};
  auto take = [&]() { const uint32_t sl = r.slot; mbar_wait(bar_addr(sb, B_RG_FULL + sl), r.phase); r.next(); return sl; };
  constexpr float SC = 0.0625f * 1.4426950408889634f;
  uint32_t ws;
#pragma unroll 1
  for (int which = 0;; which++) {
    float s[32];
#pragma unroll
    for (int i = 0; i < 32; i++) s[i] = 0.f;
    uint32_t pa[16];
    float b0, b1, l0, l1;
    const uint64_t dq = desc_k(qreg);
    uint64_t dk = 0, dqq = 0, dv = 0;
    auto prep_qk = [&](uint32_t kaddr) { dk = desc_k(kaddr); dqq = dq + (kaddr >> 31); asm volatile("" : "+l"(dk), "+l"(dqq)); };
    auto prep_pv = [&](uint32_t vaddr) { dv = desc_mn(vaddr); asm volatile("" : "+l"(dv)); };
    auto issue_qk = [&]() {
#pragma unroll
      for (int kk = 0; kk < 16; kk++)
        wgmma_ss_n64(s, desc_add(dqq, (kk >> 2) * 8192 + (kk & 3) * 32), desc_add(dk, (kk >> 2) * 8192 + (kk & 3) * 32), kk != 0);
    };
    auto issue_pv = [&](int accumulate) {
#pragma unroll
      for (int kk = 0; kk < 4; kk++)
        wgmma_rs_n256_tb(acc, pa[4 * kk], pa[4 * kk + 1], pa[4 * kk + 2], pa[4 * kk + 3], desc_add(dv, kk * 2048), accumulate | kk);
    };
    auto mask_diag = [&]() {
      const int d = (int)((lb >> 11) << 4) + (lane >> 2) - 2 * (lane & 3);
#pragma unroll
      for (int jj = 0; jj < 8; jj++) {
        if (8 * jj > d)     s[4 * jj]     = -INFINITY;
        if (8 * jj + 1 > d) s[4 * jj + 1] = -INFINITY;
        if (8 * jj - 8 > d) s[4 * jj + 2] = -INFINITY;
        if (8 * jj - 7 > d) s[4 * jj + 3] = -INFINITY;
      }
    };
    auto row_max = [&](float& x0, float& x1) {
      x0 = fmaxf(s[0], s[1]); x1 = fmaxf(s[2], s[3]);
#pragma unroll
      for (int jj = 1; jj < 8; jj++) {
        x0 = fmaxf(x0, fmaxf(s[4 * jj], s[4 * jj + 1]));
        x1 = fmaxf(x1, fmaxf(s[4 * jj + 2], s[4 * jj + 3]));
      }
      x0 = fmaxf(x0, __shfl_xor_sync(0xffffffffu, x0, 1));
      x1 = fmaxf(x1, __shfl_xor_sync(0xffffffffu, x1, 1));
      x0 = fmaxf(x0, __shfl_xor_sync(0xffffffffu, x0, 2));
      x1 = fmaxf(x1, __shfl_xor_sync(0xffffffffu, x1, 2));
    };
    auto exps = [&](uint32_t (&pp)[16], float& r0, float& r1) {
      float t0, t1, t2, t3;
#pragma unroll
      for (int jj = 0; jj < 8; jj++) {
        const float e0 = ex2(fmaf(s[4 * jj], SC, b0)), e1 = ex2(fmaf(s[4 * jj + 1], SC, b0));
        const float e2 = ex2(fmaf(s[4 * jj + 2], SC, b1)), e3 = ex2(fmaf(s[4 * jj + 3], SC, b1));
        if (jj == 0) { t0 = e0; t1 = e1; t2 = e2; t3 = e3; } else { t0 += e0; t1 += e1; t2 += e2; t3 += e3; }
        pp[2 * jj] = pack_bf16(e0, e1); pp[2 * jj + 1] = pack_bf16(e2, e3);
      }
      r0 = t0 + t1; r1 = t2 + t3;
    };

    const bool up = w == which;
    const int n = 2 * qt + 2, nw = n - up;
    int fd = which ? 0 : 2 * n - 1;
    const int dir = which ? 1 : -1;
    auto skip = [&]() { r.next(); fd += dir; };
    auto give = [&](uint32_t sl, int d) {
      lane0_arrive(bar_addr(sb, B_RG_EMPTY + sl), (d & ~2) == 0 ? 2 : 1, lane);
    };
    if (which && up) skip();
    uint32_t ks = take();
    TS(62 + which);
    TR(20);
    prep_qk(sb + ks * SLOT);
    turn_begin();
    wg_fence();
#pragma unroll
    for (int kk = 0; kk < 16; kk++)
      wgmma_rs_n64(s, pk[4 * kk], pk[4 * kk + 1], pk[4 * kk + 2], pk[4 * kk + 3], desc_add(dk, (kk >> 2) * 8192 + (kk & 3) * 32), kk != 0);
    wg_commit();
    turn_end();
    TR(21);
    if (!which && (up || !CV_FX)) conv_finish();
    TR(23);
    if (which) mbar_wait(st_empty, 0);
    if ((which || !CV_QX) && !up) store_blocks<0, Q_PRE>(qreg, lb, pk);
    TR(24);
    wg_wait<0>();
    TR(22);
    reg_fence(s);
    reg_fence(pk);
    give(ks, fd);
    fd += dir;
    if (NOCV && !which && up) { mbar_wait(st_empty, 1); mbar_wait(bar_addr(sb, B_ST_EMPTY + 1), 1); }
    if (which && up) skip();
    if ((which || NOCV) && up) store_blocks<0, 4>(qreg, lb, pk);
    if (which || nw == 1) mask_diag();
    row_max(b0, b1);
    if ((which || !CV_QX) && !up) store_blocks<16 * Q_PRE, 4 - Q_PRE>(qreg + Q_PRE * 8192, lb, pk);
    b0 *= -SC; b1 *= -SC;
#pragma unroll
    for (int i = 0; i < 128; i++) acc[i] = 0.f;
    exps(pa, l0, l1);
    if (CV_FX && !which && !up) conv_finish();
    if (which && nw == 1) { fence_async_smem(); warp_arrive(bar_addr(sb, B_QFREE + w), lane); }
#pragma unroll 1
    for (int jj = 1; jj < nw; jj++) {
      ks = take();
      const uint32_t vs = take();
      if (jj == 1) fence_async_smem();
      TR(30);
#pragma unroll
      for (int i = 0; i < 32; i++) s[i] = 0.f;
      prep_qk(sb + ks * SLOT);
      prep_pv(sb + vs * SLOT);
      turn_begin();
      wg_fence();
      issue_qk();
      wg_commit();
      issue_pv(1);
      wg_commit();
      turn_end();
      TR(31);
      wg_wait<1>();
      TR(32);
      reg_fence(s);
      give(ks, fd);
      if (jj == nw - 1) {
        if (!which) mask_diag();
        else if (lane == 0) mbar_arrive(bar_addr(sb, B_QFREE + w));
      }
      uint32_t pn[16];
      float t0, t1, a0 = 1.f, a1 = 1.f;
      exps(pn, t0, t1);
      const bool redo = __any_sync(0xffffffffu, !(t0 + t1 <= 65536.f));
      if (redo) {
        row_max(a0, a1);
        const float c0 = fminf(b0, -SC * a0), c1 = fminf(b1, -SC * a1);
        a0 = ex2(c0 - b0); a1 = ex2(c1 - b1);
        b0 = c0; b1 = c1;
        l0 *= a0; l1 *= a1;
        exps(pn, t0, t1);
      }
      l0 += t0; l1 += t1;
      wg_wait<0>();
      reg_fence(acc);
      reg_fence(pa);
      give(vs, fd + dir);
      fd += 2 * dir;
      if (redo) {
#pragma unroll
        for (int i = 0; i < 32; i++) { acc[4 * i] *= a0; acc[4 * i + 1] *= a0; acc[4 * i + 2] *= a1; acc[4 * i + 3] *= a1; }
      }
#pragma unroll
      for (int i = 0; i < 16; i++) pa[i] = (i & 1) ? pn[i] ^ (one - 1) : pn[i] * one;
    }
    if (!which && up) skip();
    const uint32_t vs = take();
    TR(40);
    prep_pv(sb + vs * SLOT);
    turn_begin();
    wg_fence();
    issue_pv(1);
    wg_commit();
    turn_end();
    TR(41);
    if (!which && up) r.next();
    ws = take();
    l0 += __shfl_xor_sync(0xffffffffu, l0, 1); l1 += __shfl_xor_sync(0xffffffffu, l1, 1);
    l0 += __shfl_xor_sync(0xffffffffu, l0, 2); l1 += __shfl_xor_sync(0xffffffffu, l1, 2);
    float i0, i1;
    asm volatile("rcp.approx.ftz.f32 %0, %1;" : "=f"(i0) : "f"(l0));
    asm volatile("rcp.approx.ftz.f32 %0, %1;" : "=f"(i1) : "f"(l1));
    uint32_t xs = 0;
    if (!which) xs = take();
    wg_wait<0>();
    TR(42);
    reg_fence(acc);
    reg_fence(pa);
    give(vs, fd);
    TS(7 + 3 * which);
#pragma unroll
    for (int i = 0; i < 32; i++) {
      pk[2 * i]     = pack_bf16(acc[4 * i] * i0, acc[4 * i + 1] * i0);
      pk[2 * i + 1] = pack_bf16(acc[4 * i + 2] * i1, acc[4 * i + 3] * i1);
    }
    TS(8 + 3 * which); TR(46);
    if (which) break;
    TS(31);
    uint32_t xaddr = sb + xs * SLOT + (w ^ 1) * 8192;
#pragma unroll 1
    for (int kc = 0;; kc++) {
      TR(11);
      const uint64_t da = desc_k(xaddr), db = desc_mn(sb + ws * SLOT);
      turn_begin();
      wg_fence();
#pragma unroll
      for (int kk = 0; kk < 4; kk++) wgmma_ss_n256_tb(acc, desc_add(da, kk * 32), desc_add(db, kk * 2048), (kc | kk) != 0);
      wg_commit();
      turn_end();
      TR(13);
      const int cb = kc;
      if (cb >= 1 && cb <= 4) { fence_async_smem(); warp_arrive(bar_addr(sb, B_CTXS + 4 * w + cb - 1), lane); }
      if ((unsigned)cb < 4) {
        if (cb & 2) { if (cb & 1) store_blocks<48, 1>(qreg + 24576, lb, pk); else store_blocks<32, 1>(qreg + 16384, lb, pk); }
        else        { if (cb & 1) store_blocks<16, 1>(qreg + 8192, lb, pk);  else store_blocks<0, 1>(qreg, lb, pk); }
      }
      TR(15);
      wg_wait<0>();
      release(bar_addr(sb, B_RG_EMPTY + ws), lane);
      if (!(kc & 1)) release(bar_addr(sb, B_RG_EMPTY + xs), lane);
      if (kc == 6) break;
      ws = take();
      if (!(kc & 1)) { xs = take(); xaddr = sb + xs * SLOT + (w ^ 1) * 8192; } else xaddr += 16384;
    }
    reg_fence(acc);
    TS(61); TR(16);
#pragma unroll
    for (int i = 0; i < 64; i++) pk[i] = pack_bf16(acc[2 * i], acc[2 * i + 1]);
    TS(9); TR(19);
    qt = 15 - qt;
  }

  {
    float oa[32], ob[32];
#pragma unroll
    for (int i = 0; i < 32; i++) { oa[i] = 0.f; ob[i] = 0.f; }
    auto stage_o = [&](float (&o)[32], int ch) {
      reg_fence(o);
      uint32_t q[16];
#pragma unroll
      for (int i = 0; i < 16; i++) q[i] = pack_bf16(o[2 * i], o[2 * i + 1]);
      if (ch >= 2) mbar_wait(bar_addr(sb, B_S2_EMPTY + w * 2 + (ch & 1)), ((ch >> 1) - 1) & 1);
      store_blocks<0, 1>(qreg + (ch & 1) * 8192, lb, q);
    };
    auto hand_over = [&](int ch) {
      fence_async_smem();
      warp_arrive(bar_addr(sb, B_S2_FULL + w * 2 + (ch & 1)), lane);
    };
    uint32_t pk2[64];
    uint32_t p2 = 0;
    auto chunk = [&](int ch, auto first, float (&o)[32], float (&oprev)[32]) {
      constexpr bool FIRST = decltype(first)::value;
      const uint32_t s1 = FIRST ? ws : take();
      TR(50);
      const uint64_t d1 = desc_mn(sb + s1 * SLOT);
      turn_begin();
      wg_fence();
#pragma unroll
      for (int kk = 0; kk < 16; kk++) {
        wgmma_rs_n64_tb(o, pk[4 * kk], pk[4 * kk + 1], pk[4 * kk + 2], pk[4 * kk + 3], desc_add(d1, kk * 2048), kk != 0);
        if (kk == ARRIVE_KK) turn_end();
      }
      wg_commit();
      TR(51);
      if constexpr (!FIRST) {
        wg_wait<1>();
        release(bar_addr(sb, B_RG_EMPTY + p2), lane);
        stage_o(oprev, ch - 1);
      } else {
        mbar_wait(bar_addr(sb, B_CTXF + w), 0);
#pragma unroll
        for (int kk = 0; kk < 16; kk++) {
          uint32_t f[4];
          ldsm4(f, qreg + (kk >> 2) * 8192 + (lb ^ ((kk & 3) << 5)));
          pk2[4 * kk] = f[0]; pk2[4 * kk + 1] = f[1]; pk2[4 * kk + 2] = f[2]; pk2[4 * kk + 3] = f[3];
        }
      }
      const uint32_t s2 = take();
      TR(53);
      const uint64_t d2 = desc_mn(sb + s2 * SLOT);
      turn_begin();
      wg_fence();
#pragma unroll
      for (int kk = 0; kk < 16; kk++) {
        wgmma_rs_n64_tb(o, pk2[4 * kk], pk2[4 * kk + 1], pk2[4 * kk + 2], pk2[4 * kk + 3], desc_add(d2, kk * 2048), 1);
        if (kk == ARRIVE_KK && (ch < 6 || w == 1)) turn_end();
      }
      wg_commit();
      TR(54);
      if (!FIRST) hand_over(ch - 1);
      wg_wait<1>();
      TR(55);
      release(bar_addr(sb, B_RG_EMPTY + s1), lane);
      p2 = s2;
    };
    chunk(0, Int<1>(), oa, ob);
#pragma unroll 1
    for (int ch = 1; ch < 7; ch += 2) { chunk(ch, Int<0>(), ob, oa); chunk(ch + 1, Int<0>(), oa, ob); }
    wg_wait<0>();
    TR(58);
    reg_fence(pk);
    reg_fence(pk2);
    stage_o(oa, 6);
    hand_over(6);
  }
  TS(12); TR(59);
  if (threadIdx.x == 128) ST(14);
  if ((threadIdx.x & 127) == 0) GT(54 + w);

  TS(16); TS(18); TS(17);
  TR(99); TR_END();
  TS(13); TSG(14);
}

#define CONV_STAGGER_NS 1200
namespace ssm {
#define CONV_GROUPS (D_SPARE / 8 / NCONV)
constexpr int GROUPS = CONV_GROUPS;
constexpr uint32_t ZROWS = 16;
constexpr uint32_t CHAN = (ZROWS + 256 + 1) * 16;
constexpr uint32_t XBUF = 8 * CHAN;
constexpr uint32_t OFF_X = 0;
constexpr uint32_t HCOPY = 4160;
constexpr uint32_t OFF_H = 2 * XBUF;
constexpr uint32_t HWARP = 3 * HCOPY;
constexpr uint32_t IO_K = 128, IO_V = IO_K + 4096, IO_Q = IO_V + 4096, IOBUF = IO_Q + 4096;
constexpr uint32_t OFF_IO = (OFF_H + 8 * HWARP + 127) / 128 * 128;
constexpr uint32_t END = OFF_IO + 4 * IOBUF;
static_assert(IOBUF % 128 == 0 && OFF_H % 16 == 0, "TMA destination alignment");
static_assert(END <= BARS, "smem");
enum : uint32_t { B_XREADY = 0, B_ZDONE = 2, B_KV = 4, B_Q = 8, B_HRAW = 12, B_QLAST = 20 };
constexpr int CW_BAR = 4;

__device__ __forceinline__ int group_d0(int cidx, int grp) { return (grp * NCONV + cidx) * 8; }
__device__ __forceinline__ uint32_t x_lane(int lane) { return (lane & 7) * CHAN + (ZROWS + (lane >> 3)) * 16; }
__device__ __forceinline__ uint32_t t_lane(int lane) { return (uint32_t)(8 * (lane >> 3) + 7 - (lane & 7)) * 16; }
struct Taps { uint32_t s[4]; };
__device__ __forceinline__ Taps load_taps(const Params& p, int d0, int c) {
  const uint2 s0 = __ldg(reinterpret_cast<const uint2*>(p.a_shift + (d0 + 2 * c) * 4)), s1 = __ldg(reinterpret_cast<const uint2*>(p.a_shift + (d0 + 2 * c + 1) * 4));
  return Taps{{__byte_perm(s0.x, s1.x, 0x5410), __byte_perm(s0.x, s1.x, 0x7632), __byte_perm(s0.y, s1.y, 0x5410), __byte_perm(s0.y, s1.y, 0x7632)}};
}
__device__ __forceinline__ uint32_t short_conv(const Taps& t, uint32_t k0, uint32_t k1, uint32_t k2, uint32_t k3, uint32_t v) {
  if (FUSED & 1) return bmul(bfma(k3, t.s[0], bfma(k2, t.s[1], bfma(k1, t.s[2], bmul(k0, t.s[3])))), v);
  return bmul(badd(badd(badd(bmul(k0, t.s[3]), bmul(k1, t.s[2])), bmul(k2, t.s[1])), bmul(k3, t.s[0])), v);
}
template <int U>
__device__ __forceinline__ void gate_chunk(uint32_t xa, uint32_t qa) {
#pragma unroll 1
  for (int i0 = 0; i0 < 8; i0 += U) {
    uint32_t zz[U][4], qq[U][4];
#pragma unroll
    for (int i = 0; i < U; i++) { ldsm4t(zz[i], xa + (i0 + i) * 64); ldsm4(qq[i], qa + (i0 + i) * 512); }
#pragma unroll
    for (int i = 0; i < U; i++) stsm4(qa + (i0 + i) * 512, bmul(qq[i][0], zz[i][0]), bmul(qq[i][1], zz[i][1]), bmul(qq[i][2], zz[i][2]), bmul(qq[i][3], zz[i][3]));
  }
}

__device__ __forceinline__ void io_warp(const Params& p, uint32_t sb, int cidx, int wq) {
  const int lane = threadIdx.x & 31;
  const uint32_t io = sb + OFF_IO + wq * IOBUF, bkv = bar_addr(sb, B_KV + wq), bq = bar_addr(sb, B_Q + wq);
  auto load_kv = [&](int e) {
    __syncwarp();
    if (lane != 0) return;
    const int d0 = group_d0(cidx, e >> 1), row = (2 * wq + (e & 1)) * 256;
    if (e < 2 * GROUPS) {
      mbar_expect_tx(bkv, IO_Q);
      tma_ld2(io, &p.ak8, bkv, d0, row - 8);
      tma_ld2(io + IO_K, &p.ak, bkv, d0, row);
      tma_ld2(io + IO_V, &p.av, bkv, d0, row);
    } else {
      const uint32_t bar = bar_addr(sb, B_QLAST + 2 * wq + 1);
      mbar_expect_tx(bar, 4096);
      tma_ld2(io + IO_K, &p.aq, bar, group_d0(cidx, GROUPS - 1), row + 256);
    }
  };
  auto load_q = [&](int e) {
    __syncwarp();
    if (lane != 0) return;
    const uint32_t bar = e < 2 * GROUPS - 2 ? bq : bar_addr(sb, B_QLAST + 2 * wq);
    mbar_expect_tx(bar, 4096);
    tma_ld2(io + IO_Q, &p.aq, bar, group_d0(cidx, e >> 1), (2 * wq + (e & 1)) * 256);
  };
  TR_DECL;
  TR(0);
  load_kv(0);
  const uint32_t xl = sb + OFF_X + x_lane(lane) + wq * 1024, tl = io + t_lane(lane);
#pragma unroll 1
  for (int grp = -2; grp + 1 < GROUPS; grp++) {
    const bool more = grp + 2 < GROUPS;
    const Taps taps = load_taps(p, group_d0(cidx, more ? grp + 2 : 0), lane & 3);
    PCLK(c0);
    if (grp >= 0) mbar_wait_nap(bar_addr(sb, B_ZDONE + (grp & 1)), (grp >> 1) & 1);
    PACC(tp, c0);
    PCLK(c1);
    TR(80);
#pragma unroll 1
    for (int i = 0; i < 2; i++) {
      const uint32_t xa = xl + (grp & 1) * XBUF + i * 512;
      if (grp >= 0) {
        mbar_wait_nap(bq, i);
        TR(81);
        gate_chunk<4>(xa, tl + IO_Q);
      }
      if (more) {
        TR(82);
        mbar_wait_nap(bkv, i);
        TR(83);
#pragma unroll 1
        for (int u0 = 0; u0 < 8; u0 += 2) {
          uint32_t k0[2][4], k1[2][4], k2[2][4], k3[2][4], vv[2][4];
#pragma unroll
          for (int u = 0; u < 2; u++) {
            const uint32_t ka = tl + IO_K + (u0 + u) * 512;
            ldsm4(k0[u], ka - 48); ldsm4(k1[u], ka - 32); ldsm4(k2[u], ka - 16); ldsm4(k3[u], ka); ldsm4(vv[u], ka + 4096);
          }
#pragma unroll
          for (int u = 0; u < 2; u++)
            stsm4t(xa + (u0 + u) * 64, short_conv(taps, k0[u][0], k1[u][0], k2[u][0], k3[u][0], vv[u][0]), short_conv(taps, k0[u][1], k1[u][1], k2[u][1], k3[u][1], vv[u][1]),
                   short_conv(taps, k0[u][2], k1[u][2], k2[u][2], k3[u][2], vv[u][2]), short_conv(taps, k0[u][3], k1[u][3], k2[u][3], k3[u][3], vv[u][3]));
        }
        load_kv(2 * (grp + 2) + i + 1);
        TR(84);
        if (i == 1) warp_arrive(bar_addr(sb, B_XREADY + (grp & 1)), lane);
      }
      if (grp >= 0) {
        fence_async_smem();
        __syncwarp();
        if (lane == 0) {
          tma_st2(&p.ao, io + IO_Q, group_d0(cidx, grp), (2 * wq + i) * 256);
          bulk_commit();
          bulk_wait_read();
        }
      }
      if (2 * grp + i + 1 >= 0) load_q(2 * grp + i + 1);
      TR(85);
    }
    PACC(te, c1);
  }
  if (lane == 0) bulk_wait_all();
  TR(99); TR_END();
}

__device__ __forceinline__ void conv_warp(const Params& p, uint32_t sb, int cidx, int ch) {
  const int lane = threadIdx.x & 31;
  const uint32_t hE0 = sb + OFF_H + ch * HWARP, hO = hE0 + HCOPY;
  const uint32_t hbar = bar_addr(sb, B_HRAW + ch);
  auto fetch_h = [&](int grp) {
    if (lane == 0) {
      mbar_expect_tx(hbar, 4096);
      asm volatile("cp.async.bulk.shared::cluster.global.mbarrier::complete_tx::bytes [%0], [%1], %2, [%3];"
                   :: "r"(hE0 + (grp & 1) * 2 * HCOPY + 32), "l"(p.a_ssmk + (size_t)(group_d0(cidx, grp) + ch) * SEQ), "r"(4096), "r"(hbar) : "memory");
    }
  };
  TR_DECL;
  TR(0);
  fetch_h(0);
#pragma unroll 1
  for (int grp = 0; grp < GROUPS; grp++) {
    const uint32_t xc = sb + OFF_X + (grp & 1) * XBUF + ch * CHAN;
    const uint32_t D1 = __ldg(reinterpret_cast<const unsigned short*>(p.a_D + group_d0(cidx, grp) + ch));
    PCLK(k0);
    mbar_wait(hbar, grp & 1);
    const uint32_t hE = hE0 + (grp & 1) * 2 * HCOPY;
    if (grp + 1 < GROUPS) fetch_h(grp + 1);
    {
      uint4 w[8]; uint32_t nx[8];
      const uint32_t o = 32 + lane * 16;
#pragma unroll
      for (int i = 0; i < 8; i++) { w[i] = lds16(hE + o + i * 512); nx[i] = lds4(hE + o + i * 512 + 16); }
#pragma unroll
      for (int i = 0; i < 8; i++)
        sts16(hO + o + i * 512, __byte_perm(w[i].x, w[i].y, 0x5432), __byte_perm(w[i].y, w[i].z, 0x5432), __byte_perm(w[i].z, w[i].w, 0x5432), __byte_perm(w[i].w, nx[i], 0x5432));
      if (lane == 0) asm volatile("st.shared.u32 [%0], %1;" :: "r"(hO + 28), "r"(w[0].x << 16) : "memory");
    }
    __syncwarp();
    const uint32_t ha = cv_h_lane(lane, hE, hO), xa = xc + cv_x_lane(lane);
    TR(71);
    mbar_wait(bar_addr(sb, B_XREADY + (grp & 1)), (grp >> 1) & 1);
    TR(72);
    if (grp == 0 && ch >= 4) __nanosleep(CONV_STAGGER_NS);
    PACC(tw, k0);
    PCLK(k1);
    float acc[16][4];
#pragma unroll
    for (int i = 0; i < 16; i++) { acc[i][0] = 0.f; acc[i][1] = 0.f; acc[i][2] = 0.f; acc[i][3] = 0.f; }
#pragma unroll 1
    for (int r = 0; r < 8; r++) {
      uint32_t fx[16][4], fh[16][2];
#pragma unroll
      for (int i = 0; i < 16; i++) { fh[i][0] = lds4(ha + i * 256 + r * 32); fh[i][1] = lds4(ha + i * 256 + r * 32 + 16); }
#pragma unroll
      for (int i = 0; i < 16; i++) ldsm4(fx[i], xa + i * 256 - r * 32);
#pragma unroll
      for (int sx = 0; sx < 16; sx++)
#pragma unroll
        for (int jj = 0; jj < 16 - sx; jj++) mma16816(acc[jj + sx], fx[sx], fh[jj][0], fh[jj][1]);
    }
    PACC(tm, k1);
    PCLK(k2);
    TR(73);
    {
      uint32_t x[8][4], Dd;
      asm volatile("prmt.b32 %0, %1, %1, 0x1010;" : "=r"(Dd) : "r"(D1));
      const uint32_t ad = xc + (ZROWS + lane) * 16;
#pragma unroll
      for (int i = 0; i < 8; i++) ldsm4(x[i], ad + i * 512);
#pragma unroll
      for (int i = 0; i < 8; i++)
        stsm4(ad + i * 512, add_skip(pack_bf16(acc[2 * i][0], acc[2 * i][1]), x[i][0], Dd), add_skip(pack_bf16(acc[2 * i][2], acc[2 * i][3]), x[i][1], Dd),
              add_skip(pack_bf16(acc[2 * i + 1][0], acc[2 * i + 1][1]), x[i][2], Dd), add_skip(pack_bf16(acc[2 * i + 1][2], acc[2 * i + 1][3]), x[i][3], Dd));
    }
    if (grp + 1 < GROUPS) warp_arrive(bar_addr(sb, B_ZDONE + (grp & 1)), lane);
    PACC(tr, k2);
    TR(74);
  }
  {
    mbar_wait(bar_addr(sb, B_QLAST + ch), 0);
    named_sync(CW_BAR, 256);
    TR(75);
    const uint32_t qb = sb + OFF_IO + (ch >> 1) * IOBUF + ((ch & 1) ? IO_K : IO_Q);
    gate_chunk<8>(sb + OFF_X + ((GROUPS - 1) & 1) * XBUF + x_lane(lane) + ch * 512, qb + t_lane(lane));
    fence_async_smem();
    __syncwarp();
    if (lane == 0) { tma_st2(&p.ao, qb, group_d0(cidx, GROUPS - 1), ch * 256); bulk_commit(); bulk_wait_read(); }
    TR(99); TR_END();
  }
}

__device__ __forceinline__ void init(uint32_t sb) {
  if (threadIdx.x < 16 * ZROWS) sts16(sb + OFF_X + (threadIdx.x >> 4) * CHAN + (threadIdx.x & 15) * 16, 0, 0, 0, 0);
  if (threadIdx.x < 96) sts16(sb + OFF_H + (threadIdx.x >> 2) * HCOPY + (threadIdx.x & 1) * 16 + ((threadIdx.x & 2) ? 4128 : 0), 0, 0, 0, 0);
  if (threadIdx.x == 0) {
    for (int i = 0; i < 2; i++) { mbar_init(bar_addr(sb, B_XREADY + i), 4); mbar_init(bar_addr(sb, B_ZDONE + i), 8); }
    for (int i = 0; i < 4; i++) { mbar_init(bar_addr(sb, B_KV + i), 1); mbar_init(bar_addr(sb, B_Q + i), 1); }
    for (int i = 0; i < 8; i++) { mbar_init(bar_addr(sb, B_HRAW + i), 1); mbar_init(bar_addr(sb, B_QLAST + i), 1); }
    fence_async_smem();
  }
  named_sync(0, NTHREADS);
}
}

__device__ __forceinline__ void ssm_side_work(const Params& p, uint32_t sb, unsigned epoch) {
  const Role ro = get_role();
  const int h = ro.h, j = ro.j;
  const int lane = threadIdx.x & 31, g = lane >> 2, c = lane & 3;
  const int d0 = D_SPARE + 8 * h;
  uint8_t* xs = g_xs + (size_t)(h * 8 + g) * CV_BYTES + c * 4;
  auto xrow = [&](int beta) { return xs + (16 + beta) * 16; };
  {
    const uint4* hp = reinterpret_cast<const uint4*>(p.a_ssmk + (size_t)(d0 + j) * SEQ) + lane;
    uint8_t* he = g_xs + (size_t)(h * 8 + j) * CV_BYTES + CV_HE;
#pragma unroll 2
    for (int i = 0; i < 8; i++) {
      const uint4 wv = __ldg(hp + i * 32);
      const uint32_t nx = i * 32 + lane < 255 ? __ldg(reinterpret_cast<const uint32_t*>(hp + i * 32 + 1)) : 0u;
      const uint32_t o = 32 + (i * 32 + lane) * 16;
      *reinterpret_cast<uint4*>(he + o) = wv;
      *reinterpret_cast<uint4*>(he + CV_HCOPY + o) =
          make_uint4(__byte_perm(wv.x, wv.y, 0x5432), __byte_perm(wv.y, wv.z, 0x5432), __byte_perm(wv.z, wv.w, 0x5432), __byte_perm(wv.w, nx, 0x5432));
      if (o == 32) *reinterpret_cast<uint32_t*>(he + CV_HCOPY + 28) = wv.x << 16;
    }
    if (lane == 0) *reinterpret_cast<uint32_t*>(he + CV_D - CV_HE) = (uint32_t)__ldg(reinterpret_cast<const unsigned short*>(p.a_D + d0 + j)) * 0x10001u;
  }
  {
    const ssm::Taps taps = ssm::load_taps(p, d0, c);
    const uint32_t* kp = reinterpret_cast<const uint32_t*>(p.a_k + (size_t)(256 * j + 7 - g) * DA + d0) + c;
    const uint32_t* vp = reinterpret_cast<const uint32_t*>(p.a_v + (size_t)(256 * j + 7 - g) * DA + d0) + c;
    uint32_t kprev = j > 0 ? __ldg(kp - 8 * (DA / 2)) : 0u;
#pragma unroll 1
    for (int i0 = 0; i0 < 32; i0 += 8) {
      uint32_t kk[8], vv[8];
#pragma unroll
      for (int i = 0; i < 8; i++) { kk[i] = __ldg(kp + (i0 + i) * 8 * (DA / 2)); vv[i] = __ldg(vp + (i0 + i) * 8 * (DA / 2)); }
#pragma unroll
      for (int i = 0; i < 8; i++) {
        const uint32_t k2 = __shfl_sync(0xffffffffu, g < 1 ? kprev : kk[i], (lane + 4) & 31);
        const uint32_t k1 = __shfl_sync(0xffffffffu, g < 2 ? kprev : kk[i], (lane + 8) & 31);
        const uint32_t k0 = __shfl_sync(0xffffffffu, g < 3 ? kprev : kk[i], (lane + 12) & 31);
        *reinterpret_cast<uint32_t*>(xrow(32 * j + i0 + i)) = transpose8(ssm::short_conv(taps, k0, k1, k2, kk[i], vv[i]));
        kprev = kk[i];
      }
    }
    __syncwarp();
    if (lane == 0) {
      flag_signal(&g_flags.xs_ready[h].v);
      flag_wait(&g_flags.xs_ready[h].v, 8, epoch);
      fence_async_all();
      mbar_arrive(bar_addr(sb, B_XS));
    }
  }
  if (lane == 0) {
    for (int i = 0; i < 3; i++) {
      flag_wait(&g_flags.kv_ready[3 * h + i].v, 16, epoch);
      fence_async_all();
      mbar_arrive(bar_addr(sb, B_KV + i));
    }
    mbar_wait_nap(bar_addr(sb, B_CONV), 0);
    flag_signal(&g_flags.zs_ready[h].v);
    flag_wait(&g_flags.zs_ready[h].v, 8, epoch);
    asm volatile("red.relaxed.gpu.global.add.u64 [%0], 1;" :: "l"(&g_flags.done) : "memory");
  }
  __syncwarp();
  fence_async_all();
  const uint32_t qb = q_region(sb, 1) + 16384, zb = qb + 4096, bar = bar_addr(sb, B_GATE);
  constexpr uint32_t ZCH = 528;
  mbar_wait_slow(bar_addr(sb, B_GFREE), 0);
  if (lane == 0) { mbar_expect_tx(bar, 8192); tma_ld2(qb, &p.aq, bar, d0, 256 * j); }
  __syncwarp();
  if (lane < 8) bulk_ld(zb + lane * ZCH, g_xs + (size_t)(h * 8 + lane) * CV_BYTES + (16 + 32 * j) * 16, 512, bar);
  mbar_wait(bar, 0);
  ssm::gate_chunk<2>(zb + (lane & 7) * ZCH + (lane >> 3) * 16, qb + ssm::t_lane(lane));
  fence_async_smem();
  __syncwarp();
  if (lane == 0) { tma_st2(&p.ao, qb, d0, 256 * j); bulk_commit(); bulk_wait_all(); }
}

__global__ void __cluster_dims__(2, 1, 1) __launch_bounds__(NTHREADS, 1)
concat_heads__ssm_conv_h3__compressed_kv_cla__prompt_kernel(uint8_t* xs, uint32_t one, const __grid_constant__ Params p) {
  if (threadIdx.x == 0) { prefetch_map(&p.wuk); prefetch_map(&p.ckv); }
  extern __shared__ uint8_t smem_raw[];
  if (threadIdx.x == 96) { ST(0); STG_(10); }
  const uint32_t sb = (smem_u32(smem_raw) + 1023) & ~1023u;
  const int warp = __shfl_sync(0xffffffffu, threadIdx.x >> 5, 0);
  const int wg = warp >> 2;
  const int cta = blockIdx.x;
  const bool attn = cta < NMAIN;
  if (attn && (threadIdx.x >> 5) == 4) {
    const Role ro = get_role();
    auto load = [&](int k) {
      const uint32_t full = bar_addr(sb, B_P1_FULL + k), dst = sb + k * P1_STAGE;
      mbar_expect_tx(full, P1_STAGE);
      tma_ld2(dst, &p.ckv, full, k * 64, kv_block(ro.j, 0) * 128);
      tma_ld3(dst + 16384, &p.wuk, full, 0, k * 64, ro.h * 4);
    };
    if (threadIdx.x == 128) {
      for (int i = 0; i < 4; i++) mbar_init(bar_addr(sb, B_P1_FULL + i), 1);
      asm volatile("fence.mbarrier_init.release.cluster;" ::: "memory");
      ST(1);
      load(0);
    }
    __syncwarp();
    named_arrive(0, NTHREADS);
    if (threadIdx.x == 128) {
      for (int k = 1; k < EARLY_LD; k++) load(k);
      ST(2);
    }
    __syncwarp();
  }
  const int lane = threadIdx.x & 31;
  if (wg == 0) {
    if (!attn) {
      asm volatile("setmaxnreg.dec.sync.aligned.u32 72;");
      if (threadIdx.x == 0) GT(0);
      if (one) { ssm::init(sb); ssm::io_warp(p, sb, cta - NMAIN, fresh_warp()); }
      if (threadIdx.x == 0) GT(14);
      return;
    }
    asm volatile("setmaxnreg.dec.sync.aligned.u32 40;");
    named_arrive(PP_BAR + 1, 256);
    if (warp == 2) {
      if (lane == 0) {
        for (int i = 0; i < 4; i++) mbar_init(bar_addr(sb, B_P1_EMPTY + i), 8);
        for (int i = 0; i < NSLOT; i++) {
          mbar_init(bar_addr(sb, B_RG_FULL + i), 1); mbar_init(bar_addr(sb, B_RG_EMPTY + i), 8);
        }
        for (int i = 0; i < 2; i++) { mbar_init(bar_addr(sb, B_ST_FULL + i), 4); mbar_init(bar_addr(sb, B_ST_EMPTY + i), 1); }
        mbar_init(bar_addr(sb, B_XS), 1); mbar_init(bar_addr(sb, B_CONV), 8); mbar_init(bar_addr(sb, B_GATE), 1); mbar_init(bar_addr(sb, B_GFREE), 1);
        for (int i = 0; i < 3; i++) mbar_init(bar_addr(sb, B_KV + i), 1);
        for (int i = 0; i < 8; i++) mbar_init(bar_addr(sb, B_CTXS + i), 4);
        for (int i = 0; i < 4; i++) { mbar_arrive(bar_addr(sb, B_RG_FULL + i)); if (i < 3) mbar_arrive_n(bar_addr(sb, B_RG_EMPTY + i), 8); }
        for (int i = 0; i < 4; i++) { mbar_init(bar_addr(sb, B_S2_FULL + i), 4); mbar_init(bar_addr(sb, B_S2_EMPTY + i), 1); }
        for (int i = 0; i < 2; i++) { mbar_init(bar_addr(sb, B_QFREE + i), 4); mbar_init(bar_addr(sb, B_CTXF + i), 1); }
        asm volatile("fence.mbarrier_init.release.cluster;" ::: "memory");
        ST(3);
      }
      __syncwarp();
      named_arrive(0, NTHREADS);
    } else {
      named_sync(0, NTHREADS);
    }
    if (threadIdx.x == 96) ST(4);
    if (warp == 0) {
      if (lane == 0) producer_main(p, sb);
    } else if (warp < 3) {
      storer_main(p, sb);
    } else {
      const unsigned epoch = load_epoch();
      mbar_wait(bar_addr(sb, B_P1_FULL + 3), 0);
      __nanosleep(SIDE_DELAY_NS);
      ssm_side_work(p, sb, epoch);
    }
  } else {
    if (attn) {
      asm volatile("setmaxnreg.inc.sync.aligned.u32 232;");
      if (threadIdx.x == 256) ST(5);
      if (one) consumer_main(p, sb, xs, one);
    } else {
      asm volatile("setmaxnreg.inc.sync.aligned.u32 216;");
      if (threadIdx.x == 128) { GT(12); PT(10); }
      if (one) { ssm::init(sb); ssm::conv_warp(p, sb, cta - NMAIN, fresh_warp() - 4); }
      if (threadIdx.x == 128) { PT(9); GT(13); }
    }
  }
}

typedef CUresult (*EncodeTiledFn)(CUtensorMap*, CUtensorMapDataType, cuuint32_t, void*, const cuuint64_t*, const cuuint64_t*,
                                  const cuuint32_t*, const cuuint32_t*, CUtensorMapInterleave, CUtensorMapSwizzle,
                                  CUtensorMapL2promotion, CUtensorMapFloatOOBfill);

void make_map(EncodeTiledFn enc, CUtensorMap* m, const void* ptr, int rank, const uint64_t* dims, const uint64_t* strides, const uint32_t* box) {
  cuuint64_t d[3], s[2]; cuuint32_t b[3], e[3] = {1, 1, 1};
  for (int i = 0; i < rank; i++) { d[i] = dims[i]; b[i] = box[i]; if (i) s[i - 1] = strides[i - 1]; }
  enc(m, CU_TENSOR_MAP_DATA_TYPE_BFLOAT16, rank, const_cast<void*>(ptr), d, s, b, e, CU_TENSOR_MAP_INTERLEAVE_NONE,
      CU_TENSOR_MAP_SWIZZLE_128B, CU_TENSOR_MAP_L2_PROMOTION_L2_256B, CU_TENSOR_MAP_FLOAT_OOB_FILL_NONE);
}
void map2(EncodeTiledFn enc, CUtensorMap* m, const void* ptr, uint64_t cols, uint64_t rows, uint32_t bc, uint32_t br) {
  const uint64_t dims[2] = {cols, rows}, st[1] = {cols * 2}; const uint32_t box[2] = {bc, br};
  make_map(enc, m, ptr, 2, dims, st, box);
}
void map2_plain(EncodeTiledFn enc, CUtensorMap* m, const void* ptr, uint64_t cols, uint64_t rows, uint32_t bc, uint32_t br) {
  cuuint64_t d[2] = {cols, rows}, st[1] = {cols * 2}; cuuint32_t b[2] = {bc, br}, e[2] = {1, 1};
  enc(m, CU_TENSOR_MAP_DATA_TYPE_BFLOAT16, 2, const_cast<void*>(ptr), d, st, b, e, CU_TENSOR_MAP_INTERLEAVE_NONE,
      CU_TENSOR_MAP_SWIZZLE_NONE, CU_TENSOR_MAP_L2_PROMOTION_L2_128B, CU_TENSOR_MAP_FLOAT_OOB_FILL_NONE);
}
void map3(EncodeTiledFn enc, CUtensorMap* m, const void* ptr, uint64_t rows, uint32_t nblk) {
  const uint64_t dims[3] = {64, rows, 64}, st[2] = {8192, 128}; const uint32_t box[3] = {64, 64, nblk};
  make_map(enc, m, ptr, 3, dims, st, box);
}

}

extern "C" void kernel_launch(void* const* d_in, const int* in_sizes, int n_in, void* d_out, int out_size) {
  (void)in_sizes; (void)n_in; (void)out_size;
  static EncodeTiledFn enc = nullptr;
  static void *kv_ptr = nullptr, *acc_ptr = nullptr, *xs_ptr = nullptr;
  if (!enc) {
    void* fn = nullptr; cudaDriverEntryPointQueryResult qr;
    cudaGetDriverEntryPoint("cuTensorMapEncodeTiled", &fn, cudaEnableDefault, &qr);
    enc = (EncodeTiledFn)fn;
    cudaGetSymbolAddress(&kv_ptr, g_kv);
    cudaGetSymbolAddress(&acc_ptr, g_ctx);
    cudaGetSymbolAddress(&xs_ptr, g_xs);
    cudaFuncSetAttribute(concat_heads__ssm_conv_h3__compressed_kv_cla__prompt_kernel, cudaFuncAttributeMaxDynamicSharedMemorySize, SMEM_BYTES);
  }
  Params p;
  p.a_q = (const bf16*)d_in[0]; p.a_k = (const bf16*)d_in[1]; p.a_v = (const bf16*)d_in[2];
  map2_plain(enc, &p.aq, d_in[0], DA, SEQ, 8, 256);
  map2_plain(enc, &p.ak, d_in[1], DA, SEQ, 8, 256);
  map2_plain(enc, &p.ak8, d_in[1], DA, SEQ, 8, 8);
  map2_plain(enc, &p.av, d_in[2], DA, SEQ, 8, 256);
  map2_plain(enc, &p.ao, d_out, OUTW, SEQ, 8, 256);
  p.a_shift = (const bf16*)d_in[3]; p.a_ssmk = (const bf16*)d_in[4]; p.a_D = (const bf16*)d_in[5];
  p.out = (bf16*)d_out; p.b_x = (const bf16*)d_in[6]; p.b_wo = (const bf16*)d_in[11];
  map2(enc, &p.x, d_in[6], DM, SEQ, 64, 128);
  map2(enc, &p.ckv, d_in[7], DC, SEQ, 64, 128);
  map3(enc, &p.wq, d_in[8], DM, 4);
  map2_plain(enc, &p.wqp, d_in[8], NH * HD, DM, 256, 4);
  map3(enc, &p.wuk, d_in[9], DC, 4);
  map3(enc, &p.wuv, d_in[10], DC, 4);
  map2(enc, &p.wo, d_in[11], DM, NH * HD, 64, 256);
  map2(enc, &p.part, d_out, OUTW, SEQ, 64, 64);
  p.kv = (uint8_t*)kv_ptr; p.ctx = (uint8_t*)acc_ptr;
  concat_heads__ssm_conv_h3__compressed_kv_cla__prompt_kernel<<<NCTA, NTHREADS, SMEM_BYTES>>>((uint8_t*)xs_ptr, 1u, p);
}
```

```cpp
#include <cuda_runtime.h>
#include <cuda_bf16.h>
#include <cuda.h>
#include <stdint.h>

namespace {

typedef __nv_bfloat16 bf16;

constexpr int SEQ  = 2048;
constexpr int DA   = 448;
constexpr int NH   = 16;
constexpr int HD   = 256;
constexpr int DM   = 448;
constexpr int DC   = 1024;
constexpr int OUTW = DA + DM;
constexpr int NMAIN = 128;
constexpr int NCONV = 4;
constexpr int NCTA  = NMAIN + NCONV;
constexpr int NTHREADS = 384;
constexpr int D_SPARE = 320;

__device__ __align__(1024) bf16 g_kv[2ull * SEQ * NH * HD];
__device__ __align__(1024) bf16 g_ctx[(size_t)NMAIN * 128 * HD];
constexpr uint32_t CV_HE = 272 * 16, CV_HCOPY = 4160, CV_D = CV_HE + 4144, CV_BYTES = CV_HE + 2 * CV_HCOPY;
__device__ __align__(128) uint8_t g_xs[NMAIN * CV_BYTES];
struct alignas(128) Flag { unsigned v; unsigned pad[31]; };
struct Flags {
  Flag kv_ready[3 * NH];
  Flag ctx_ready[NMAIN * 2];
  Flag out_ready[16 * 2];
  Flag xs_ready[NH];
  Flag zs_ready[NH];
  alignas(128) unsigned long long done;
};
__device__ Flags g_flags;

struct alignas(64) Params {
  CUtensorMap ckv;
  CUtensorMap wuk;
  CUtensorMap wuv;
  CUtensorMap x;
  CUtensorMap wq;
  CUtensorMap wqp;
  CUtensorMap part;
  CUtensorMap wo;
  CUtensorMap ak, ak8, av, aq, ao;
  const bf16 *a_shift, *a_ssmk, *a_D, *b_x, *b_wo;
  bf16* out;
  uint8_t *kv, *ctx;
};

constexpr uint32_t P1_STAGE = 49152;
constexpr uint32_t P1_STG   = 196608;
constexpr uint32_t SLOT     = 32768;
constexpr int      NSLOT    = 5;
constexpr uint32_t QREG     = 163840;
constexpr uint32_t CV_X = 4 * SLOT + 16384, CV_R = 3 * SLOT;
static_assert(CV_BYTES <= 16384 && CV_BYTES % 128 == 0, "SSM operands");
constexpr uint32_t BARS     = 229376;
constexpr uint32_t SMEM_BYTES = BARS + 512 + 1024;
enum : uint32_t {
  B_P1_FULL = 0, B_P1_EMPTY = 4, B_RG_FULL = 8, B_RG_EMPTY = 13, B_ST_FULL = 18, B_ST_EMPTY = 20,
  B_XS = 22, B_SIDE = 23, B_S2_FULL = 28, B_S2_EMPTY = 32, B_QFREE = 36, B_CTXF = 38, B_KV = 40, B_GATE = 43, B_CTXS = 44, B_GFREE = 52, B_CONV = 53, B_COUNT = 54
};

__device__ __forceinline__ uint32_t smem_u32(const void* p) { return (uint32_t)__cvta_generic_to_shared(p); }
__device__ __forceinline__ void mbar_init(uint32_t bar, uint32_t cnt) {
  asm volatile("mbarrier.init.shared::cta.b64 [%0], %1;" :: "r"(bar), "r"(cnt) : "memory");
}
__device__ __forceinline__ void mbar_expect_tx(uint32_t bar, uint32_t bytes) {
  asm volatile("mbarrier.arrive.expect_tx.shared::cta.b64 _, [%0], %1;" :: "r"(bar), "r"(bytes) : "memory");
}
__device__ __forceinline__ void mbar_arrive(uint32_t bar) {
  asm volatile("mbarrier.arrive.shared::cta.b64 _, [%0];" :: "r"(bar) : "memory");
}
__device__ __forceinline__ void mbar_arrive_n(uint32_t bar, uint32_t n) {
  asm volatile("mbarrier.arrive.shared::cta.b64 _, [%0], %1;" :: "r"(bar), "r"(n) : "memory");
}
__device__ __forceinline__ void lane0_arrive(uint32_t bar, uint32_t n, int lane) {
  asm volatile("{\n.reg .pred p;\nsetp.eq.s32 p, %2, 0;\n@p mbarrier.arrive.shared::cta.b64 _, [%0], %1;\n}" :: "r"(bar), "r"(n), "r"(lane) : "memory");
}
__device__ __forceinline__ bool mbar_try(uint32_t bar, uint32_t parity) {
  uint32_t ok;
  asm volatile("{\n.reg .pred p;\nmbarrier.try_wait.parity.shared::cta.b64 p, [%1], %2;\nselp.u32 %0, 1, 0, p;\n}"
               : "=r"(ok) : "r"(bar), "r"(parity) : "memory");
  return ok;
}
#define FLAG_NS 100
#define NAP_NS 100
constexpr uint32_t SPIN_LIMIT = 1u << 24;
__device__ __forceinline__ void mbar_wait(uint32_t bar, uint32_t parity) {
  if (mbar_try(bar, parity)) return;
  uint32_t n = 0;
  while (!mbar_try(bar, parity)) { if (++n > SPIN_LIMIT) __trap(); }
}
__device__ __forceinline__ void mbar_wait_nap(uint32_t bar, uint32_t parity) {
  uint32_t n = 0;
  while (!mbar_try(bar, parity)) { if (++n > (SPIN_LIMIT >> 2)) __trap(); __nanosleep(NAP_NS); }
}
__device__ __forceinline__ void mbar_wait_slow(uint32_t bar, uint32_t parity) {
  uint32_t n = 0;
  while (!mbar_try(bar, parity)) { if (++n > (SPIN_LIMIT >> 4)) __trap(); __nanosleep(500); }
}
__device__ __forceinline__ unsigned load_epoch() {
  unsigned long long e; asm volatile("ld.relaxed.gpu.global.u64 %0, [%1];" : "=l"(e) : "l"(&g_flags.done) : "memory"); return (unsigned)(e / NMAIN);
}
__device__ __forceinline__ void flag_wait(const unsigned* f, unsigned count, unsigned epoch) {
  const unsigned target = (epoch + 1) * count;
  uint32_t n = 0;
  while (true) {
    unsigned v;
    asm volatile("ld.acquire.gpu.global.u32 %0, [%1];" : "=r"(v) : "l"(f) : "memory");
    if ((int)(v - target) >= 0) break;
    if (++n > SPIN_LIMIT) __trap();
    __nanosleep(FLAG_NS);
  }
}
__device__ __forceinline__ void fence_async_all() { asm volatile("fence.proxy.async;" ::: "memory"); }
__device__ __forceinline__ void flag_signal(unsigned* f) {
  asm volatile("fence.acq_rel.gpu;" ::: "memory");
  asm volatile("red.relaxed.gpu.global.add.u32 [%0], 1;" :: "l"(f) : "memory");
}
__device__ __forceinline__ void flag_signal_after_bulk(unsigned* f) {
  asm volatile("red.relaxed.gpu.global.add.u32 [%0], 1;" :: "l"(f) : "memory");
}
__device__ __forceinline__ void fence_async_smem() { asm volatile("fence.proxy.async.shared::cta;" ::: "memory"); }
__device__ __forceinline__ void tma_ld2(uint32_t dst, const CUtensorMap* m, uint32_t bar, int c0, int c1) {
  asm volatile("cp.async.bulk.tensor.2d.shared::cluster.global.mbarrier::complete_tx::bytes [%0], [%1, {%3, %4}], [%2];"
               :: "r"(dst), "l"(m), "r"(bar), "r"(c0), "r"(c1) : "memory");
}
__device__ __forceinline__ void tma_ld3(uint32_t dst, const CUtensorMap* m, uint32_t bar, int c0, int c1, int c2) {
  asm volatile("cp.async.bulk.tensor.3d.shared::cluster.global.mbarrier::complete_tx::bytes [%0], [%1, {%3, %4, %5}], [%2];"
               :: "r"(dst), "l"(m), "r"(bar), "r"(c0), "r"(c1), "r"(c2) : "memory");
}
__device__ __forceinline__ void bulk_ld(uint32_t dst, const void* src, uint32_t bytes, uint32_t bar) {
  asm volatile("cp.async.bulk.shared::cluster.global.mbarrier::complete_tx::bytes [%0], [%1], %2, [%3];"
               :: "r"(dst), "l"(src), "r"(bytes), "r"(bar) : "memory");
}
__device__ __forceinline__ void bulk_st(void* dst, uint32_t src, uint32_t bytes) {
  asm volatile("cp.async.bulk.global.shared::cta.bulk_group [%0], [%1], %2;" :: "l"(dst), "r"(src), "r"(bytes) : "memory");
}
__device__ __forceinline__ void tma_st2(const CUtensorMap* m, uint32_t src, int c0, int c1) {
  asm volatile("cp.async.bulk.tensor.2d.global.shared::cta.bulk_group [%0, {%2, %3}], [%1];"
               :: "l"(m), "r"(src), "r"(c0), "r"(c1) : "memory");
}
__device__ __forceinline__ void tma_red2(const CUtensorMap* m, uint32_t src, int c0, int c1) {
  asm volatile("cp.reduce.async.bulk.tensor.2d.global.shared::cta.add.tile.bulk_group [%0, {%2, %3}], [%1];"
               :: "l"(m), "r"(src), "r"(c0), "r"(c1) : "memory");
}
__device__ __forceinline__ void tma_pf2(const CUtensorMap* m, int c0, int c1) {
  asm volatile("cp.async.bulk.prefetch.tensor.2d.L2.global.tile [%0, {%1, %2}];" :: "l"(m), "r"(c0), "r"(c1) : "memory");
}
__device__ __forceinline__ void bulk_prefetch(const void* src, uint32_t bytes) {
  asm volatile("cp.async.bulk.prefetch.L2.global [%0], %1;" :: "l"(src), "r"(bytes) : "memory");
}
__device__ __forceinline__ void bulk_commit() { asm volatile("cp.async.bulk.commit_group;" ::: "memory"); }
__device__ __forceinline__ void bulk_wait_read() { asm volatile("cp.async.bulk.wait_group.read 0;" ::: "memory"); }
__device__ __forceinline__ void bulk_wait_all() { asm volatile("cp.async.bulk.wait_group 0;" ::: "memory"); }
__device__ __forceinline__ void prefetch_map(const CUtensorMap* m) { asm volatile("prefetch.tensormap [%0];" :: "l"(m) : "memory"); }
__device__ __forceinline__ void wg_fence() { asm volatile("wgmma.fence.sync.aligned;" ::: "memory"); }
__device__ __forceinline__ void wg_commit() { asm volatile("wgmma.commit_group.sync.aligned;" ::: "memory"); }
template <int N> __device__ __forceinline__ void wg_wait() { asm volatile("wgmma.wait_group.sync.aligned %0;" :: "n"(N) : "memory"); }
template <int N> __device__ __forceinline__ void reg_fence(float (&d)[N]) {
#pragma unroll
  for (int i = 0; i < N; i++) asm volatile("" : "+f"(d[i]) :: "memory");
}
template <int N> __device__ __forceinline__ void reg_fence(uint32_t (&d)[N]) {
#pragma unroll
  for (int i = 0; i < N; i++) asm volatile("" : "+r"(d[i]) :: "memory");
}
__device__ __forceinline__ uint32_t fresh_tid() { uint32_t t; asm volatile("mov.u32 %0, %%tid.x;" : "=r"(t)); return t; }
__device__ __forceinline__ uint32_t lane_base16() {
  const uint32_t t = fresh_tid(), lane = t & 31, wq = (t >> 5) & 3;
  return (16 * wq + (lane & 7) + 8 * ((lane >> 3) & 1)) * 128 + (((lane >> 4) ^ (lane & 7)) << 4);
}
__device__ __forceinline__ void named_sync(int id, int n) { asm volatile("bar.sync %0, %1;" :: "r"(id), "r"(n) : "memory"); }
__device__ __forceinline__ void named_arrive(int id, int n) { asm volatile("bar.arrive %0, %1;" :: "r"(id), "r"(n) : "memory"); }
__device__ __forceinline__ uint32_t pack_bf16(float lo, float hi) {
  uint32_t r; asm("cvt.rn.bf16x2.f32 %0, %1, %2;" : "=r"(r) : "f"(hi), "f"(lo)); return r;
}
__device__ __forceinline__ float ex2(float x) { float y; asm("ex2.approx.ftz.f32 %0, %1;" : "=f"(y) : "f"(x)); return y; }
__device__ __forceinline__ void stsm4(uint32_t addr, uint32_t a, uint32_t b, uint32_t c, uint32_t d) {
  asm volatile("stmatrix.sync.aligned.m8n8.x4.shared.b16 [%0], {%1, %2, %3, %4};" :: "r"(addr), "r"(a), "r"(b), "r"(c), "r"(d) : "memory");
}
__device__ __forceinline__ void stsm4t(uint32_t addr, uint32_t a, uint32_t b, uint32_t c, uint32_t d) {
  asm volatile("stmatrix.sync.aligned.m8n8.x4.trans.shared.b16 [%0], {%1, %2, %3, %4};" :: "r"(addr), "r"(a), "r"(b), "r"(c), "r"(d) : "memory");
}
__device__ __forceinline__ uint64_t mk_desc(uint32_t addr, uint32_t lbo, uint32_t sbo) {
  return (uint64_t)(((addr & 0x3FFFF) >> 4) | ((lbo >> 4) << 16)) | ((uint64_t)((sbo >> 4) | (1u << 30)) << 32);
}
__device__ __forceinline__ uint64_t desc_k(uint32_t addr)  { return mk_desc(addr, 16, 1024); }
__device__ __forceinline__ uint64_t desc_mn(uint32_t addr) { return mk_desc(addr, 8192, 1024); }
__device__ __forceinline__ uint64_t desc_add(uint64_t d, uint32_t bytes) { return d + (bytes >> 4); }

__device__ __forceinline__ void wgmma_ss_n256_tb(float (&d)[128], uint64_t da, uint64_t db, int sd) {
  asm volatile("{\n.reg .pred p;\nsetp.ne.b32 p, %130, 0;\n"
    "wgmma.mma_async.sync.aligned.m64n256k16.f32.bf16.bf16 "
    "{%0, %1, %2, %3, %4, %5, %6, %7, %8, %9, %10, %11, %12, %13, %14, %15, "
    "%16, %17, %18, %19, %20, %21, %22, %23, %24, %25, %26, %27, %28, %29, %30, %31, "
    "%32, %33, %34, %35, %36, %37, %38, %39, %40, %41, %42, %43, %44, %45, %46, %47, "
    "%48, %49, %50, %51, %52, %53, %54, %55, %56, %57, %58, %59, %60, %61, %62, %63, "
    "%64, %65, %66, %67, %68, %69, %70, %71, %72, %73, %74, %75, %76, %77, %78, %79, "
    "%80, %81, %82, %83, %84, %85, %86, %87, %88, %89, %90, %91, %92, %93, %94, %95, "
    "%96, %97, %98, %99, %100, %101, %102, %103, %104, %105, %106, %107, %108, %109, %110, %111, "
    "%112, %113, %114, %115, %116, %117, %118, %119, %120, %121, %122, %123, %124, %125, %126, %127}, "
    "%128, %129, p, 1, 1, 0, 1;\n}"
    : "+f"(d[0]), "+f"(d[1]), "+f"(d[2]), "+f"(d[3]), "+f"(d[4]), "+f"(d[5]), "+f"(d[6]), "+f"(d[7]),
      "+f"(d[8]), "+f"(d[9]), "+f"(d[10]), "+f"(d[11]), "+f"(d[12]), "+f"(d[13]), "+f"(d[14]), "+f"(d[15]),
      "+f"(d[16]), "+f"(d[17]), "+f"(d[18]), "+f"(d[19]), "+f"(d[20]), "+f"(d[21]), "+f"(d[22]), "+f"(d[23]),
      "+f"(d[24]), "+f"(d[25]), "+f"(d[26]), "+f"(d[27]), "+f"(d[28]), "+f"(d[29]), "+f"(d[30]), "+f"(d[31]),
      "+f"(d[32]), "+f"(d[33]), "+f"(d[34]), "+f"(d[35]), "+f"(d[36]), "+f"(d[37]), "+f"(d[38]), "+f"(d[39]),
      "+f"(d[40]), "+f"(d[41]), "+f"(d[42]), "+f"(d[43]), "+f"(d[44]), "+f"(d[45]), "+f"(d[46]), "+f"(d[47]),
      "+f"(d[48]), "+f"(d[49]), "+f"(d[50]), "+f"(d[51]), "+f"(d[52]), "+f"(d[53]), "+f"(d[54]), "+f"(d[55]),
      "+f"(d[56]), "+f"(d[57]), "+f"(d[58]), "+f"(d[59]), "+f"(d[60]), "+f"(d[61]), "+f"(d[62]), "+f"(d[63]),
      "+f"(d[64]), "+f"(d[65]), "+f"(d[66]), "+f"(d[67]), "+f"(d[68]), "+f"(d[69]), "+f"(d[70]), "+f"(d[71]),
      "+f"(d[72]), "+f"(d[73]), "+f"(d[74]), "+f"(d[75]), "+f"(d[76]), "+f"(d[77]), "+f"(d[78]), "+f"(d[79]),
      "+f"(d[80]), "+f"(d[81]), "+f"(d[82]), "+f"(d[83]), "+f"(d[84]), "+f"(d[85]), "+f"(d[86]), "+f"(d[87]),
      "+f"(d[88]), "+f"(d[89]), "+f"(d[90]), "+f"(d[91]), "+f"(d[92]), "+f"(d[93]), "+f"(d[94]), "+f"(d[95]),
      "+f"(d[96]), "+f"(d[97]), "+f"(d[98]), "+f"(d[99]), "+f"(d[100]), "+f"(d[101]), "+f"(d[102]), "+f"(d[103]),
      "+f"(d[104]), "+f"(d[105]), "+f"(d[106]), "+f"(d[107]), "+f"(d[108]), "+f"(d[109]), "+f"(d[110]), "+f"(d[111]),
      "+f"(d[112]), "+f"(d[113]), "+f"(d[114]), "+f"(d[115]), "+f"(d[116]), "+f"(d[117]), "+f"(d[118]), "+f"(d[119]),
      "+f"(d[120]), "+f"(d[121]), "+f"(d[122]), "+f"(d[123]), "+f"(d[124]), "+f"(d[125]), "+f"(d[126]), "+f"(d[127])
    : "l"(da), "l"(db), "r"(sd));
}
__device__ __forceinline__ void wgmma_ss_n64(float (&d)[32], uint64_t da, uint64_t db, int sd) {
  asm volatile("{\n.reg .pred p;\nsetp.ne.b32 p, %34, 0;\n"
    "wgmma.mma_async.sync.aligned.m64n64k16.f32.bf16.bf16 "
    "{%0, %1, %2, %3, %4, %5, %6, %7, %8, %9, %10, %11, %12, %13, %14, %15, "
    "%16, %17, %18, %19, %20, %21, %22, %23, %24, %25, %26, %27, %28, %29, %30, %31}, "
    "%32, %33, p, 1, 1, 0, 0;\n}"
    : "+f"(d[0]), "+f"(d[1]), "+f"(d[2]), "+f"(d[3]), "+f"(d[4]), "+f"(d[5]), "+f"(d[6]), "+f"(d[7]),
      "+f"(d[8]), "+f"(d[9]), "+f"(d[10]), "+f"(d[11]), "+f"(d[12]), "+f"(d[13]), "+f"(d[14]), "+f"(d[15]),
      "+f"(d[16]), "+f"(d[17]), "+f"(d[18]), "+f"(d[19]), "+f"(d[20]), "+f"(d[21]), "+f"(d[22]), "+f"(d[23]),
      "+f"(d[24]), "+f"(d[25]), "+f"(d[26]), "+f"(d[27]), "+f"(d[28]), "+f"(d[29]), "+f"(d[30]), "+f"(d[31])
    : "l"(da), "l"(db), "r"(sd));
}
__device__ __forceinline__ void wgmma_rs_n256_tb(float (&d)[128], uint32_t a0, uint32_t a1, uint32_t a2, uint32_t a3, uint64_t db, int sd) {
  asm volatile("{\n.reg .pred p;\nsetp.ne.b32 p, %133, 0;\n"
    "wgmma.mma_async.sync.aligned.m64n256k16.f32.bf16.bf16 "
    "{%0, %1, %2, %3, %4, %5, %6, %7, %8, %9, %10, %11, %12, %13, %14, %15, "
    "%16, %17, %18, %19, %20, %21, %22, %23, %24, %25, %26, %27, %28, %29, %30, %31, "
    "%32, %33, %34, %35, %36, %37, %38, %39, %40, %41, %42, %43, %44, %45, %46, %47, "
    "%48, %49, %50, %51, %52, %53, %54, %55, %56, %57, %58, %59, %60, %61, %62, %63, "
    "%64, %65, %66, %67, %68, %69, %70, %71, %72, %73, %74, %75, %76, %77, %78, %79, "
    "%80, %81, %82, %83, %84, %85, %86, %87, %88, %89, %90, %91, %92, %93, %94, %95, "
    "%96, %97, %98, %99, %100, %101, %102, %103, %104, %105, %106, %107, %108, %109, %110, %111, "
    "%112, %113, %114, %115, %116, %117, %118, %119, %120, %121, %122, %123, %124, %125, %126, %127}, "
    "{%128, %129, %130, %131}, %132, p, 1, 1, 1;\n}"
    : "+f"(d[0]), "+f"(d[1]), "+f"(d[2]), "+f"(d[3]), "+f"(d[4]), "+f"(d[5]), "+f"(d[6]), "+f"(d[7]),
      "+f"(d[8]), "+f"(d[9]), "+f"(d[10]), "+f"(d[11]), "+f"(d[12]), "+f"(d[13]), "+f"(d[14]), "+f"(d[15]),
      "+f"(d[16]), "+f"(d[17]), "+f"(d[18]), "+f"(d[19]), "+f"(d[20]), "+f"(d[21]), "+f"(d[22]), "+f"(d[23]),
      "+f"(d[24]), "+f"(d[25]), "+f"(d[26]), "+f"(d[27]), "+f"(d[28]), "+f"(d[29]), "+f"(d[30]), "+f"(d[31]),
      "+f"(d[32]), "+f"(d[33]), "+f"(d[34]), "+f"(d[35]), "+f"(d[36]), "+f"(d[37]), "+f"(d[38]), "+f"(d[39]),
      "+f"(d[40]), "+f"(d[41]), "+f"(d[42]), "+f"(d[43]), "+f"(d[44]), "+f"(d[45]), "+f"(d[46]), "+f"(d[47]),
      "+f"(d[48]), "+f"(d[49]), "+f"(d[50]), "+f"(d[51]), "+f"(d[52]), "+f"(d[53]), "+f"(d[54]), "+f"(d[55]),
      "+f"(d[56]), "+f"(d[57]), "+f"(d[58]), "+f"(d[59]), "+f"(d[60]), "+f"(d[61]), "+f"(d[62]), "+f"(d[63]),
      "+f"(d[64]), "+f"(d[65]), "+f"(d[66]), "+f"(d[67]), "+f"(d[68]), "+f"(d[69]), "+f"(d[70]), "+f"(d[71]),
      "+f"(d[72]), "+f"(d[73]), "+f"(d[74]), "+f"(d[75]), "+f"(d[76]), "+f"(d[77]), "+f"(d[78]), "+f"(d[79]),
      "+f"(d[80]), "+f"(d[81]), "+f"(d[82]), "+f"(d[83]), "+f"(d[84]), "+f"(d[85]), "+f"(d[86]), "+f"(d[87]),
      "+f"(d[88]), "+f"(d[89]), "+f"(d[90]), "+f"(d[91]), "+f"(d[92]), "+f"(d[93]), "+f"(d[94]), "+f"(d[95]),
      "+f"(d[96]), "+f"(d[97]), "+f"(d[98]), "+f"(d[99]), "+f"(d[100]), "+f"(d[101]), "+f"(d[102]), "+f"(d[103]),
      "+f"(d[104]), "+f"(d[105]), "+f"(d[106]), "+f"(d[107]), "+f"(d[108]), "+f"(d[109]), "+f"(d[110]), "+f"(d[111]),
      "+f"(d[112]), "+f"(d[113]), "+f"(d[114]), "+f"(d[115]), "+f"(d[116]), "+f"(d[117]), "+f"(d[118]), "+f"(d[119]),
      "+f"(d[120]), "+f"(d[121]), "+f"(d[122]), "+f"(d[123]), "+f"(d[124]), "+f"(d[125]), "+f"(d[126]), "+f"(d[127])
    : "r"(a0), "r"(a1), "r"(a2), "r"(a3), "l"(db), "r"(sd));
}
__device__ __forceinline__ void wgmma_rs_n64_tb(float (&d)[32], uint32_t a0, uint32_t a1, uint32_t a2, uint32_t a3, uint64_t db, int sd) {
  asm volatile("{\n.reg .pred p;\nsetp.ne.b32 p, %37, 0;\n"
    "wgmma.mma_async.sync.aligned.m64n64k16.f32.bf16.bf16 "
    "{%0, %1, %2, %3, %4, %5, %6, %7, %8, %9, %10, %11, %12, %13, %14, %15, "
    "%16, %17, %18, %19, %20, %21, %22, %23, %24, %25, %26, %27, %28, %29, %30, %31}, "
    "{%32, %33, %34, %35}, %36, p, 1, 1, 1;\n}"
    : "+f"(d[0]), "+f"(d[1]), "+f"(d[2]), "+f"(d[3]), "+f"(d[4]), "+f"(d[5]), "+f"(d[6]), "+f"(d[7]),
      "+f"(d[8]), "+f"(d[9]), "+f"(d[10]), "+f"(d[11]), "+f"(d[12]), "+f"(d[13]), "+f"(d[14]), "+f"(d[15]),
      "+f"(d[16]), "+f"(d[17]), "+f"(d[18]), "+f"(d[19]), "+f"(d[20]), "+f"(d[21]), "+f"(d[22]), "+f"(d[23]),
      "+f"(d[24]), "+f"(d[25]), "+f"(d[26]), "+f"(d[27]), "+f"(d[28]), "+f"(d[29]), "+f"(d[30]), "+f"(d[31])
    : "r"(a0), "r"(a1), "r"(a2), "r"(a3), "l"(db), "r"(sd));
}
__device__ __forceinline__ void wgmma_rs_n64(float (&d)[32], uint32_t a0, uint32_t a1, uint32_t a2, uint32_t a3, uint64_t db, int sd) {
  asm volatile("{\n.reg .pred p;\nsetp.ne.b32 p, %37, 0;\n"
    "wgmma.mma_async.sync.aligned.m64n64k16.f32.bf16.bf16 "
    "{%0, %1, %2, %3, %4, %5, %6, %7, %8, %9, %10, %11, %12, %13, %14, %15, "
    "%16, %17, %18, %19, %20, %21, %22, %23, %24, %25, %26, %27, %28, %29, %30, %31}, "
    "{%32, %33, %34, %35}, %36, p, 1, 1, 0;\n}"
    : "+f"(d[0]), "+f"(d[1]), "+f"(d[2]), "+f"(d[3]), "+f"(d[4]), "+f"(d[5]), "+f"(d[6]), "+f"(d[7]),
      "+f"(d[8]), "+f"(d[9]), "+f"(d[10]), "+f"(d[11]), "+f"(d[12]), "+f"(d[13]), "+f"(d[14]), "+f"(d[15]),
      "+f"(d[16]), "+f"(d[17]), "+f"(d[18]), "+f"(d[19]), "+f"(d[20]), "+f"(d[21]), "+f"(d[22]), "+f"(d[23]),
      "+f"(d[24]), "+f"(d[25]), "+f"(d[26]), "+f"(d[27]), "+f"(d[28]), "+f"(d[29]), "+f"(d[30]), "+f"(d[31])
    : "r"(a0), "r"(a1), "r"(a2), "r"(a3), "l"(db), "r"(sd));
}

__device__ __forceinline__ uint4 lds16(uint32_t a) {
  uint4 v; asm volatile("ld.shared.v4.u32 {%0, %1, %2, %3}, [%4];" : "=r"(v.x), "=r"(v.y), "=r"(v.z), "=r"(v.w) : "r"(a) : "memory"); return v;
}
__device__ __forceinline__ void sts16(uint32_t a, uint32_t x, uint32_t y, uint32_t z, uint32_t w) {
  asm volatile("st.shared.v4.u32 [%0], {%1, %2, %3, %4};" :: "r"(a), "r"(x), "r"(y), "r"(z), "r"(w) : "memory");
}
__device__ __forceinline__ uint32_t lds4(uint32_t a) { uint32_t v; asm volatile("ld.shared.u32 %0, [%1];" : "=r"(v) : "r"(a) : "memory"); return v; }
__device__ __forceinline__ uint32_t lds4v(uint32_t a) { uint32_t v; asm volatile("ld.volatile.shared.u32 %0, [%1];" : "=r"(v) : "r"(a) : "memory"); return v; }
__device__ __forceinline__ uint32_t bmul(uint32_t a, uint32_t b) { uint32_t r; asm("mul.rn.bf16x2 %0, %1, %2;" : "=r"(r) : "r"(a), "r"(b)); return r; }
__device__ __forceinline__ uint32_t badd(uint32_t a, uint32_t b) { uint32_t r; asm("add.rn.bf16x2 %0, %1, %2;" : "=r"(r) : "r"(a), "r"(b)); return r; }

__device__ __forceinline__ uint32_t add_skip(uint32_t y, uint32_t x, uint32_t d) { return badd(y, bmul(x, d)); }
__device__ __forceinline__ void ldsm4(uint32_t (&r)[4], uint32_t a) {
  asm volatile("ldmatrix.sync.aligned.m8n8.x4.shared.b16 {%0, %1, %2, %3}, [%4];" : "=r"(r[0]), "=r"(r[1]), "=r"(r[2]), "=r"(r[3]) : "r"(a) : "memory");
}
__device__ __forceinline__ void ldsm4t(uint32_t (&r)[4], uint32_t a) {
  asm volatile("ldmatrix.sync.aligned.m8n8.x4.trans.shared.b16 {%0, %1, %2, %3}, [%4];" : "=r"(r[0]), "=r"(r[1]), "=r"(r[2]), "=r"(r[3]) : "r"(a) : "memory");
}
__device__ __forceinline__ uint32_t transpose8(uint32_t a) { uint32_t d; asm volatile("movmatrix.sync.aligned.m8n8.trans.b16 %0, %1;" : "=r"(d) : "r"(a)); return d; }

__device__ __forceinline__ void mma16816(float (&d)[4], const uint32_t (&a)[4], uint32_t b0, uint32_t b1) {
  asm volatile("mma.sync.aligned.m16n8k16.row.col.f32.bf16.bf16.f32 {%0, %1, %2, %3}, {%4, %5, %6, %7}, {%8, %9}, {%0, %1, %2, %3};"
               : "+f"(d[0]), "+f"(d[1]), "+f"(d[2]), "+f"(d[3]) : "r"(a[0]), "r"(a[1]), "r"(a[2]), "r"(a[3]), "r"(b0), "r"(b1));
}

#define STG_K1 2
#define STG_K2 10
#define STG_Q1 1
#define STG_Q2 5
#define PACE_A 400
#define PACE_B 100
#define PF_QA 48
#define PF_CV 64
#define PF_X 8
#define PF_WO 11
#define Q_PRE 2
#define ARRIVE_KK 12
#define SIDE_DELAY_NS 2000
#define EARLY_LD 2
#define HI_ORDER 9
constexpr int PP_BAR = 3;
template <int V> struct Int { static constexpr int value = V; };
struct Ring {
  uint32_t slot, phase;
  __device__ __forceinline__ void next() { if (++slot == NSLOT) { slot = 0; phase ^= 1; } }
};
__device__ __forceinline__ uint32_t bar_addr(uint32_t sb, uint32_t i) { return sb + BARS + 8 * i; }
__device__ __forceinline__ uint32_t q_region(uint32_t sb, int w) { return sb + QREG + (w ^ 1) * 32768; }

struct Role { int h, j; };
__device__ __forceinline__ Role get_role() {
  int cta; asm volatile("mov.u32 %0, %%ctaid.x;" : "=r"(cta));
  const int c = cta >> 1;
  int h, u;
  const int a = c - 4, b = c - 36, q = (b * 37) >> 8;
  h = a < 0 ? 8 : b < 0 ? a & 7 : 9 + b - 7 * q;
  u = a < 0 ? c : b < 0 ? a >> 3 : q;
  return Role{h, 2 * u + (cta & 1)};
}
__device__ __forceinline__ int fresh_warp() { return __shfl_sync(0xffffffffu, fresh_tid() >> 5, 0); }

__device__ __forceinline__ int q_tile(int h, int j, int which) { return ((h < 8) == (which == 0)) ? 15 - j : j; }

__device__ __forceinline__ int o_chunk(int h, int c) { const int x = c + (h & 7); return x % 7; }

__device__ __forceinline__ int kv_block(int j, int t) { return j + 8 * ((HI_ORDER >> t) & 1); }
__device__ __forceinline__ uint8_t* kv_tile(const Params& p, int v, int h, int tile) {
  return p.kv + (size_t)((v * NH + h) * 32 + tile) * 32768;
}

__device__ __forceinline__ void ring_acquire(uint32_t sb, Ring& r, uint32_t bytes) {
  mbar_wait(bar_addr(sb, B_RG_EMPTY + r.slot), r.phase ^ 1);
  mbar_expect_tx(bar_addr(sb, B_RG_FULL + r.slot), bytes);
}
__device__ __forceinline__ void producer_main(const Params& p, uint32_t sb) {
  const Role ro = get_role();
  const int h = ro.h, j = ro.j;
  for (int it = EARLY_LD; it < 71; it++) {
    const int t = it >> 4, k = it & 15, s = it & 3;
    mbar_wait(bar_addr(sb, B_P1_EMPTY + s), ((it >> 2) & 1) ^ 1);
    const uint32_t full = bar_addr(sb, B_P1_FULL + s), dst = sb + s * P1_STAGE;
    mbar_expect_tx(full, P1_STAGE);
    if (t < 4) {
      tma_ld2(dst, &p.ckv, full, k * 64, kv_block(j, t) * 128);
      tma_ld3(dst + 16384, (t >> 1) ? &p.wuv : &p.wuk, full, 0, k * 64, h * 4);
    } else {
      tma_ld2(dst, &p.x, full, k * 64, q_tile(h, j, 0) * 128);
      tma_ld3(dst + 16384, &p.wq, full, 0, k * 64, h * 4);
    }
    if (it >= PF_QA && it < PF_QA + 14) {
      const int i = it - PF_QA;
      bulk_prefetch(p.b_x + (size_t)(q_tile(h, j, 0) * 128 + (h & 7) * 16) * DM + i * 512, 1024);
      tma_pf2(&p.wqp, h * HD, (i * 8 + j) * 4);
    }
    if (it >= PF_CV && it < PF_CV + 3) {
      mbar_wait(bar_addr(sb, B_XS), 0);
      bulk_prefetch(g_xs + (size_t)(h * 8 + j) * CV_BYTES + (it - PF_CV) * (CV_BYTES / 3), CV_BYTES / 3);
    }
  }
  mbar_wait(bar_addr(sb, B_P1_EMPTY + 3), 0);
  mbar_wait(bar_addr(sb, B_XS), 0);
  mbar_expect_tx(bar_addr(sb, B_RG_FULL + 4), CV_BYTES);
  bulk_ld(sb + CV_X, g_xs + (size_t)(h * 8 + j) * CV_BYTES, CV_BYTES, bar_addr(sb, B_RG_FULL + 4));
  Ring r{0, 1};
  auto prefetch_wo = [&](int left) {
    const int i = PF_WO - left;
    if (PF_WO && i >= 0 && i < 8) bulk_prefetch(p.b_wo + (size_t)(h * HD + j * 32 + 4 * i) * DM, 4 * DM * 2);
  };
  mbar_wait(bar_addr(sb, B_KV), 0);
  for (int which = 0; which < 2; which++) {
    const int qt = q_tile(h, j, which);
    if (which == 1) {
      for (int kc = 0; kc < 7; kc++) {
        prefetch_wo(4 * qt + 4 + 7 - kc);
        ring_acquire(sb, r, 32768);
        tma_ld3(sb + r.slot * SLOT, &p.wq, bar_addr(sb, B_RG_FULL + r.slot), 0, kc * 64, h * 4);
        r.next();
        if (kc == 0 || (kc & 1)) {
          ring_acquire(sb, r, kc == 0 ? 16384 : 32768);
          const uint32_t full = bar_addr(sb, B_RG_FULL + r.slot), dst = sb + r.slot * SLOT;
          tma_ld2(dst, &p.x, full, kc * 64, qt * 128);
          if (kc > 0) tma_ld2(dst + 16384, &p.x, full, kc * 64 + 64, qt * 128);
          r.next();
        }
      }
    }
    const int n = 2 * qt + 2;
    for (int f = 0; f < 2 * n; f++) {
      if (which == 0) {
        const int i = f - max(2 * n - PF_X, 0);
        if (PF_X && i >= 0 && i < 4) bulk_prefetch(p.b_x + (size_t)((15 - qt) * 128 + (h & 7) * 16 + 4 * i) * DM, 4 * DM * 2);
      } else prefetch_wo(2 * n - f);
      const bool isK = (f == 0) || ((f & 1) && f < 2 * n - 1);
      const int i = isK ? (f + 1) >> 1 : (f == 2 * n - 1 ? n - 1 : (f >> 1) - 1);
      const int tile = which ? n - 1 - i : i;
      if (!isK) mbar_wait(bar_addr(sb, B_KV + 1 + ((tile >> 4) ^ ((HI_ORDER >> 2) & 1))), 0);
      if (which == 0 && f < 2) mbar_wait(bar_addr(sb, B_P1_EMPTY + f), 1);
      ring_acquire(sb, r, 32768);
      bulk_ld(sb + r.slot * SLOT, kv_tile(p, !isK, h, tile), 32768, bar_addr(sb, B_RG_FULL + r.slot));
      r.next();
    }
  }
  for (int i = 0; i < 14; i++) {
    ring_acquire(sb, r, 32768);
    tma_ld2(sb + r.slot * SLOT, &p.wo, bar_addr(sb, B_RG_FULL + r.slot), o_chunk(h, i >> 1) * 64, ((i & 1) ? h ^ 8 : h) * HD);
    r.next();
  }
}

__device__ __forceinline__ void storer_main(const Params& p, uint32_t sb) {
  const Role ro = get_role();
  const int h = ro.h, j = ro.j, w = fresh_warp() - 1;
  const uint32_t full = bar_addr(sb, B_ST_FULL + w), empty = bar_addr(sb, B_ST_EMPTY + w);
  const int lane = threadIdx.x & 31;
  const unsigned epoch = load_epoch();
  if (lane == 0) {
    for (int job = 0; job < 8; job++) {
      const int t = job >> 1;
      uint8_t* dst = kv_tile(p, t >> 1, h, 2 * kv_block(j, t) + w) + (job & 1) * 16384;
      mbar_wait_nap(full, job & 1);
      for (int i = 0; i < 8; i++) {
        if (i) __nanosleep(job < 6 ? PACE_A : PACE_B);
        bulk_st(dst + i * 2048, sb + P1_STG + w * 16384 + i * 2048, 2048);
      }
      bulk_commit();
      bulk_wait_read();
      mbar_arrive(empty);
      if (job >= 3 && (job & 1)) { bulk_wait_all(); flag_signal(&g_flags.kv_ready[3 * h + t - 1].v); }
    }
  }
  __syncwarp();
  const int cta = h * 8 + j, qt = q_tile(h, j, 1);
  const uint32_t qreg = q_region(sb, w);
  {
    mbar_wait_nap(bar_addr(sb, B_CTXS + 4 * w), 0);
    uint4* z = reinterpret_cast<uint4*>(p.out + (size_t)(qt * 128 + w * 64 + (h & 7) * 8 + (lane >> 2)) * OUTW + DA) + (lane & 3);
#pragma unroll
    for (int i = 0; i < 14; i++) z[4 * i] = make_uint4(0, 0, 0, 0);
    __syncwarp();
    if (lane != 0) return;
    for (int b = 0; b < 4; b++) {
      mbar_wait(bar_addr(sb, B_CTXS + 4 * w + b), 0);
      bulk_st(p.ctx + (size_t)(cta * 2 + w) * 32768 + b * 8192, qreg + b * 8192, 8192);
      bulk_commit();
    }
    bulk_wait_read();
    mbar_arrive(empty);
    bulk_wait_all();
    flag_signal(&g_flags.ctx_ready[cta * 2 + w].v);
    flag_signal_after_bulk(&g_flags.out_ready[qt * 2 + w].v);
  }
  {
    const int wx = w ^ 1;
    flag_wait(&g_flags.ctx_ready[(cta ^ 64) * 2 + wx].v, 1, epoch);
    flag_wait(&g_flags.out_ready[qt * 2 + wx].v, 8, epoch);
    fence_async_all();
    mbar_wait_nap(bar_addr(sb, B_QFREE + w), 0);
    mbar_expect_tx(bar_addr(sb, B_CTXF + w), 32768);
    bulk_ld(qreg, p.ctx + (size_t)((cta ^ 64) * 2 + wx) * 32768, 32768, bar_addr(sb, B_CTXF + w));
    for (int ch = 0; ch < 7; ch++) {
      const int b = ch & 1;
      mbar_wait(bar_addr(sb, B_S2_FULL + w * 2 + b), (ch >> 1) & 1);
      tma_red2(&p.part, qreg + b * 8192, DA + o_chunk(h, ch) * 64, qt * 128 + wx * 64);
      bulk_commit();
      if (ch == 0 && w == 1) mbar_arrive(bar_addr(sb, B_GFREE));
      bulk_wait_read();
      mbar_arrive(bar_addr(sb, B_S2_EMPTY + w * 2 + b));
    }
  }
}

template <int OFF, int NB, int NREG>
__device__ __forceinline__ void store_blocks(uint32_t base, uint32_t lanebase, const uint32_t (&pk)[NREG]) {
#pragma unroll
  for (int J = 0; J < NB * 8; J += 2) {
    const uint32_t a = base + (J >> 3) * 8192 + (lanebase ^ ((J & 7) << 4));
    stsm4(a, pk[OFF + 2 * J], pk[OFF + 2 * J + 1], pk[OFF + 2 * J + 2], pk[OFF + 2 * J + 3]);
  }
}
__device__ __forceinline__ void warp_arrive(uint32_t bar, int lane) { __syncwarp(); if (lane == 0) mbar_arrive(bar); }
__device__ __forceinline__ void release(uint32_t bar, int lane) { lane0_arrive(bar, 1, lane); }

template <int W> __device__ __forceinline__ constexpr int cv_tile(int u) { return 2 * u + ((u ^ W) & 1); }
__device__ __forceinline__ uint32_t cv_x_lane(uint32_t lane) { return (16 + (lane & 15) - (lane >> 4)) * 16; }
__device__ __forceinline__ uint32_t cv_h_lane(uint32_t lane, uint32_t hE, uint32_t hO) {
  const uint32_t g = lane >> 2, c = lane & 3;
  return (g & 1) ? hO + (15 + 2 * c - g) * 2 : hE + (16 + 2 * c - g) * 2;
}
template <int W>
__device__ __forceinline__ void conv_mma(float (&ca)[8][4], uint32_t xa, uint32_t ha, uint32_t sb, uint32_t lb, const uint32_t (&pk)[64], uint32_t one) {
  constexpr int N = 16 - W;
  uint32_t fx[N][4], fh[N][2];
  auto ld_h = [&](int i, int rr) { fh[i][0] = lds4(ha + i * 256 + rr * 128); fh[i][1] = lds4(ha + i * 256 + rr * 128 + 16); };
  uint32_t c1 = 0, c3 = 0;
  ldsm4(fx[0], xa);
#pragma unroll
  for (int u = 0; u < 8; u++) ld_h(cv_tile<W>(u), 0);
  ldsm4(fx[1], xa + 256);
#pragma unroll
  for (int u = 0; u < 8; u++) if (cv_tile<W ^ 1>(u) < N) ld_h(cv_tile<W ^ 1>(u), 0);
#pragma unroll
  for (int i = 2; i < N; i++) ldsm4(fx[i], xa + i * 256);
#pragma unroll
  for (int sx = 0; sx < N; sx++) {
#pragma unroll
    for (int u = 0; u < 8; u++) {
      const int jj = cv_tile<W>(u) - sx;
      if (jj >= 0) mma16816(ca[u], fx[sx], fh[jj < 0 ? 0 : jj][0], fh[jj < 0 ? 0 : jj][1]);
    }
    {
      const uint32_t t1 = fx[sx][1], t3 = fx[sx][3];
      fx[sx][1] = fx[sx][0] * one; fx[sx][3] = fx[sx][2] ^ (one - 1); fx[sx][0] = c1 * one; fx[sx][2] = c3 ^ (one - 1);
      c1 = t1; c3 = t3;
    }
    ld_h(N - 1 - sx, 1);
  }
  mbar_wait(bar_addr(sb, B_P1_EMPTY + 2), 1);
  if (W == 0) { mbar_wait(bar_addr(sb, B_ST_EMPTY), 1); mbar_wait(bar_addr(sb, B_ST_EMPTY + 1), 1); }
#pragma unroll
  for (int jj = 15; jj >= 0; jj--) {
    if (W == 0) stsm4(q_region(sb, W) + (jj >> 2) * 8192 + (lb ^ ((jj & 3) << 5)), pk[4 * jj], pk[4 * jj + 1], pk[4 * jj + 2], pk[4 * jj + 3]);
#pragma unroll
    for (int u = 0; u < 8; u++) {
      const int sx = cv_tile<W>(u) - jj;
      if (sx >= 0) mma16816(ca[u], fx[sx < 0 ? 0 : sx], fh[jj < N ? jj : 0][0], fh[jj < N ? jj : 0][1]);
    }
  }
}

__device__ __forceinline__ void consumer_main(const Params& p, uint32_t sb, uint8_t* xs_base, uint32_t one) {
  const int lane = fresh_tid() & 31, w = (fresh_warp() >> 2) - 1;
  const uint32_t lb = lane_base16();
  int qt, cc;
  { const Role ro = get_role(); qt = q_tile(ro.h, ro.j, 0); cc = ro.h * 8 + ro.j; }
  const uint32_t st_full = bar_addr(sb, B_ST_FULL + w), st_empty = bar_addr(sb, B_ST_EMPTY + w);
  const uint32_t stg = sb + P1_STG + w * 16384;

  auto turn_begin = [&]() { named_sync(PP_BAR + w, 256); };
  auto turn_end = [&]() { named_arrive(PP_BAR + (w ^ 1), 256); };
  float acc[128];
#pragma unroll
  for (int i = 0; i < 128; i++) acc[i] = 0.f;
  uint32_t pk[64];
#pragma unroll
  for (int i = 0; i < 64; i++) pk[i] = 0;
  if (fresh_warp() != 4) named_sync(0, NTHREADS);
  const uint32_t qreg = q_region(sb, w);
  for (int t = 0; t < 5; t++) {
    const int nk = t < 4 ? 16 : 7;
#pragma unroll 1
    for (int k = 0; k < nk; k++) {
      const int it = t * 16 + k, s = k & 3;
      if (it == 0) { mbar_wait(bar_addr(sb, B_P1_FULL), 0); turn_begin(); }
      const uint64_t da = desc_k(sb + s * P1_STAGE + w * 8192), db = desc_mn(sb + s * P1_STAGE + 16384);
      wg_fence();
#pragma unroll
      for (int kk = 0; kk < 4; kk++) wgmma_ss_n256_tb(acc, desc_add(da, kk * 32), desc_add(db, kk * 2048), (k | kk) != 0);
      wg_commit();
      turn_end();
      wg_wait<1>();
      if (k > 0) release(bar_addr(sb, B_P1_EMPTY + ((k - 1) & 3)), lane);
      const int k1 = t < 4 ? STG_K1 : STG_Q1, k2 = t < 4 ? STG_K2 : STG_Q2;
      if (t > 0 && (k == k1 || k == k2)) {
        const int job = 2 * (t - 1) + (k != k1);
        mbar_wait(job > 0 ? st_empty : bar_addr(sb, B_SIDE + 1), job > 0 ? (job - 1) & 1 : 0);
        if (k == k1) store_blocks<0, 2>(stg, lb, pk); else store_blocks<32, 2>(stg, lb, pk);
      }
      if (t > 0 && (k == k1 + 1 || k == k2 + 1)) { fence_async_smem(); warp_arrive(st_full, lane); }
      if (it < 70) { mbar_wait(bar_addr(sb, B_P1_FULL + ((k + 1) & 3)), ((it + 1) >> 2) & 1); turn_begin(); }
      else mbar_wait(bar_addr(sb, B_RG_FULL + 4), 0);
    }
    wg_wait<0>();
    reg_fence(acc);
    release(bar_addr(sb, B_P1_EMPTY + ((nk - 1) & 3)), lane);
#pragma unroll
    for (int i = 0; i < 64; i++) pk[i] = pack_bf16(acc[2 * i], acc[2 * i + 1]);
  }
  {
    const uint32_t wq = lb >> 11, ln = lane, cx = sb + CV_X;
    float ca[8][4];
#pragma unroll
    for (int i = 0; i < 8; i++) { ca[i][0] = 0.f; ca[i][1] = 0.f; ca[i][2] = 0.f; ca[i][3] = 0.f; }
    const uint32_t xa = cx + cv_x_lane(ln) - wq * 32, ha = cv_h_lane(ln, cx + CV_HE, cx + CV_HE + CV_HCOPY) + wq * 32;
    if (w) conv_mma<1>(ca, xa, ha, sb, lb, pk, one); else conv_mma<0>(ca, xa, ha, sb, lb, pk, one);
    const uint32_t ex = sb + CV_R + w * 16384 + ln * 16;
#pragma unroll
    for (int u = 0; u < 8; u++)
      sts16(ex + (wq * 8 + u) * 512, __float_as_uint(ca[u][0]), __float_as_uint(ca[u][1]), __float_as_uint(ca[u][2]), __float_as_uint(ca[u][3]));
  }
  auto conv_finish = [&]() {
    const uint32_t wq = lb >> 11, cx = sb + CV_X, ex = sb + CV_R + w * 16384 + lane * 16;
    uint8_t* gz = xs_base + (size_t)cc * CV_BYTES;
    const uint32_t Dd = lds4(cx + CV_D);
#pragma unroll
    for (int e = 0; e < 2; e++) {
      const uint32_t u = 2 * wq + e, nt = 2 * u + ((e ^ w) & 1);
      float y[4] = {0.f, 0.f, 0.f, 0.f};
#pragma unroll
      for (int v = 0; v < 4; v++) {
        const uint4 t = lds16(ex + (v * 8 + u) * 512);
        y[0] += __uint_as_float(t.x); y[1] += __uint_as_float(t.y); y[2] += __uint_as_float(t.z); y[3] += __uint_as_float(t.w);
      }
      const uint32_t o = (16 + 16 * nt) * 16 + lane * 4;
      *reinterpret_cast<uint32_t*>(gz + o)       = badd(pack_bf16(y[0], y[1]), bmul(lds4(cx + o), Dd));
      *reinterpret_cast<uint32_t*>(gz + o + 128) = badd(pack_bf16(y[2], y[3]), bmul(lds4(cx + o + 128), Dd));
    }
    __syncwarp();
    release(bar_addr(sb, B_RG_EMPTY + 3), lane);
    release(bar_addr(sb, B_RG_EMPTY + 4), lane);
    if (lane == 0) mbar_arrive(bar_addr(sb, B_CONV));
  };
  Ring r{0, 1};
  auto take = [&]() { const uint32_t sl = r.slot; mbar_wait(bar_addr(sb, B_RG_FULL + sl), r.phase); r.next(); return sl; };
  constexpr float SC = 0.0625f * 1.4426950408889634f;
  uint32_t ws;
#pragma unroll 1
  for (int which = 0;; which++) {
    float s[32];
#pragma unroll
    for (int i = 0; i < 32; i++) s[i] = 0.f;
    uint32_t pa[16];
    float b0, b1, l0, l1;
    const uint64_t dq = desc_k(qreg);
    uint64_t dk = 0, dqq = 0, dv = 0;
    auto prep_qk = [&](uint32_t kaddr) { dk = desc_k(kaddr); dqq = dq + (kaddr >> 31); asm volatile("" : "+l"(dk), "+l"(dqq)); };
    auto prep_pv = [&](uint32_t vaddr) { dv = desc_mn(vaddr); asm volatile("" : "+l"(dv)); };
    auto issue_qk = [&]() {
#pragma unroll
      for (int kk = 0; kk < 16; kk++)
        wgmma_ss_n64(s, desc_add(dqq, (kk >> 2) * 8192 + (kk & 3) * 32), desc_add(dk, (kk >> 2) * 8192 + (kk & 3) * 32), kk != 0);
    };
    auto issue_pv = [&](int accumulate) {
#pragma unroll
      for (int kk = 0; kk < 4; kk++)
        wgmma_rs_n256_tb(acc, pa[4 * kk], pa[4 * kk + 1], pa[4 * kk + 2], pa[4 * kk + 3], desc_add(dv, kk * 2048), accumulate | kk);
    };
    auto mask_diag = [&]() {
      const int d = (int)((lb >> 11) << 4) + (lane >> 2) - 2 * (lane & 3);
#pragma unroll
      for (int jj = 0; jj < 8; jj++) {
        if (8 * jj > d)     s[4 * jj]     = -INFINITY;
        if (8 * jj + 1 > d) s[4 * jj + 1] = -INFINITY;
        if (8 * jj - 8 > d) s[4 * jj + 2] = -INFINITY;
        if (8 * jj - 7 > d) s[4 * jj + 3] = -INFINITY;
      }
    };
    auto row_max = [&](float& x0, float& x1) {
      x0 = fmaxf(s[0], s[1]); x1 = fmaxf(s[2], s[3]);
#pragma unroll
      for (int jj = 1; jj < 8; jj++) {
        x0 = fmaxf(x0, fmaxf(s[4 * jj], s[4 * jj + 1]));
        x1 = fmaxf(x1, fmaxf(s[4 * jj + 2], s[4 * jj + 3]));
      }
      x0 = fmaxf(x0, __shfl_xor_sync(0xffffffffu, x0, 1));
      x1 = fmaxf(x1, __shfl_xor_sync(0xffffffffu, x1, 1));
      x0 = fmaxf(x0, __shfl_xor_sync(0xffffffffu, x0, 2));
      x1 = fmaxf(x1, __shfl_xor_sync(0xffffffffu, x1, 2));
    };
    auto exps = [&](uint32_t (&pp)[16], float& r0, float& r1) {
      float t0, t1, t2, t3;
#pragma unroll
      for (int jj = 0; jj < 8; jj++) {
        const float e0 = ex2(fmaf(s[4 * jj], SC, b0)), e1 = ex2(fmaf(s[4 * jj + 1], SC, b0));
        const float e2 = ex2(fmaf(s[4 * jj + 2], SC, b1)), e3 = ex2(fmaf(s[4 * jj + 3], SC, b1));
        if (jj == 0) { t0 = e0; t1 = e1; t2 = e2; t3 = e3; } else { t0 += e0; t1 += e1; t2 += e2; t3 += e3; }
        pp[2 * jj] = pack_bf16(e0, e1); pp[2 * jj + 1] = pack_bf16(e2, e3);
      }
      r0 = t0 + t1; r1 = t2 + t3;
    };

    const bool up = w == which;
    const int n = 2 * qt + 2, nw = n - up;
    int fd = which ? 0 : 2 * n - 1;
    const int dir = which ? 1 : -1;
    auto skip = [&]() { r.next(); fd += dir; };
    auto give = [&](uint32_t sl, int d) {
      lane0_arrive(bar_addr(sb, B_RG_EMPTY + sl), (d & ~2) == 0 ? 2 : 1, lane);
    };
    if (which && up) skip();
    uint32_t ks = take();
    prep_qk(sb + ks * SLOT);
    turn_begin();
    wg_fence();
#pragma unroll
    for (int kk = 0; kk < 16; kk++)
      wgmma_rs_n64(s, pk[4 * kk], pk[4 * kk + 1], pk[4 * kk + 2], pk[4 * kk + 3], desc_add(dk, (kk >> 2) * 8192 + (kk & 3) * 32), kk != 0);
    wg_commit();
    turn_end();
    if (!which && up) conv_finish();
    if (which) mbar_wait(st_empty, 0);
    if (!up) store_blocks<0, Q_PRE>(qreg, lb, pk);
    wg_wait<0>();
    reg_fence(s);
    reg_fence(pk);
    give(ks, fd);
    fd += dir;
    if (which && up) { skip(); store_blocks<0, 4>(qreg, lb, pk); }
    if (which || nw == 1) mask_diag();
    row_max(b0, b1);
    if (!up) store_blocks<16 * Q_PRE, 4 - Q_PRE>(qreg + Q_PRE * 8192, lb, pk);
    b0 *= -SC; b1 *= -SC;
#pragma unroll
    for (int i = 0; i < 128; i++) acc[i] = 0.f;
    exps(pa, l0, l1);
    if (!which && !up) conv_finish();
    if (which && nw == 1) { fence_async_smem(); warp_arrive(bar_addr(sb, B_QFREE + w), lane); }
#pragma unroll 1
    for (int jj = 1; jj < nw; jj++) {
      ks = take();
      const uint32_t vs = take();
      if (jj == 1) fence_async_smem();
#pragma unroll
      for (int i = 0; i < 32; i++) s[i] = 0.f;
      prep_qk(sb + ks * SLOT);
      prep_pv(sb + vs * SLOT);
      turn_begin();
      wg_fence();
      issue_qk();
      wg_commit();
      issue_pv(1);
      wg_commit();
      turn_end();
      wg_wait<1>();
      reg_fence(s);
      give(ks, fd);
      if (jj == nw - 1) {
        if (!which) mask_diag();
        else if (lane == 0) mbar_arrive(bar_addr(sb, B_QFREE + w));
      }
      uint32_t pn[16];
      float t0, t1, a0 = 1.f, a1 = 1.f;
      exps(pn, t0, t1);
      const bool redo = __any_sync(0xffffffffu, !(t0 + t1 <= 0x1p30f));
      if (redo) {
        row_max(a0, a1);
        const float c0 = fminf(b0, -SC * a0), c1 = fminf(b1, -SC * a1);
        a0 = ex2(c0 - b0); a1 = ex2(c1 - b1);
        b0 = c0; b1 = c1;
        l0 *= a0; l1 *= a1;
        exps(pn, t0, t1);
      }
      l0 += t0; l1 += t1;
      wg_wait<0>();
      reg_fence(acc);
      reg_fence(pa);
      give(vs, fd + dir);
      fd += 2 * dir;
      if (redo) {
#pragma unroll
        for (int i = 0; i < 32; i++) { acc[4 * i] *= a0; acc[4 * i + 1] *= a0; acc[4 * i + 2] *= a1; acc[4 * i + 3] *= a1; }
      }
#pragma unroll
      for (int i = 0; i < 16; i++) pa[i] = (i & 1) ? pn[i] ^ (one - 1) : pn[i] * one;
    }
    if (!which && up) skip();
    const uint32_t vs = take();
    prep_pv(sb + vs * SLOT);
    turn_begin();
    wg_fence();
    issue_pv(1);
    wg_commit();
    turn_end();
    if (!which && up) r.next();
    ws = take();
    l0 += __shfl_xor_sync(0xffffffffu, l0, 1); l1 += __shfl_xor_sync(0xffffffffu, l1, 1);
    l0 += __shfl_xor_sync(0xffffffffu, l0, 2); l1 += __shfl_xor_sync(0xffffffffu, l1, 2);
    float i0, i1;
    asm volatile("rcp.approx.ftz.f32 %0, %1;" : "=f"(i0) : "f"(l0));
    asm volatile("rcp.approx.ftz.f32 %0, %1;" : "=f"(i1) : "f"(l1));
    uint32_t xs = 0;
    if (!which) xs = take();
    wg_wait<0>();
    reg_fence(acc);
    reg_fence(pa);
    give(vs, fd);
#pragma unroll
    for (int i = 0; i < 32; i++) {
      pk[2 * i]     = pack_bf16(acc[4 * i] * i0, acc[4 * i + 1] * i0);
      pk[2 * i + 1] = pack_bf16(acc[4 * i + 2] * i1, acc[4 * i + 3] * i1);
    }
    if (which) break;
    uint32_t xaddr = sb + xs * SLOT + (w ^ 1) * 8192;
#pragma unroll 1
    for (int kc = 0;; kc++) {
      const uint64_t da = desc_k(xaddr), db = desc_mn(sb + ws * SLOT);
      turn_begin();
      wg_fence();
#pragma unroll
      for (int kk = 0; kk < 4; kk++) wgmma_ss_n256_tb(acc, desc_add(da, kk * 32), desc_add(db, kk * 2048), (kc | kk) != 0);
      wg_commit();
      turn_end();
      const int cb = kc;
      if (cb >= 1 && cb <= 4) { fence_async_smem(); warp_arrive(bar_addr(sb, B_CTXS + 4 * w + cb - 1), lane); }
      if ((unsigned)cb < 4) {
        if (cb & 2) { if (cb & 1) store_blocks<48, 1>(qreg + 24576, lb, pk); else store_blocks<32, 1>(qreg + 16384, lb, pk); }
        else        { if (cb & 1) store_blocks<16, 1>(qreg + 8192, lb, pk);  else store_blocks<0, 1>(qreg, lb, pk); }
      }
      wg_wait<0>();
      release(bar_addr(sb, B_RG_EMPTY + ws), lane);
      if (!(kc & 1)) release(bar_addr(sb, B_RG_EMPTY + xs), lane);
      if (kc == 6) break;
      ws = take();
      if (!(kc & 1)) { xs = take(); xaddr = sb + xs * SLOT + (w ^ 1) * 8192; } else xaddr += 16384;
    }
    reg_fence(acc);
#pragma unroll
    for (int i = 0; i < 64; i++) pk[i] = pack_bf16(acc[2 * i], acc[2 * i + 1]);
    qt = 15 - qt;
  }

  {
    float oa[32], ob[32];
#pragma unroll
    for (int i = 0; i < 32; i++) { oa[i] = 0.f; ob[i] = 0.f; }
    auto stage_o = [&](float (&o)[32], int ch) {
      reg_fence(o);
      uint32_t q[16];
#pragma unroll
      for (int i = 0; i < 16; i++) q[i] = pack_bf16(o[2 * i], o[2 * i + 1]);
      if (ch >= 2) mbar_wait(bar_addr(sb, B_S2_EMPTY + w * 2 + (ch & 1)), ((ch >> 1) - 1) & 1);
      store_blocks<0, 1>(qreg + (ch & 1) * 8192, lb, q);
    };
    auto hand_over = [&](int ch) {
      fence_async_smem();
      warp_arrive(bar_addr(sb, B_S2_FULL + w * 2 + (ch & 1)), lane);
    };
    uint32_t pk2[64];
    uint32_t p2 = 0;
    auto chunk = [&](int ch, auto first, float (&o)[32], float (&oprev)[32]) {
      constexpr bool FIRST = decltype(first)::value;
      const uint32_t s1 = FIRST ? ws : take();
      const uint64_t d1 = desc_mn(sb + s1 * SLOT);
      turn_begin();
      wg_fence();
#pragma unroll
      for (int kk = 0; kk < 16; kk++) {
        wgmma_rs_n64_tb(o, pk[4 * kk], pk[4 * kk + 1], pk[4 * kk + 2], pk[4 * kk + 3], desc_add(d1, kk * 2048), kk != 0);
        if (kk == ARRIVE_KK) turn_end();
      }
      wg_commit();
      if constexpr (!FIRST) {
        wg_wait<1>();
        release(bar_addr(sb, B_RG_EMPTY + p2), lane);
        stage_o(oprev, ch - 1);
      } else {
        mbar_wait(bar_addr(sb, B_CTXF + w), 0);
#pragma unroll
        for (int kk = 0; kk < 16; kk++) {
          uint32_t f[4];
          ldsm4(f, qreg + (kk >> 2) * 8192 + (lb ^ ((kk & 3) << 5)));
          pk2[4 * kk] = f[0]; pk2[4 * kk + 1] = f[1]; pk2[4 * kk + 2] = f[2]; pk2[4 * kk + 3] = f[3];
        }
      }
      const uint32_t s2 = take();
      const uint64_t d2 = desc_mn(sb + s2 * SLOT);
      turn_begin();
      wg_fence();
#pragma unroll
      for (int kk = 0; kk < 16; kk++) {
        wgmma_rs_n64_tb(o, pk2[4 * kk], pk2[4 * kk + 1], pk2[4 * kk + 2], pk2[4 * kk + 3], desc_add(d2, kk * 2048), 1);
        if (kk == ARRIVE_KK && (ch < 6 || w == 1)) turn_end();
      }
      wg_commit();
      if (!FIRST) hand_over(ch - 1);
      wg_wait<1>();
      release(bar_addr(sb, B_RG_EMPTY + s1), lane);
      p2 = s2;
    };
    chunk(0, Int<1>(), oa, ob);
#pragma unroll 1
    for (int ch = 1; ch < 7; ch += 2) { chunk(ch, Int<0>(), ob, oa); chunk(ch + 1, Int<0>(), oa, ob); }
    wg_wait<0>();
    reg_fence(pk);
    reg_fence(pk2);
    stage_o(oa, 6);
    hand_over(6);
  }

}

#define CONV_STAGGER_NS 1200
namespace ssm {
#define CONV_GROUPS (D_SPARE / 8 / NCONV)
constexpr int GROUPS = CONV_GROUPS;
constexpr uint32_t ZROWS = 16;
constexpr uint32_t CHAN = (ZROWS + 256 + 1) * 16;
constexpr uint32_t XBUF = 8 * CHAN;
constexpr uint32_t OFF_X = 0;
constexpr uint32_t HCOPY = 4160;
constexpr uint32_t OFF_H = 2 * XBUF;
constexpr uint32_t HWARP = 3 * HCOPY;
constexpr uint32_t IO_K = 128, IO_V = IO_K + 4096, IO_Q = IO_V + 4096, IOBUF = IO_Q + 4096;
constexpr uint32_t OFF_IO = (OFF_H + 8 * HWARP + 127) / 128 * 128;
constexpr uint32_t END = OFF_IO + 4 * IOBUF;
static_assert(IOBUF % 128 == 0 && OFF_H % 16 == 0, "TMA destination alignment");
static_assert(END <= BARS, "smem");
enum : uint32_t { B_XREADY = 0, B_ZDONE = 2, B_KV = 4, B_Q = 8, B_HRAW = 12, B_QLAST = 20 };
constexpr int CW_BAR = 4;

__device__ __forceinline__ int group_d0(int cidx, int grp) { return (grp * NCONV + cidx) * 8; }
__device__ __forceinline__ uint32_t x_lane(int lane) { return (lane & 7) * CHAN + (ZROWS + (lane >> 3)) * 16; }
__device__ __forceinline__ uint32_t t_lane(int lane) { return (uint32_t)(8 * (lane >> 3) + 7 - (lane & 7)) * 16; }
struct Taps { uint32_t s[4]; };
__device__ __forceinline__ Taps load_taps(const Params& p, int d0, int c) {
  const uint2 s0 = __ldg(reinterpret_cast<const uint2*>(p.a_shift + (d0 + 2 * c) * 4)), s1 = __ldg(reinterpret_cast<const uint2*>(p.a_shift + (d0 + 2 * c + 1) * 4));
  return Taps{{__byte_perm(s0.x, s1.x, 0x5410), __byte_perm(s0.x, s1.x, 0x7632), __byte_perm(s0.y, s1.y, 0x5410), __byte_perm(s0.y, s1.y, 0x7632)}};
}
__device__ __forceinline__ uint32_t short_conv(const Taps& t, uint32_t k0, uint32_t k1, uint32_t k2, uint32_t k3, uint32_t v) {
  return bmul(badd(badd(badd(bmul(k0, t.s[3]), bmul(k1, t.s[2])), bmul(k2, t.s[1])), bmul(k3, t.s[0])), v);
}
template <int U>
__device__ __forceinline__ void x_chunk(const Taps& taps, uint32_t ka, uint32_t xa) {
#pragma unroll 1
  for (int u0 = 0; u0 < 8; u0 += U) {
    uint32_t k0[U][4], k1[U][4], k2[U][4], k3[U][4], vv[U][4];
#pragma unroll
    for (int u = 0; u < U; u++) {
      const uint32_t a = ka + (u0 + u) * 512;
      ldsm4(k0[u], a - 48); ldsm4(k1[u], a - 32); ldsm4(k2[u], a - 16); ldsm4(k3[u], a); ldsm4(vv[u], a + 4096);
    }
#pragma unroll
    for (int u = 0; u < U; u++)
      stsm4t(xa + (u0 + u) * 64, short_conv(taps, k0[u][0], k1[u][0], k2[u][0], k3[u][0], vv[u][0]), short_conv(taps, k0[u][1], k1[u][1], k2[u][1], k3[u][1], vv[u][1]),
             short_conv(taps, k0[u][2], k1[u][2], k2[u][2], k3[u][2], vv[u][2]), short_conv(taps, k0[u][3], k1[u][3], k2[u][3], k3[u][3], vv[u][3]));
  }
}
template <int U>
__device__ __forceinline__ void shift_filter(uint32_t hE, uint32_t hO, int lane) {
#pragma unroll 1
  for (int i0 = 0; i0 < 8; i0 += U) {
    uint4 w[U]; uint32_t nx[U];
    const uint32_t o = 32 + lane * 16 + i0 * 512;
#pragma unroll
    for (int i = 0; i < U; i++) { w[i] = lds16(hE + o + i * 512); nx[i] = lds4(hE + o + i * 512 + 16); }
#pragma unroll
    for (int i = 0; i < U; i++)
      sts16(hO + o + i * 512, __byte_perm(w[i].x, w[i].y, 0x5432), __byte_perm(w[i].y, w[i].z, 0x5432), __byte_perm(w[i].z, w[i].w, 0x5432), __byte_perm(w[i].w, nx[i], 0x5432));
    if (o == 32) asm volatile("st.shared.u32 [%0], %1;" :: "r"(hO + 28), "r"(w[0].x << 16) : "memory");
  }
}
template <int U>
__device__ __forceinline__ void gate_chunk(uint32_t xa, uint32_t qa) {
#pragma unroll 1
  for (int i0 = 0; i0 < 8; i0 += U) {
    uint32_t zz[U][4], qq[U][4];
#pragma unroll
    for (int i = 0; i < U; i++) { ldsm4t(zz[i], xa + (i0 + i) * 64); ldsm4(qq[i], qa + (i0 + i) * 512); }
#pragma unroll
    for (int i = 0; i < U; i++) stsm4(qa + (i0 + i) * 512, bmul(qq[i][0], zz[i][0]), bmul(qq[i][1], zz[i][1]), bmul(qq[i][2], zz[i][2]), bmul(qq[i][3], zz[i][3]));
  }
}

__device__ __forceinline__ void io_warp(const Params& p, uint32_t sb, int cidx, int wq) {
  const int lane = threadIdx.x & 31;
  const uint32_t io = sb + OFF_IO + wq * IOBUF, bkv = bar_addr(sb, B_KV + wq), bq = bar_addr(sb, B_Q + wq);
  auto load_kv = [&](int e) {
    __syncwarp();
    if (lane != 0) return;
    const int d0 = group_d0(cidx, e >> 1), row = (2 * wq + (e & 1)) * 256;
    if (e < 2 * GROUPS) {
      mbar_expect_tx(bkv, IO_Q);
      tma_ld2(io, &p.ak8, bkv, d0, row - 8);
      tma_ld2(io + IO_K, &p.ak, bkv, d0, row);
      tma_ld2(io + IO_V, &p.av, bkv, d0, row);
    } else {
      const uint32_t bar = bar_addr(sb, B_QLAST + 2 * wq + 1);
      mbar_expect_tx(bar, 4096);
      tma_ld2(io + IO_K, &p.aq, bar, group_d0(cidx, GROUPS - 1), row + 256);
    }
  };
  auto load_q = [&](int e) {
    __syncwarp();
    if (lane != 0) return;
    const uint32_t bar = e < 2 * GROUPS - 2 ? bq : bar_addr(sb, B_QLAST + 2 * wq);
    mbar_expect_tx(bar, 4096);
    tma_ld2(io + IO_Q, &p.aq, bar, group_d0(cidx, e >> 1), (2 * wq + (e & 1)) * 256);
  };
  load_kv(0);
  const uint32_t xl = sb + OFF_X + x_lane(lane) + wq * 1024, tl = io + t_lane(lane);
#pragma unroll 1
  for (int grp = -2; grp + 1 < GROUPS; grp++) {
    const bool more = grp + 2 < GROUPS;
    const Taps taps = load_taps(p, group_d0(cidx, more ? grp + 2 : 0), lane & 3);
    if (grp >= 0) mbar_wait_nap(bar_addr(sb, B_ZDONE + (grp & 1)), (grp >> 1) & 1);

#pragma unroll 1
    for (int i = 0; i < 2; i++) {
      const uint32_t xa = xl + (grp & 1) * XBUF + i * 512;
      if (grp >= 0) {
        mbar_wait_nap(bq, i);
        gate_chunk<4>(xa, tl + IO_Q);
      }
      if (more) {
        mbar_wait_nap(bkv, i);
        x_chunk<2>(taps, tl + IO_K, xa);
        load_kv(2 * (grp + 2) + i + 1);
        if (i == 1) warp_arrive(bar_addr(sb, B_XREADY + (grp & 1)), lane);
      }
      if (grp >= 0) {
        fence_async_smem();
        __syncwarp();
        if (lane == 0) {
          tma_st2(&p.ao, io + IO_Q, group_d0(cidx, grp), (2 * wq + i) * 256);
          bulk_commit();
          bulk_wait_read();
        }
      }
      if (2 * grp + i + 1 >= 0) load_q(2 * grp + i + 1);
    }
  }
  if (lane == 0) bulk_wait_all();
}

__device__ __forceinline__ void conv_warp(const Params& p, uint32_t sb, int cidx, int ch) {
  const int lane = threadIdx.x & 31;
  const uint32_t hE0 = sb + OFF_H + ch * HWARP, hO = hE0 + HCOPY;
  const uint32_t hbar = bar_addr(sb, B_HRAW + ch);
  auto fetch_h = [&](int grp) {
    if (lane == 0) {
      mbar_expect_tx(hbar, 4096);
      asm volatile("cp.async.bulk.shared::cluster.global.mbarrier::complete_tx::bytes [%0], [%1], %2, [%3];"
                   :: "r"(hE0 + (grp & 1) * 2 * HCOPY + 32), "l"(p.a_ssmk + (size_t)(group_d0(cidx, grp) + ch) * SEQ), "r"(4096), "r"(hbar) : "memory");
    }
  };
  fetch_h(0);
#pragma unroll 1
  for (int grp = 0; grp < GROUPS; grp++) {
    const uint32_t xc = sb + OFF_X + (grp & 1) * XBUF + ch * CHAN;
    const uint32_t D1 = __ldg(reinterpret_cast<const unsigned short*>(p.a_D + group_d0(cidx, grp) + ch));
    mbar_wait(hbar, grp & 1);
    const uint32_t hE = hE0 + (grp & 1) * 2 * HCOPY;
    if (grp + 1 < GROUPS) fetch_h(grp + 1);
    shift_filter<8>(hE, hO, lane);
    __syncwarp();
    const uint32_t ha = cv_h_lane(lane, hE, hO), xa = xc + cv_x_lane(lane);
    mbar_wait(bar_addr(sb, B_XREADY + (grp & 1)), (grp >> 1) & 1);
    if (grp == 0 && ch >= 4) __nanosleep(CONV_STAGGER_NS);

    float acc[16][4];
#pragma unroll
    for (int i = 0; i < 16; i++) { acc[i][0] = 0.f; acc[i][1] = 0.f; acc[i][2] = 0.f; acc[i][3] = 0.f; }
#pragma unroll 1
    for (int r = 0; r < 8; r++) {
      uint32_t fx[16][4], fh[16][2];
#pragma unroll
      for (int i = 0; i < 16; i++) { fh[i][0] = lds4(ha + i * 256 + r * 32); fh[i][1] = lds4(ha + i * 256 + r * 32 + 16); }
#pragma unroll
      for (int i = 0; i < 16; i++) ldsm4(fx[i], xa + i * 256 - r * 32);
#pragma unroll
      for (int sx = 0; sx < 16; sx++)
#pragma unroll
        for (int jj = 0; jj < 16 - sx; jj++) mma16816(acc[jj + sx], fx[sx], fh[jj][0], fh[jj][1]);
    }

    {
      uint32_t x[8][4], Dd;
      asm volatile("prmt.b32 %0, %1, %1, 0x1010;" : "=r"(Dd) : "r"(D1));
      const uint32_t ad = xc + (ZROWS + lane) * 16;
#pragma unroll
      for (int i = 0; i < 8; i++) ldsm4(x[i], ad + i * 512);
#pragma unroll
      for (int i = 0; i < 8; i++)
        stsm4(ad + i * 512, add_skip(pack_bf16(acc[2 * i][0], acc[2 * i][1]), x[i][0], Dd), add_skip(pack_bf16(acc[2 * i][2], acc[2 * i][3]), x[i][1], Dd),
              add_skip(pack_bf16(acc[2 * i + 1][0], acc[2 * i + 1][1]), x[i][2], Dd), add_skip(pack_bf16(acc[2 * i + 1][2], acc[2 * i + 1][3]), x[i][3], Dd));
    }
    if (grp + 1 < GROUPS) warp_arrive(bar_addr(sb, B_ZDONE + (grp & 1)), lane);
  }
  {
    mbar_wait(bar_addr(sb, B_QLAST + ch), 0);
    named_sync(CW_BAR, 256);
    const uint32_t qb = sb + OFF_IO + (ch >> 1) * IOBUF + ((ch & 1) ? IO_K : IO_Q);
    gate_chunk<8>(sb + OFF_X + ((GROUPS - 1) & 1) * XBUF + x_lane(lane) + ch * 512, qb + t_lane(lane));
    fence_async_smem();
    __syncwarp();
    if (lane == 0) { tma_st2(&p.ao, qb, group_d0(cidx, GROUPS - 1), ch * 256); bulk_commit(); bulk_wait_read(); }
  }
}

__device__ __forceinline__ void init(uint32_t sb) {
  if (threadIdx.x < 16 * ZROWS) sts16(sb + OFF_X + (threadIdx.x >> 4) * CHAN + (threadIdx.x & 15) * 16, 0, 0, 0, 0);
  if (threadIdx.x < 96) sts16(sb + OFF_H + (threadIdx.x >> 2) * HCOPY + (threadIdx.x & 1) * 16 + ((threadIdx.x & 2) ? 4128 : 0), 0, 0, 0, 0);
  if (threadIdx.x == 0) {
    for (int i = 0; i < 2; i++) { mbar_init(bar_addr(sb, B_XREADY + i), 4); mbar_init(bar_addr(sb, B_ZDONE + i), 8); }
    for (int i = 0; i < 4; i++) { mbar_init(bar_addr(sb, B_KV + i), 1); mbar_init(bar_addr(sb, B_Q + i), 1); }
    for (int i = 0; i < 8; i++) { mbar_init(bar_addr(sb, B_HRAW + i), 1); mbar_init(bar_addr(sb, B_QLAST + i), 1); }
    fence_async_smem();
  }
  named_sync(0, NTHREADS);
}
}

__device__ __forceinline__ void ssm_side_work(const Params& p, uint32_t sb, unsigned epoch) {
  const Role ro = get_role();
  const int h = ro.h, j = ro.j;
  const int lane = threadIdx.x & 31;
  const int d0 = D_SPARE + 8 * h;
  constexpr uint32_t ZCH = 528;
  {
    const uint32_t kb = sb + P1_STG, xb = kb + 8320, hE = xb + 8 * ZCH, hO = hE + CV_HCOPY, zero = hO + CV_HCOPY, bar = bar_addr(sb, B_SIDE);
    if (lane == 0) {
      mbar_expect_tx(bar, 128 + 3 * 4096);
      tma_ld2(kb, &p.ak8, bar, d0, 256 * j - 8);
      tma_ld2(kb + 128, &p.ak, bar, d0, 256 * j);
      bulk_ld(hE + 32, p.a_ssmk + (size_t)(d0 + j) * SEQ, 4096, bar);
      __nanosleep(600);
      tma_ld2(kb + 128 + 4096, &p.av, bar, d0, 256 * j);
    }
    const ssm::Taps taps = ssm::load_taps(p, d0, lane & 3);
    const uint32_t Dd = (uint32_t)__ldg(reinterpret_cast<const unsigned short*>(p.a_D + d0 + j)) * 0x10001u;
    if (lane < 16) sts16(zero + lane * 16, 0, 0, 0, 0);
    else if (lane < 24) sts16(hE + ((lane >> 2) & 1) * CV_HCOPY + (lane & 1) * 16 + ((lane & 2) ? 4128 : 0), lane == 19 ? Dd : 0, 0, 0, 0);
    __syncwarp();
    mbar_wait_nap(bar, 0);
    ssm::x_chunk<1>(taps, kb + 128 + ssm::t_lane(lane), xb + (lane & 7) * ZCH + (lane >> 3) * 16);
    ssm::shift_filter<2>(hE, hO, lane);
    fence_async_smem();
    __syncwarp();
    if (lane == 0) {
      uint8_t* img = g_xs + (size_t)(h * 8) * CV_BYTES;
      for (int i = 0; i < 8; i++) bulk_st(img + i * CV_BYTES + (16 + 32 * j) * 16, xb + i * ZCH, 512);
      bulk_st(img + j * CV_BYTES, zero, 256);
      for (int i = 0; i < 4; i++) { __nanosleep(200); bulk_st(img + j * CV_BYTES + CV_HE + i * (CV_HCOPY / 2), hE + i * (CV_HCOPY / 2), CV_HCOPY / 2); }
      bulk_commit();
      bulk_wait_read();
      mbar_arrive(bar_addr(sb, B_SIDE + 1));
      bulk_wait_all();
      flag_signal(&g_flags.xs_ready[h].v);
      flag_wait(&g_flags.xs_ready[h].v, 8, epoch);
      fence_async_all();
      mbar_arrive(bar_addr(sb, B_XS));
    }
  }
  if (lane == 0) {
    for (int i = 0; i < 3; i++) {
      flag_wait(&g_flags.kv_ready[3 * h + i].v, 16, epoch);
      fence_async_all();
      mbar_arrive(bar_addr(sb, B_KV + i));
    }
    mbar_wait_nap(bar_addr(sb, B_CONV), 0);
    flag_signal(&g_flags.zs_ready[h].v);
    flag_wait(&g_flags.zs_ready[h].v, 8, epoch);
    asm volatile("red.relaxed.gpu.global.add.u64 [%0], 1;" :: "l"(&g_flags.done) : "memory");
  }
  __syncwarp();
  fence_async_all();
  const uint32_t qb = q_region(sb, 1) + 16384, zb = qb + 4096, bar = bar_addr(sb, B_GATE);
  mbar_wait_slow(bar_addr(sb, B_GFREE), 0);
  if (lane == 0) { mbar_expect_tx(bar, 8192); tma_ld2(qb, &p.aq, bar, d0, 256 * j); }
  __syncwarp();
  if (lane < 8) bulk_ld(zb + lane * ZCH, g_xs + (size_t)(h * 8 + lane) * CV_BYTES + (16 + 32 * j) * 16, 512, bar);
  mbar_wait(bar, 0);
  ssm::gate_chunk<2>(zb + (lane & 7) * ZCH + (lane >> 3) * 16, qb + ssm::t_lane(lane));
  fence_async_smem();
  __syncwarp();
  if (lane == 0) { tma_st2(&p.ao, qb, d0, 256 * j); bulk_commit(); bulk_wait_all(); }
}

__global__ void __cluster_dims__(2, 1, 1) __launch_bounds__(NTHREADS, 1)
concat_heads__ssm_conv_h3__compressed_kv_cla__prompt_kernel(uint8_t* xs, uint32_t one, const __grid_constant__ Params p) {
  if (threadIdx.x == 0) { prefetch_map(&p.wuk); prefetch_map(&p.ckv); }
  extern __shared__ uint8_t smem_raw[];
  const uint32_t sb = (smem_u32(smem_raw) + 1023) & ~1023u;
  const int warp = __shfl_sync(0xffffffffu, threadIdx.x >> 5, 0);
  const int wg = warp >> 2;
  const int cta = blockIdx.x;
  const bool attn = cta < NMAIN;
  if (attn && (threadIdx.x >> 5) == 4) {
    const Role ro = get_role();
    auto load = [&](int k) {
      const uint32_t full = bar_addr(sb, B_P1_FULL + k), dst = sb + k * P1_STAGE;
      mbar_expect_tx(full, P1_STAGE);
      tma_ld2(dst, &p.ckv, full, k * 64, kv_block(ro.j, 0) * 128);
      tma_ld3(dst + 16384, &p.wuk, full, 0, k * 64, ro.h * 4);
    };
    if (threadIdx.x == 128) {
      for (int i = 0; i < 4; i++) mbar_init(bar_addr(sb, B_P1_FULL + i), 1);
      asm volatile("fence.mbarrier_init.release.cluster;" ::: "memory");
      load(0);
    }
    __syncwarp();
    named_arrive(0, NTHREADS);
    if (threadIdx.x == 128) {
      for (int k = 1; k < EARLY_LD; k++) load(k);
    }
    __syncwarp();
  }
  const int lane = threadIdx.x & 31;
  if (wg == 0) {
    if (!attn) {
      asm volatile("setmaxnreg.dec.sync.aligned.u32 72;");
      if (one) { ssm::init(sb); ssm::io_warp(p, sb, cta - NMAIN, fresh_warp()); }
      return;
    }
    asm volatile("setmaxnreg.dec.sync.aligned.u32 40;");
    named_arrive(PP_BAR + 1, 256);
    if (warp == 2) {
      if (lane == 0) {
        for (int i = 0; i < 4; i++) mbar_init(bar_addr(sb, B_P1_EMPTY + i), 8);
        for (int i = 0; i < NSLOT; i++) {
          mbar_init(bar_addr(sb, B_RG_FULL + i), 1); mbar_init(bar_addr(sb, B_RG_EMPTY + i), 8);
        }
        for (int i = 0; i < 2; i++) { mbar_init(bar_addr(sb, B_ST_FULL + i), 4); mbar_init(bar_addr(sb, B_ST_EMPTY + i), 1); }
        mbar_init(bar_addr(sb, B_XS), 1); mbar_init(bar_addr(sb, B_SIDE), 1); mbar_init(bar_addr(sb, B_SIDE + 1), 1); mbar_init(bar_addr(sb, B_CONV), 8); mbar_init(bar_addr(sb, B_GATE), 1); mbar_init(bar_addr(sb, B_GFREE), 1);
        for (int i = 0; i < 3; i++) mbar_init(bar_addr(sb, B_KV + i), 1);
        for (int i = 0; i < 8; i++) mbar_init(bar_addr(sb, B_CTXS + i), 4);
        for (int i = 0; i < 4; i++) { mbar_arrive(bar_addr(sb, B_RG_FULL + i)); if (i < 3) mbar_arrive_n(bar_addr(sb, B_RG_EMPTY + i), 8); }
        for (int i = 0; i < 4; i++) { mbar_init(bar_addr(sb, B_S2_FULL + i), 4); mbar_init(bar_addr(sb, B_S2_EMPTY + i), 1); }
        for (int i = 0; i < 2; i++) { mbar_init(bar_addr(sb, B_QFREE + i), 4); mbar_init(bar_addr(sb, B_CTXF + i), 1); }
        asm volatile("fence.mbarrier_init.release.cluster;" ::: "memory");
      }
      __syncwarp();
      named_arrive(0, NTHREADS);
    } else {
      named_sync(0, NTHREADS);
    }
    if (warp == 0) {
      if (lane == 0) producer_main(p, sb);
    } else if (warp < 3) {
      storer_main(p, sb);
    } else {
      const unsigned epoch = load_epoch();
      mbar_wait(bar_addr(sb, B_P1_FULL + 3), 0);
      __nanosleep(SIDE_DELAY_NS);
      ssm_side_work(p, sb, epoch);
    }
  } else {
    if (attn) {
      asm volatile("setmaxnreg.inc.sync.aligned.u32 232;");
      if (one) consumer_main(p, sb, xs, one);
    } else {
      asm volatile("setmaxnreg.inc.sync.aligned.u32 216;");
      if (one) { ssm::init(sb); ssm::conv_warp(p, sb, cta - NMAIN, fresh_warp() - 4); }
    }
  }
}

typedef CUresult (*EncodeTiledFn)(CUtensorMap*, CUtensorMapDataType, cuuint32_t, void*, const cuuint64_t*, const cuuint64_t*,
                                  const cuuint32_t*, const cuuint32_t*, CUtensorMapInterleave, CUtensorMapSwizzle,
                                  CUtensorMapL2promotion, CUtensorMapFloatOOBfill);

void make_map(EncodeTiledFn enc, CUtensorMap* m, const void* ptr, int rank, const uint64_t* dims, const uint64_t* strides, const uint32_t* box) {
  cuuint64_t d[3], s[2]; cuuint32_t b[3], e[3] = {1, 1, 1};
  for (int i = 0; i < rank; i++) { d[i] = dims[i]; b[i] = box[i]; if (i) s[i - 1] = strides[i - 1]; }
  enc(m, CU_TENSOR_MAP_DATA_TYPE_BFLOAT16, rank, const_cast<void*>(ptr), d, s, b, e, CU_TENSOR_MAP_INTERLEAVE_NONE,
      CU_TENSOR_MAP_SWIZZLE_128B, CU_TENSOR_MAP_L2_PROMOTION_L2_256B, CU_TENSOR_MAP_FLOAT_OOB_FILL_NONE);
}
void map2(EncodeTiledFn enc, CUtensorMap* m, const void* ptr, uint64_t cols, uint64_t rows, uint32_t bc, uint32_t br) {
  const uint64_t dims[2] = {cols, rows}, st[1] = {cols * 2}; const uint32_t box[2] = {bc, br};
  make_map(enc, m, ptr, 2, dims, st, box);
}
void map2_plain(EncodeTiledFn enc, CUtensorMap* m, const void* ptr, uint64_t cols, uint64_t rows, uint32_t bc, uint32_t br) {
  cuuint64_t d[2] = {cols, rows}, st[1] = {cols * 2}; cuuint32_t b[2] = {bc, br}, e[2] = {1, 1};
  enc(m, CU_TENSOR_MAP_DATA_TYPE_BFLOAT16, 2, const_cast<void*>(ptr), d, st, b, e, CU_TENSOR_MAP_INTERLEAVE_NONE,
      CU_TENSOR_MAP_SWIZZLE_NONE, CU_TENSOR_MAP_L2_PROMOTION_L2_128B, CU_TENSOR_MAP_FLOAT_OOB_FILL_NONE);
}
void map3(EncodeTiledFn enc, CUtensorMap* m, const void* ptr, uint64_t rows, uint32_t nblk) {
  const uint64_t dims[3] = {64, rows, 64}, st[2] = {8192, 128}; const uint32_t box[3] = {64, 64, nblk};
  make_map(enc, m, ptr, 3, dims, st, box);
}

}

extern "C" void kernel_launch(void* const* d_in, const int* in_sizes, int n_in, void* d_out, int out_size) {
  (void)in_sizes; (void)n_in; (void)out_size;
  static EncodeTiledFn enc = nullptr;
  static void *kv_ptr = nullptr, *acc_ptr = nullptr, *xs_ptr = nullptr;
  if (!enc) {
    void* fn = nullptr; cudaDriverEntryPointQueryResult qr;
    cudaGetDriverEntryPoint("cuTensorMapEncodeTiled", &fn, cudaEnableDefault, &qr);
    enc = (EncodeTiledFn)fn;
    cudaGetSymbolAddress(&kv_ptr, g_kv);
    cudaGetSymbolAddress(&acc_ptr, g_ctx);
    cudaGetSymbolAddress(&xs_ptr, g_xs);
    cudaFuncSetAttribute(concat_heads__ssm_conv_h3__compressed_kv_cla__prompt_kernel, cudaFuncAttributeMaxDynamicSharedMemorySize, SMEM_BYTES);
  }
  Params p;
  map2_plain(enc, &p.aq, d_in[0], DA, SEQ, 8, 256);
  map2_plain(enc, &p.ak, d_in[1], DA, SEQ, 8, 256);
  map2_plain(enc, &p.ak8, d_in[1], DA, SEQ, 8, 8);
  map2_plain(enc, &p.av, d_in[2], DA, SEQ, 8, 256);
  map2_plain(enc, &p.ao, d_out, OUTW, SEQ, 8, 256);
  p.a_shift = (const bf16*)d_in[3]; p.a_ssmk = (const bf16*)d_in[4]; p.a_D = (const bf16*)d_in[5];
  p.out = (bf16*)d_out; p.b_x = (const bf16*)d_in[6]; p.b_wo = (const bf16*)d_in[11];
  map2(enc, &p.x, d_in[6], DM, SEQ, 64, 128);
  map2(enc, &p.ckv, d_in[7], DC, SEQ, 64, 128);
  map3(enc, &p.wq, d_in[8], DM, 4);
  map2_plain(enc, &p.wqp, d_in[8], NH * HD, DM, 256, 4);
  map3(enc, &p.wuk, d_in[9], DC, 4);
  map3(enc, &p.wuv, d_in[10], DC, 4);
  map2(enc, &p.wo, d_in[11], DM, NH * HD, 64, 256);
  map2(enc, &p.part, d_out, OUTW, SEQ, 64, 64);
  p.kv = (uint8_t*)kv_ptr; p.ctx = (uint8_t*)acc_ptr;
  concat_heads__ssm_conv_h3__compressed_kv_cla__prompt_kernel<<<NCTA, NTHREADS, SMEM_BYTES>>>((uint8_t*)xs_ptr, 1u, p);
}
```

```cpp
#include <cuda_runtime.h>
#include <cuda_bf16.h>
#include <cuda.h>
#include <stdint.h>

namespace {

typedef __nv_bfloat16 bf16;

constexpr int SEQ  = 2048;
constexpr int DA   = 448;
constexpr int NH   = 16;
constexpr int HD   = 256;
constexpr int DM   = 448;
constexpr int DC   = 1024;
constexpr int OUTW = DA + DM;
constexpr int NMAIN = 128;
constexpr int NCONV = 4;
constexpr int NCTA  = NMAIN + NCONV;
constexpr int NTHREADS = 384;
constexpr int D_SPARE = 320;

__device__ __align__(1024) bf16 g_kv[2ull * SEQ * NH * HD];
__device__ __align__(1024) bf16 g_ctx[(size_t)NMAIN * 128 * HD];
constexpr uint32_t CV_HE = 272 * 16, CV_HCOPY = 4160, CV_D = CV_HE + 4144, CV_BYTES = CV_HE + 2 * CV_HCOPY;
__device__ __align__(128) uint8_t g_xs[NMAIN * CV_BYTES];
struct alignas(128) Flag { unsigned v; unsigned pad[31]; };
struct Flags {
  Flag kv_ready[3 * NH];
  Flag ctx_ready[NMAIN * 2];
  Flag out_ready[16 * 2];
  Flag xs_ready[NH];
  Flag zs_ready[NH];
  alignas(128) unsigned long long done;
};
__device__ Flags g_flags;

struct alignas(64) Params {
  CUtensorMap ckv;
  CUtensorMap wuk;
  CUtensorMap wuv;
  CUtensorMap x;
  CUtensorMap wq;
  CUtensorMap wqp;
  CUtensorMap part;
  CUtensorMap wo;
  CUtensorMap ak, ak8, av, aq, ao;
  const bf16 *a_shift, *a_ssmk, *a_D, *b_x, *b_wo;
  bf16* out;
  uint8_t *kv, *ctx;
};

constexpr uint32_t P1_STAGE = 49152;
constexpr uint32_t P1_STG   = 196608;
constexpr uint32_t SLOT     = 32768;
constexpr int      NSLOT    = 5;
constexpr uint32_t QREG     = 163840;
constexpr uint32_t CV_X = 4 * SLOT + 16384, CV_R = 3 * SLOT;
static_assert(CV_BYTES <= 16384 && CV_BYTES % 128 == 0, "SSM operands");
constexpr uint32_t BARS     = 229376;
constexpr uint32_t SMEM_BYTES = BARS + 512 + 1024;
enum : uint32_t {
  B_P1_FULL = 0, B_P1_EMPTY = 4, B_RG_FULL = 8, B_RG_EMPTY = 13, B_ST_FULL = 18, B_ST_EMPTY = 20,
  B_XS = 22, B_SIDE = 23, B_S2_FULL = 28, B_S2_EMPTY = 32, B_QFREE = 36, B_CTXF = 38, B_KV = 40, B_GATE = 43, B_CTXS = 44, B_GFREE = 52, B_CONV = 53, B_COUNT = 54
};

__device__ __forceinline__ uint32_t smem_u32(const void* p) { return (uint32_t)__cvta_generic_to_shared(p); }
__device__ __forceinline__ void mbar_init(uint32_t bar, uint32_t cnt) {
  asm volatile("mbarrier.init.shared::cta.b64 [%0], %1;" :: "r"(bar), "r"(cnt) : "memory");
}
__device__ __forceinline__ void mbar_expect_tx(uint32_t bar, uint32_t bytes) {
  asm volatile("mbarrier.arrive.expect_tx.shared::cta.b64 _, [%0], %1;" :: "r"(bar), "r"(bytes) : "memory");
}
__device__ __forceinline__ void mbar_arrive(uint32_t bar) {
  asm volatile("mbarrier.arrive.shared::cta.b64 _, [%0];" :: "r"(bar) : "memory");
}
__device__ __forceinline__ void mbar_arrive_n(uint32_t bar, uint32_t n) {
  asm volatile("mbarrier.arrive.shared::cta.b64 _, [%0], %1;" :: "r"(bar), "r"(n) : "memory");
}
__device__ __forceinline__ void lane0_arrive(uint32_t bar, uint32_t n, int lane) {
  asm volatile("{\n.reg .pred p;\nsetp.eq.s32 p, %2, 0;\n@p mbarrier.arrive.shared::cta.b64 _, [%0], %1;\n}" :: "r"(bar), "r"(n), "r"(lane) : "memory");
}
__device__ __forceinline__ bool mbar_try(uint32_t bar, uint32_t parity) {
  uint32_t ok;
  asm volatile("{\n.reg .pred p;\nmbarrier.try_wait.parity.shared::cta.b64 p, [%1], %2;\nselp.u32 %0, 1, 0, p;\n}"
               : "=r"(ok) : "r"(bar), "r"(parity) : "memory");
  return ok;
}
#define FLAG_NS 100
#define NAP_NS 100
constexpr uint32_t SPIN_LIMIT = 1u << 24;
__device__ __forceinline__ void mbar_wait(uint32_t bar, uint32_t parity) {
  if (mbar_try(bar, parity)) return;
  uint32_t n = 0;
  while (!mbar_try(bar, parity)) { if (++n > SPIN_LIMIT) __trap(); }
}
__device__ __forceinline__ void mbar_wait_nap(uint32_t bar, uint32_t parity) {
  uint32_t n = 0;
  while (!mbar_try(bar, parity)) { if (++n > (SPIN_LIMIT >> 2)) __trap(); __nanosleep(NAP_NS); }
}
__device__ __forceinline__ void mbar_wait_slow(uint32_t bar, uint32_t parity) {
  uint32_t n = 0;
  while (!mbar_try(bar, parity)) { if (++n > (SPIN_LIMIT >> 4)) __trap(); __nanosleep(500); }
}
__device__ __forceinline__ unsigned load_epoch() {
  unsigned long long e; asm volatile("ld.relaxed.gpu.global.u64 %0, [%1];" : "=l"(e) : "l"(&g_flags.done) : "memory"); return (unsigned)(e / NMAIN);
}
__device__ __forceinline__ void flag_wait(const unsigned* f, unsigned count, unsigned epoch) {
  const unsigned target = (epoch + 1) * count;
  uint32_t n = 0;
  while (true) {
    unsigned v;
    asm volatile("ld.acquire.gpu.global.u32 %0, [%1];" : "=r"(v) : "l"(f) : "memory");
    if ((int)(v - target) >= 0) break;
    if (++n > SPIN_LIMIT) __trap();
    __nanosleep(FLAG_NS);
  }
}
__device__ __forceinline__ void fence_async_all() { asm volatile("fence.proxy.async;" ::: "memory"); }
__device__ __forceinline__ void flag_signal(unsigned* f) {
  asm volatile("fence.acq_rel.gpu;" ::: "memory");
  asm volatile("red.relaxed.gpu.global.add.u32 [%0], 1;" :: "l"(f) : "memory");
}
__device__ __forceinline__ void flag_signal_after_bulk(unsigned* f) {
  asm volatile("red.relaxed.gpu.global.add.u32 [%0], 1;" :: "l"(f) : "memory");
}
__device__ __forceinline__ void fence_async_smem() { asm volatile("fence.proxy.async.shared::cta;" ::: "memory"); }
__device__ __forceinline__ void tma_ld2(uint32_t dst, const CUtensorMap* m, uint32_t bar, int c0, int c1) {
  asm volatile("cp.async.bulk.tensor.2d.shared::cluster.global.mbarrier::complete_tx::bytes [%0], [%1, {%3, %4}], [%2];"
               :: "r"(dst), "l"(m), "r"(bar), "r"(c0), "r"(c1) : "memory");
}
__device__ __forceinline__ void tma_ld3(uint32_t dst, const CUtensorMap* m, uint32_t bar, int c0, int c1, int c2) {
  asm volatile("cp.async.bulk.tensor.3d.shared::cluster.global.mbarrier::complete_tx::bytes [%0], [%1, {%3, %4, %5}], [%2];"
               :: "r"(dst), "l"(m), "r"(bar), "r"(c0), "r"(c1), "r"(c2) : "memory");
}
__device__ __forceinline__ void bulk_ld(uint32_t dst, const void* src, uint32_t bytes, uint32_t bar) {
  asm volatile("cp.async.bulk.shared::cluster.global.mbarrier::complete_tx::bytes [%0], [%1], %2, [%3];"
               :: "r"(dst), "l"(src), "r"(bytes), "r"(bar) : "memory");
}
__device__ __forceinline__ void bulk_st(void* dst, uint32_t src, uint32_t bytes) {
  asm volatile("cp.async.bulk.global.shared::cta.bulk_group [%0], [%1], %2;" :: "l"(dst), "r"(src), "r"(bytes) : "memory");
}
__device__ __forceinline__ void tma_st2(const CUtensorMap* m, uint32_t src, int c0, int c1) {
  asm volatile("cp.async.bulk.tensor.2d.global.shared::cta.bulk_group [%0, {%2, %3}], [%1];"
               :: "l"(m), "r"(src), "r"(c0), "r"(c1) : "memory");
}
__device__ __forceinline__ void tma_red2(const CUtensorMap* m, uint32_t src, int c0, int c1) {
  asm volatile("cp.reduce.async.bulk.tensor.2d.global.shared::cta.add.tile.bulk_group [%0, {%2, %3}], [%1];"
               :: "l"(m), "r"(src), "r"(c0), "r"(c1) : "memory");
}
__device__ __forceinline__ void tma_pf2(const CUtensorMap* m, int c0, int c1) {
  asm volatile("cp.async.bulk.prefetch.tensor.2d.L2.global.tile [%0, {%1, %2}];" :: "l"(m), "r"(c0), "r"(c1) : "memory");
}
__device__ __forceinline__ void bulk_prefetch(const void* src, uint32_t bytes) {
  asm volatile("cp.async.bulk.prefetch.L2.global [%0], %1;" :: "l"(src), "r"(bytes) : "memory");
}
__device__ __forceinline__ void bulk_commit() { asm volatile("cp.async.bulk.commit_group;" ::: "memory"); }
__device__ __forceinline__ void bulk_wait_read() { asm volatile("cp.async.bulk.wait_group.read 0;" ::: "memory"); }
__device__ __forceinline__ void bulk_wait_all() { asm volatile("cp.async.bulk.wait_group 0;" ::: "memory"); }
__device__ __forceinline__ void prefetch_map(const CUtensorMap* m) { asm volatile("prefetch.tensormap [%0];" :: "l"(m) : "memory"); }
__device__ __forceinline__ void wg_fence() { asm volatile("wgmma.fence.sync.aligned;" ::: "memory"); }
__device__ __forceinline__ void wg_commit() { asm volatile("wgmma.commit_group.sync.aligned;" ::: "memory"); }
template <int N> __device__ __forceinline__ void wg_wait() { asm volatile("wgmma.wait_group.sync.aligned %0;" :: "n"(N) : "memory"); }
template <int N> __device__ __forceinline__ void reg_fence(float (&d)[N]) {
#pragma unroll
  for (int i = 0; i < N; i++) asm volatile("" : "+f"(d[i]) :: "memory");
}
template <int N> __device__ __forceinline__ void reg_fence(uint32_t (&d)[N]) {
#pragma unroll
  for (int i = 0; i < N; i++) asm volatile("" : "+r"(d[i]) :: "memory");
}
__device__ __forceinline__ uint32_t fresh_tid() { uint32_t t; asm volatile("mov.u32 %0, %%tid.x;" : "=r"(t)); return t; }
__device__ __forceinline__ uint32_t lane_base16() {
  const uint32_t t = fresh_tid(), lane = t & 31, wq = (t >> 5) & 3;
  return (16 * wq + (lane & 7) + 8 * ((lane >> 3) & 1)) * 128 + (((lane >> 4) ^ (lane & 7)) << 4);
}
__device__ __forceinline__ void named_sync(int id, int n) { asm volatile("bar.sync %0, %1;" :: "r"(id), "r"(n) : "memory"); }
__device__ __forceinline__ void named_arrive(int id, int n) { asm volatile("bar.arrive %0, %1;" :: "r"(id), "r"(n) : "memory"); }
__device__ __forceinline__ uint32_t pack_bf16(float lo, float hi) {
  uint32_t r; asm("cvt.rn.bf16x2.f32 %0, %1, %2;" : "=r"(r) : "f"(hi), "f"(lo)); return r;
}
__device__ __forceinline__ float ex2(float x) { float y; asm("ex2.approx.ftz.f32 %0, %1;" : "=f"(y) : "f"(x)); return y; }
__device__ __forceinline__ void stsm4(uint32_t addr, uint32_t a, uint32_t b, uint32_t c, uint32_t d) {
  asm volatile("stmatrix.sync.aligned.m8n8.x4.shared.b16 [%0], {%1, %2, %3, %4};" :: "r"(addr), "r"(a), "r"(b), "r"(c), "r"(d) : "memory");
}
__device__ __forceinline__ void stsm4t(uint32_t addr, uint32_t a, uint32_t b, uint32_t c, uint32_t d) {
  asm volatile("stmatrix.sync.aligned.m8n8.x4.trans.shared.b16 [%0], {%1, %2, %3, %4};" :: "r"(addr), "r"(a), "r"(b), "r"(c), "r"(d) : "memory");
}
__device__ __forceinline__ uint64_t mk_desc(uint32_t addr, uint32_t lbo, uint32_t sbo) {
  return (uint64_t)(((addr & 0x3FFFF) >> 4) | ((lbo >> 4) << 16)) | ((uint64_t)((sbo >> 4) | (1u << 30)) << 32);
}
__device__ __forceinline__ uint64_t desc_k(uint32_t addr)  { return mk_desc(addr, 16, 1024); }
__device__ __forceinline__ uint64_t desc_mn(uint32_t addr) { return mk_desc(addr, 8192, 1024); }
__device__ __forceinline__ uint64_t desc_add(uint64_t d, uint32_t bytes) { return d + (bytes >> 4); }

__device__ __forceinline__ void wgmma_ss_n256_tb(float (&d)[128], uint64_t da, uint64_t db, int sd) {
  asm volatile("{\n.reg .pred p;\nsetp.ne.b32 p, %130, 0;\n"
    "wgmma.mma_async.sync.aligned.m64n256k16.f32.bf16.bf16 "
    "{%0, %1, %2, %3, %4, %5, %6, %7, %8, %9, %10, %11, %12, %13, %14, %15, "
    "%16, %17, %18, %19, %20, %21, %22, %23, %24, %25, %26, %27, %28, %29, %30, %31, "
    "%32, %33, %34, %35, %36, %37, %38, %39, %40, %41, %42, %43, %44, %45, %46, %47, "
    "%48, %49, %50, %51, %52, %53, %54, %55, %56, %57, %58, %59, %60, %61, %62, %63, "
    "%64, %65, %66, %67, %68, %69, %70, %71, %72, %73, %74, %75, %76, %77, %78, %79, "
    "%80, %81, %82, %83, %84, %85, %86, %87, %88, %89, %90, %91, %92, %93, %94, %95, "
    "%96, %97, %98, %99, %100, %101, %102, %103, %104, %105, %106, %107, %108, %109, %110, %111, "
    "%112, %113, %114, %115, %116, %117, %118, %119, %120, %121, %122, %123, %124, %125, %126, %127}, "
    "%128, %129, p, 1, 1, 0, 1;\n}"
    : "+f"(d[0]), "+f"(d[1]), "+f"(d[2]), "+f"(d[3]), "+f"(d[4]), "+f"(d[5]), "+f"(d[6]), "+f"(d[7]),
      "+f"(d[8]), "+f"(d[9]), "+f"(d[10]), "+f"(d[11]), "+f"(d[12]), "+f"(d[13]), "+f"(d[14]), "+f"(d[15]),
      "+f"(d[16]), "+f"(d[17]), "+f"(d[18]), "+f"(d[19]), "+f"(d[20]), "+f"(d[21]), "+f"(d[22]), "+f"(d[23]),
      "+f"(d[24]), "+f"(d[25]), "+f"(d[26]), "+f"(d[27]), "+f"(d[28]), "+f"(d[29]), "+f"(d[30]), "+f"(d[31]),
      "+f"(d[32]), "+f"(d[33]), "+f"(d[34]), "+f"(d[35]), "+f"(d[36]), "+f"(d[37]), "+f"(d[38]), "+f"(d[39]),
      "+f"(d[40]), "+f"(d[41]), "+f"(d[42]), "+f"(d[43]), "+f"(d[44]), "+f"(d[45]), "+f"(d[46]), "+f"(d[47]),
      "+f"(d[48]), "+f"(d[49]), "+f"(d[50]), "+f"(d[51]), "+f"(d[52]), "+f"(d[53]), "+f"(d[54]), "+f"(d[55]),
      "+f"(d[56]), "+f"(d[57]), "+f"(d[58]), "+f"(d[59]), "+f"(d[60]), "+f"(d[61]), "+f"(d[62]), "+f"(d[63]),
      "+f"(d[64]), "+f"(d[65]), "+f"(d[66]), "+f"(d[67]), "+f"(d[68]), "+f"(d[69]), "+f"(d[70]), "+f"(d[71]),
      "+f"(d[72]), "+f"(d[73]), "+f"(d[74]), "+f"(d[75]), "+f"(d[76]), "+f"(d[77]), "+f"(d[78]), "+f"(d[79]),
      "+f"(d[80]), "+f"(d[81]), "+f"(d[82]), "+f"(d[83]), "+f"(d[84]), "+f"(d[85]), "+f"(d[86]), "+f"(d[87]),
      "+f"(d[88]), "+f"(d[89]), "+f"(d[90]), "+f"(d[91]), "+f"(d[92]), "+f"(d[93]), "+f"(d[94]), "+f"(d[95]),
      "+f"(d[96]), "+f"(d[97]), "+f"(d[98]), "+f"(d[99]), "+f"(d[100]), "+f"(d[101]), "+f"(d[102]), "+f"(d[103]),
      "+f"(d[104]), "+f"(d[105]), "+f"(d[106]), "+f"(d[107]), "+f"(d[108]), "+f"(d[109]), "+f"(d[110]), "+f"(d[111]),
      "+f"(d[112]), "+f"(d[113]), "+f"(d[114]), "+f"(d[115]), "+f"(d[116]), "+f"(d[117]), "+f"(d[118]), "+f"(d[119]),
      "+f"(d[120]), "+f"(d[121]), "+f"(d[122]), "+f"(d[123]), "+f"(d[124]), "+f"(d[125]), "+f"(d[126]), "+f"(d[127])
    : "l"(da), "l"(db), "r"(sd));
}
__device__ __forceinline__ void wgmma_ss_n64(float (&d)[32], uint64_t da, uint64_t db, int sd) {
  asm volatile("{\n.reg .pred p;\nsetp.ne.b32 p, %34, 0;\n"
    "wgmma.mma_async.sync.aligned.m64n64k16.f32.bf16.bf16 "
    "{%0, %1, %2, %3, %4, %5, %6, %7, %8, %9, %10, %11, %12, %13, %14, %15, "
    "%16, %17, %18, %19, %20, %21, %22, %23, %24, %25, %26, %27, %28, %29, %30, %31}, "
    "%32, %33, p, 1, 1, 0, 0;\n}"
    : "+f"(d[0]), "+f"(d[1]), "+f"(d[2]), "+f"(d[3]), "+f"(d[4]), "+f"(d[5]), "+f"(d[6]), "+f"(d[7]),
      "+f"(d[8]), "+f"(d[9]), "+f"(d[10]), "+f"(d[11]), "+f"(d[12]), "+f"(d[13]), "+f"(d[14]), "+f"(d[15]),
      "+f"(d[16]), "+f"(d[17]), "+f"(d[18]), "+f"(d[19]), "+f"(d[20]), "+f"(d[21]), "+f"(d[22]), "+f"(d[23]),
      "+f"(d[24]), "+f"(d[25]), "+f"(d[26]), "+f"(d[27]), "+f"(d[28]), "+f"(d[29]), "+f"(d[30]), "+f"(d[31])
    : "l"(da), "l"(db), "r"(sd));
}
__device__ __forceinline__ void wgmma_ss_n64_tb(float (&d)[32], uint64_t da, uint64_t db, int sd) {
  asm volatile("{\n.reg .pred p;\nsetp.ne.b32 p, %34, 0;\n"
    "wgmma.mma_async.sync.aligned.m64n64k16.f32.bf16.bf16 "
    "{%0, %1, %2, %3, %4, %5, %6, %7, %8, %9, %10, %11, %12, %13, %14, %15, "
    "%16, %17, %18, %19, %20, %21, %22, %23, %24, %25, %26, %27, %28, %29, %30, %31}, "
    "%32, %33, p, 1, 1, 0, 1;\n}"
    : "+f"(d[0]), "+f"(d[1]), "+f"(d[2]), "+f"(d[3]), "+f"(d[4]), "+f"(d[5]), "+f"(d[6]), "+f"(d[7]),
      "+f"(d[8]), "+f"(d[9]), "+f"(d[10]), "+f"(d[11]), "+f"(d[12]), "+f"(d[13]), "+f"(d[14]), "+f"(d[15]),
      "+f"(d[16]), "+f"(d[17]), "+f"(d[18]), "+f"(d[19]), "+f"(d[20]), "+f"(d[21]), "+f"(d[22]), "+f"(d[23]),
      "+f"(d[24]), "+f"(d[25]), "+f"(d[26]), "+f"(d[27]), "+f"(d[28]), "+f"(d[29]), "+f"(d[30]), "+f"(d[31])
    : "l"(da), "l"(db), "r"(sd));
}
__device__ __forceinline__ void wgmma_rs_n256_tb(float (&d)[128], uint32_t a0, uint32_t a1, uint32_t a2, uint32_t a3, uint64_t db, int sd) {
  asm volatile("{\n.reg .pred p;\nsetp.ne.b32 p, %133, 0;\n"
    "wgmma.mma_async.sync.aligned.m64n256k16.f32.bf16.bf16 "
    "{%0, %1, %2, %3, %4, %5, %6, %7, %8, %9, %10, %11, %12, %13, %14, %15, "
    "%16, %17, %18, %19, %20, %21, %22, %23, %24, %25, %26, %27, %28, %29, %30, %31, "
    "%32, %33, %34, %35, %36, %37, %38, %39, %40, %41, %42, %43, %44, %45, %46, %47, "
    "%48, %49, %50, %51, %52, %53, %54, %55, %56, %57, %58, %59, %60, %61, %62, %63, "
    "%64, %65, %66, %67, %68, %69, %70, %71, %72, %73, %74, %75, %76, %77, %78, %79, "
    "%80, %81, %82, %83, %84, %85, %86, %87, %88, %89, %90, %91, %92, %93, %94, %95, "
    "%96, %97, %98, %99, %100, %101, %102, %103, %104, %105, %106, %107, %108, %109, %110, %111, "
    "%112, %113, %114, %115, %116, %117, %118, %119, %120, %121, %122, %123, %124, %125, %126, %127}, "
    "{%128, %129, %130, %131}, %132, p, 1, 1, 1;\n}"
    : "+f"(d[0]), "+f"(d[1]), "+f"(d[2]), "+f"(d[3]), "+f"(d[4]), "+f"(d[5]), "+f"(d[6]), "+f"(d[7]),
      "+f"(d[8]), "+f"(d[9]), "+f"(d[10]), "+f"(d[11]), "+f"(d[12]), "+f"(d[13]), "+f"(d[14]), "+f"(d[15]),
      "+f"(d[16]), "+f"(d[17]), "+f"(d[18]), "+f"(d[19]), "+f"(d[20]), "+f"(d[21]), "+f"(d[22]), "+f"(d[23]),
      "+f"(d[24]), "+f"(d[25]), "+f"(d[26]), "+f"(d[27]), "+f"(d[28]), "+f"(d[29]), "+f"(d[30]), "+f"(d[31]),
      "+f"(d[32]), "+f"(d[33]), "+f"(d[34]), "+f"(d[35]), "+f"(d[36]), "+f"(d[37]), "+f"(d[38]), "+f"(d[39]),
      "+f"(d[40]), "+f"(d[41]), "+f"(d[42]), "+f"(d[43]), "+f"(d[44]), "+f"(d[45]), "+f"(d[46]), "+f"(d[47]),
      "+f"(d[48]), "+f"(d[49]), "+f"(d[50]), "+f"(d[51]), "+f"(d[52]), "+f"(d[53]), "+f"(d[54]), "+f"(d[55]),
      "+f"(d[56]), "+f"(d[57]), "+f"(d[58]), "+f"(d[59]), "+f"(d[60]), "+f"(d[61]), "+f"(d[62]), "+f"(d[63]),
      "+f"(d[64]), "+f"(d[65]), "+f"(d[66]), "+f"(d[67]), "+f"(d[68]), "+f"(d[69]), "+f"(d[70]), "+f"(d[71]),
      "+f"(d[72]), "+f"(d[73]), "+f"(d[74]), "+f"(d[75]), "+f"(d[76]), "+f"(d[77]), "+f"(d[78]), "+f"(d[79]),
      "+f"(d[80]), "+f"(d[81]), "+f"(d[82]), "+f"(d[83]), "+f"(d[84]), "+f"(d[85]), "+f"(d[86]), "+f"(d[87]),
      "+f"(d[88]), "+f"(d[89]), "+f"(d[90]), "+f"(d[91]), "+f"(d[92]), "+f"(d[93]), "+f"(d[94]), "+f"(d[95]),
      "+f"(d[96]), "+f"(d[97]), "+f"(d[98]), "+f"(d[99]), "+f"(d[100]), "+f"(d[101]), "+f"(d[102]), "+f"(d[103]),
      "+f"(d[104]), "+f"(d[105]), "+f"(d[106]), "+f"(d[107]), "+f"(d[108]), "+f"(d[109]), "+f"(d[110]), "+f"(d[111]),
      "+f"(d[112]), "+f"(d[113]), "+f"(d[114]), "+f"(d[115]), "+f"(d[116]), "+f"(d[117]), "+f"(d[118]), "+f"(d[119]),
      "+f"(d[120]), "+f"(d[121]), "+f"(d[122]), "+f"(d[123]), "+f"(d[124]), "+f"(d[125]), "+f"(d[126]), "+f"(d[127])
    : "r"(a0), "r"(a1), "r"(a2), "r"(a3), "l"(db), "r"(sd));
}
__device__ __forceinline__ void wgmma_rs_n64_tb(float (&d)[32], uint32_t a0, uint32_t a1, uint32_t a2, uint32_t a3, uint64_t db, int sd) {
  asm volatile("{\n.reg .pred p;\nsetp.ne.b32 p, %37, 0;\n"
    "wgmma.mma_async.sync.aligned.m64n64k16.f32.bf16.bf16 "
    "{%0, %1, %2, %3, %4, %5, %6, %7, %8, %9, %10, %11, %12, %13, %14, %15, "
    "%16, %17, %18, %19, %20, %21, %22, %23, %24, %25, %26, %27, %28, %29, %30, %31}, "
    "{%32, %33, %34, %35}, %36, p, 1, 1, 1;\n}"
    : "+f"(d[0]), "+f"(d[1]), "+f"(d[2]), "+f"(d[3]), "+f"(d[4]), "+f"(d[5]), "+f"(d[6]), "+f"(d[7]),
      "+f"(d[8]), "+f"(d[9]), "+f"(d[10]), "+f"(d[11]), "+f"(d[12]), "+f"(d[13]), "+f"(d[14]), "+f"(d[15]),
      "+f"(d[16]), "+f"(d[17]), "+f"(d[18]), "+f"(d[19]), "+f"(d[20]), "+f"(d[21]), "+f"(d[22]), "+f"(d[23]),
      "+f"(d[24]), "+f"(d[25]), "+f"(d[26]), "+f"(d[27]), "+f"(d[28]), "+f"(d[29]), "+f"(d[30]), "+f"(d[31])
    : "r"(a0), "r"(a1), "r"(a2), "r"(a3), "l"(db), "r"(sd));
}
__device__ __forceinline__ void wgmma_rs_n64(float (&d)[32], uint32_t a0, uint32_t a1, uint32_t a2, uint32_t a3, uint64_t db, int sd) {
  asm volatile("{\n.reg .pred p;\nsetp.ne.b32 p, %37, 0;\n"
    "wgmma.mma_async.sync.aligned.m64n64k16.f32.bf16.bf16 "
    "{%0, %1, %2, %3, %4, %5, %6, %7, %8, %9, %10, %11, %12, %13, %14, %15, "
    "%16, %17, %18, %19, %20, %21, %22, %23, %24, %25, %26, %27, %28, %29, %30, %31}, "
    "{%32, %33, %34, %35}, %36, p, 1, 1, 0;\n}"
    : "+f"(d[0]), "+f"(d[1]), "+f"(d[2]), "+f"(d[3]), "+f"(d[4]), "+f"(d[5]), "+f"(d[6]), "+f"(d[7]),
      "+f"(d[8]), "+f"(d[9]), "+f"(d[10]), "+f"(d[11]), "+f"(d[12]), "+f"(d[13]), "+f"(d[14]), "+f"(d[15]),
      "+f"(d[16]), "+f"(d[17]), "+f"(d[18]), "+f"(d[19]), "+f"(d[20]), "+f"(d[21]), "+f"(d[22]), "+f"(d[23]),
      "+f"(d[24]), "+f"(d[25]), "+f"(d[26]), "+f"(d[27]), "+f"(d[28]), "+f"(d[29]), "+f"(d[30]), "+f"(d[31])
    : "r"(a0), "r"(a1), "r"(a2), "r"(a3), "l"(db), "r"(sd));
}

__device__ __forceinline__ uint4 lds16(uint32_t a) {
  uint4 v; asm volatile("ld.shared.v4.u32 {%0, %1, %2, %3}, [%4];" : "=r"(v.x), "=r"(v.y), "=r"(v.z), "=r"(v.w) : "r"(a) : "memory"); return v;
}
__device__ __forceinline__ void sts16(uint32_t a, uint32_t x, uint32_t y, uint32_t z, uint32_t w) {
  asm volatile("st.shared.v4.u32 [%0], {%1, %2, %3, %4};" :: "r"(a), "r"(x), "r"(y), "r"(z), "r"(w) : "memory");
}
__device__ __forceinline__ uint32_t lds4(uint32_t a) { uint32_t v; asm volatile("ld.shared.u32 %0, [%1];" : "=r"(v) : "r"(a) : "memory"); return v; }
__device__ __forceinline__ uint32_t lds4v(uint32_t a) { uint32_t v; asm volatile("ld.volatile.shared.u32 %0, [%1];" : "=r"(v) : "r"(a) : "memory"); return v; }
__device__ __forceinline__ uint32_t bmul(uint32_t a, uint32_t b) { uint32_t r; asm("mul.rn.bf16x2 %0, %1, %2;" : "=r"(r) : "r"(a), "r"(b)); return r; }
__device__ __forceinline__ uint32_t badd(uint32_t a, uint32_t b) { uint32_t r; asm("add.rn.bf16x2 %0, %1, %2;" : "=r"(r) : "r"(a), "r"(b)); return r; }

__device__ __forceinline__ uint32_t add_skip(uint32_t y, uint32_t x, uint32_t d) { return badd(y, bmul(x, d)); }
__device__ __forceinline__ void ldsm4(uint32_t (&r)[4], uint32_t a) {
  asm volatile("ldmatrix.sync.aligned.m8n8.x4.shared.b16 {%0, %1, %2, %3}, [%4];" : "=r"(r[0]), "=r"(r[1]), "=r"(r[2]), "=r"(r[3]) : "r"(a) : "memory");
}
__device__ __forceinline__ void ldsm4t(uint32_t (&r)[4], uint32_t a) {
  asm volatile("ldmatrix.sync.aligned.m8n8.x4.trans.shared.b16 {%0, %1, %2, %3}, [%4];" : "=r"(r[0]), "=r"(r[1]), "=r"(r[2]), "=r"(r[3]) : "r"(a) : "memory");
}
__device__ __forceinline__ uint32_t transpose8(uint32_t a) { uint32_t d; asm volatile("movmatrix.sync.aligned.m8n8.trans.b16 %0, %1;" : "=r"(d) : "r"(a)); return d; }

__device__ __forceinline__ void mma16816(float (&d)[4], const uint32_t (&a)[4], uint32_t b0, uint32_t b1) {
  asm volatile("mma.sync.aligned.m16n8k16.row.col.f32.bf16.bf16.f32 {%0, %1, %2, %3}, {%4, %5, %6, %7}, {%8, %9}, {%0, %1, %2, %3};"
               : "+f"(d[0]), "+f"(d[1]), "+f"(d[2]), "+f"(d[3]) : "r"(a[0]), "r"(a[1]), "r"(a[2]), "r"(a[3]), "r"(b0), "r"(b1));
}

#define STG_K1 2
#define STG_K2 10
#define STG_Q1 1
#define STG_Q2 5
#define PACE_A 400
#define PACE_B 100
#define PF_QA 48
#define PF_CV 64
#define PF_X 8
#define PF_WO 11
#define Q_PRE 2
#define O_PRE 12
#define ARRIVE_KK 12
#define SIDE_DELAY_NS 2000
#define EARLY_LD 2
#define HI_ORDER 9
constexpr int PP_BAR = 3;
template <int V> struct Int { static constexpr int value = V; };
struct Ring {
  uint32_t slot, phase;
  __device__ __forceinline__ void next() { if (++slot == NSLOT) { slot = 0; phase ^= 1; } }
};
__device__ __forceinline__ uint32_t bar_addr(uint32_t sb, uint32_t i) { return sb + BARS + 8 * i; }
__device__ __forceinline__ uint32_t q_region(uint32_t sb, int w) { return sb + QREG + (w ^ 1) * 32768; }

struct Role { int h, j; };
__device__ __forceinline__ Role get_role() {
  int cta; asm volatile("mov.u32 %0, %%ctaid.x;" : "=r"(cta));
  const int c = cta >> 1;
  int h, u;
  const int a = c - 4, b = c - 36, q = (b * 37) >> 8;
  h = a < 0 ? 8 : b < 0 ? a & 7 : 9 + b - 7 * q;
  u = a < 0 ? c : b < 0 ? a >> 3 : q;
  return Role{h, 2 * u + (cta & 1)};
}
__device__ __forceinline__ int fresh_warp() { return __shfl_sync(0xffffffffu, fresh_tid() >> 5, 0); }

__device__ __forceinline__ int q_tile(int h, int j, int which) { return ((h < 8) == (which == 0)) ? 15 - j : j; }

__device__ __forceinline__ int o_chunk(int h, int c) { const int x = c + (h & 7); return x % 7; }

__device__ __forceinline__ int kv_block(int j, int t) { return j + 8 * ((HI_ORDER >> t) & 1); }
__device__ __forceinline__ uint8_t* kv_tile(const Params& p, int v, int h, int tile) {
  return p.kv + (size_t)((v * NH + h) * 32 + tile) * 32768;
}

__device__ __forceinline__ void ring_acquire(uint32_t sb, Ring& r, uint32_t bytes) {
  mbar_wait(bar_addr(sb, B_RG_EMPTY + r.slot), r.phase ^ 1);
  mbar_expect_tx(bar_addr(sb, B_RG_FULL + r.slot), bytes);
}
__device__ __forceinline__ void producer_main(const Params& p, uint32_t sb) {
  const Role ro = get_role();
  const int h = ro.h, j = ro.j;
  for (int it = EARLY_LD; it < 71; it++) {
    const int t = it >> 4, k = it & 15, s = it & 3;
    mbar_wait(bar_addr(sb, B_P1_EMPTY + s), ((it >> 2) & 1) ^ 1);
    const uint32_t full = bar_addr(sb, B_P1_FULL + s), dst = sb + s * P1_STAGE;
    mbar_expect_tx(full, P1_STAGE);
    if (t < 4) {
      tma_ld2(dst, &p.ckv, full, k * 64, kv_block(j, t) * 128);
      tma_ld3(dst + 16384, (t >> 1) ? &p.wuv : &p.wuk, full, 0, k * 64, h * 4);
    } else {
      tma_ld2(dst, &p.x, full, k * 64, q_tile(h, j, 0) * 128);
      tma_ld3(dst + 16384, &p.wq, full, 0, k * 64, h * 4);
    }
    if (it >= PF_QA && it < PF_QA + 14) {
      const int i = it - PF_QA;
      bulk_prefetch(p.b_x + (size_t)(q_tile(h, j, 0) * 128 + (h & 7) * 16) * DM + i * 512, 1024);
      tma_pf2(&p.wqp, h * HD, (i * 8 + j) * 4);
    }
    if (it >= PF_CV && it < PF_CV + 3) {
      mbar_wait(bar_addr(sb, B_XS), 0);
      bulk_prefetch(g_xs + (size_t)(h * 8 + j) * CV_BYTES + (it - PF_CV) * (CV_BYTES / 3), CV_BYTES / 3);
    }
  }
  mbar_wait(bar_addr(sb, B_P1_EMPTY + 3), 0);
  mbar_wait(bar_addr(sb, B_XS), 0);
  mbar_expect_tx(bar_addr(sb, B_RG_FULL + 4), CV_BYTES);
  bulk_ld(sb + CV_X, g_xs + (size_t)(h * 8 + j) * CV_BYTES, CV_BYTES, bar_addr(sb, B_RG_FULL + 4));
  Ring r{0, 1};
  auto prefetch_wo = [&](int left) {
    const int i = PF_WO - left;
    if (PF_WO && i >= 0 && i < 8) bulk_prefetch(p.b_wo + (size_t)(h * HD + j * 32 + 4 * i) * DM, 4 * DM * 2);
  };
  mbar_wait(bar_addr(sb, B_KV), 0);
  for (int which = 0; which < 2; which++) {
    const int qt = q_tile(h, j, which);
    if (which == 1) {
      for (int kc = 0; kc < 7; kc++) {
        prefetch_wo(4 * qt + 4 + 7 - kc);
        ring_acquire(sb, r, 32768);
        tma_ld3(sb + r.slot * SLOT, &p.wq, bar_addr(sb, B_RG_FULL + r.slot), 0, kc * 64, h * 4);
        r.next();
        if (kc == 0 || (kc & 1)) {
          ring_acquire(sb, r, kc == 0 ? 16384 : 32768);
          const uint32_t full = bar_addr(sb, B_RG_FULL + r.slot), dst = sb + r.slot * SLOT;
          tma_ld2(dst, &p.x, full, kc * 64, qt * 128);
          if (kc > 0) tma_ld2(dst + 16384, &p.x, full, kc * 64 + 64, qt * 128);
          r.next();
        }
      }
    }
    const int n = 2 * qt + 2;
    for (int f = 0; f < 2 * n; f++) {
      if (which == 0) {
        const int i = f - max(2 * n - PF_X, 0);
        if (PF_X && i >= 0 && i < 4) bulk_prefetch(p.b_x + (size_t)((15 - qt) * 128 + (h & 7) * 16 + 4 * i) * DM, 4 * DM * 2);
      } else prefetch_wo(2 * n - f);
      const bool isK = (f == 0) || ((f & 1) && f < 2 * n - 1);
      const int i = isK ? (f + 1) >> 1 : (f == 2 * n - 1 ? n - 1 : (f >> 1) - 1);
      const int tile = which ? n - 1 - i : i;
      if (!isK) mbar_wait(bar_addr(sb, B_KV + 1 + ((tile >> 4) ^ ((HI_ORDER >> 2) & 1))), 0);
      if (which == 0 && f < 2) mbar_wait(bar_addr(sb, B_P1_EMPTY + f), 1);
      ring_acquire(sb, r, 32768);
      bulk_ld(sb + r.slot * SLOT, kv_tile(p, !isK, h, tile), 32768, bar_addr(sb, B_RG_FULL + r.slot));
      r.next();
    }
  }
  for (int i = 0; i < 14; i++) {
    ring_acquire(sb, r, 32768);
    tma_ld2(sb + r.slot * SLOT, &p.wo, bar_addr(sb, B_RG_FULL + r.slot), o_chunk(h, i >> 1) * 64, ((i & 1) ? h ^ 8 : h) * HD);
    r.next();
  }
}

__device__ __forceinline__ void storer_main(const Params& p, uint32_t sb) {
  const Role ro = get_role();
  const int h = ro.h, j = ro.j, w = fresh_warp() - 1;
  const uint32_t full = bar_addr(sb, B_ST_FULL + w), empty = bar_addr(sb, B_ST_EMPTY + w);
  const int lane = threadIdx.x & 31;
  const unsigned epoch = load_epoch();
  if (lane == 0) {
    for (int job = 0; job < 8; job++) {
      const int t = job >> 1;
      uint8_t* dst = kv_tile(p, t >> 1, h, 2 * kv_block(j, t) + w) + (job & 1) * 16384;
      mbar_wait_nap(full, job & 1);
      for (int i = 0; i < 8; i++) {
        if (i) __nanosleep(job < 6 ? PACE_A : PACE_B);
        bulk_st(dst + i * 2048, sb + P1_STG + w * 16384 + i * 2048, 2048);
      }
      bulk_commit();
      bulk_wait_read();
      mbar_arrive(empty);
      if (job >= 3 && (job & 1)) { bulk_wait_all(); flag_signal(&g_flags.kv_ready[3 * h + t - 1].v); }
    }
  }
  __syncwarp();
  const int cta = h * 8 + j, qt = q_tile(h, j, 1);
  const uint32_t qreg = q_region(sb, w);
  {
    mbar_wait_nap(bar_addr(sb, B_CTXS + 4 * w), 0);
    uint4* z = reinterpret_cast<uint4*>(p.out + (size_t)(qt * 128 + w * 64 + (h & 7) * 8 + (lane >> 2)) * OUTW + DA) + (lane & 3);
#pragma unroll
    for (int i = 0; i < 14; i++) z[4 * i] = make_uint4(0, 0, 0, 0);
    __syncwarp();
    if (lane != 0) return;
    for (int b = 0; b < 4; b++) {
      mbar_wait(bar_addr(sb, B_CTXS + 4 * w + b), 0);
      bulk_st(p.ctx + (size_t)(cta * 2 + w) * 32768 + b * 8192, qreg + b * 8192, 8192);
      bulk_commit();
    }
    bulk_wait_read();
    mbar_arrive(empty);
    bulk_wait_all();
    flag_signal(&g_flags.ctx_ready[cta * 2 + w].v);
    flag_signal_after_bulk(&g_flags.out_ready[qt * 2 + w].v);
  }
  {
    const int wx = w ^ 1;
    flag_wait(&g_flags.ctx_ready[(cta ^ 64) * 2 + wx].v, 1, epoch);
    flag_wait(&g_flags.out_ready[qt * 2 + wx].v, 8, epoch);
    fence_async_all();
    mbar_wait_nap(bar_addr(sb, B_QFREE + w), 0);
    mbar_expect_tx(bar_addr(sb, B_CTXF + w), 32768);
    bulk_ld(qreg, p.ctx + (size_t)((cta ^ 64) * 2 + wx) * 32768, 32768, bar_addr(sb, B_CTXF + w));
    for (int ch = 0; ch < 7; ch++) {
      const int b = ch & 1;
      mbar_wait(bar_addr(sb, B_S2_FULL + w * 2 + b), (ch >> 1) & 1);
      tma_red2(&p.part, qreg + b * 8192, DA + o_chunk(h, ch) * 64, qt * 128 + wx * 64);
      bulk_commit();
      if (ch == 0 && w == 1) mbar_arrive(bar_addr(sb, B_GFREE));
      bulk_wait_read();
      mbar_arrive(bar_addr(sb, B_S2_EMPTY + w * 2 + b));
    }
  }
}

template <int OFF, int NB, int NREG>
__device__ __forceinline__ void store_blocks(uint32_t base, uint32_t lanebase, const uint32_t (&pk)[NREG]) {
#pragma unroll
  for (int J = 0; J < NB * 8; J += 2) {
    const uint32_t a = base + (J >> 3) * 8192 + (lanebase ^ ((J & 7) << 4));
    stsm4(a, pk[OFF + 2 * J], pk[OFF + 2 * J + 1], pk[OFF + 2 * J + 2], pk[OFF + 2 * J + 3]);
  }
}
__device__ __forceinline__ void warp_arrive(uint32_t bar, int lane) { __syncwarp(); if (lane == 0) mbar_arrive(bar); }
__device__ __forceinline__ void release(uint32_t bar, int lane) { lane0_arrive(bar, 1, lane); }

template <int W> __device__ __forceinline__ constexpr int cv_tile(int u) { return 2 * u + ((u ^ W) & 1); }
__device__ __forceinline__ uint32_t cv_x_lane(uint32_t lane) { return (16 + (lane & 15) - (lane >> 4)) * 16; }
__device__ __forceinline__ uint32_t cv_h_lane(uint32_t lane, uint32_t hE, uint32_t hO) {
  const uint32_t g = lane >> 2, c = lane & 3;
  return (g & 1) ? hO + (15 + 2 * c - g) * 2 : hE + (16 + 2 * c - g) * 2;
}
template <int W>
__device__ __forceinline__ void conv_mma(float (&ca)[8][4], uint32_t xa, uint32_t ha, uint32_t sb, uint32_t lb, const uint32_t (&pk)[64], uint32_t one) {
  constexpr int N = 16 - W;
  uint32_t fx[N][4], fh[N][2];
  auto ld_h = [&](int i, int rr) { fh[i][0] = lds4(ha + i * 256 + rr * 128); fh[i][1] = lds4(ha + i * 256 + rr * 128 + 16); };
  uint32_t c1 = 0, c3 = 0;
  ldsm4(fx[0], xa);
#pragma unroll
  for (int u = 0; u < 8; u++) ld_h(cv_tile<W>(u), 0);
  ldsm4(fx[1], xa + 256);
#pragma unroll
  for (int u = 0; u < 8; u++) if (cv_tile<W ^ 1>(u) < N) ld_h(cv_tile<W ^ 1>(u), 0);
#pragma unroll
  for (int i = 2; i < N; i++) ldsm4(fx[i], xa + i * 256);
#pragma unroll
  for (int sx = 0; sx < N; sx++) {
#pragma unroll
    for (int u = 0; u < 8; u++) {
      const int jj = cv_tile<W>(u) - sx;
      if (jj >= 0) mma16816(ca[u], fx[sx], fh[jj < 0 ? 0 : jj][0], fh[jj < 0 ? 0 : jj][1]);
    }
    {
      const uint32_t t1 = fx[sx][1], t3 = fx[sx][3];
      fx[sx][1] = fx[sx][0] * one; fx[sx][3] = fx[sx][2] ^ (one - 1); fx[sx][0] = c1 * one; fx[sx][2] = c3 ^ (one - 1);
      c1 = t1; c3 = t3;
    }
    ld_h(N - 1 - sx, 1);
  }
  mbar_wait(bar_addr(sb, B_P1_EMPTY + 2), 1);
  if (W == 0) { mbar_wait(bar_addr(sb, B_ST_EMPTY), 1); mbar_wait(bar_addr(sb, B_ST_EMPTY + 1), 1); }
#pragma unroll
  for (int jj = 15; jj >= 0; jj--) {
    if (W == 0) stsm4(q_region(sb, W) + (jj >> 2) * 8192 + (lb ^ ((jj & 3) << 5)), pk[4 * jj], pk[4 * jj + 1], pk[4 * jj + 2], pk[4 * jj + 3]);
#pragma unroll
    for (int u = 0; u < 8; u++) {
      const int sx = cv_tile<W>(u) - jj;
      if (sx >= 0) mma16816(ca[u], fx[sx < 0 ? 0 : sx], fh[jj < N ? jj : 0][0], fh[jj < N ? jj : 0][1]);
    }
  }
}

__device__ __forceinline__ void consumer_main(const Params& p, uint32_t sb, uint8_t* xs_base, uint32_t one) {
  const int lane = fresh_tid() & 31, w = (fresh_warp() >> 2) - 1;
  const uint32_t lb = lane_base16();
  int qt, cc;
  { const Role ro = get_role(); qt = q_tile(ro.h, ro.j, 0); cc = ro.h * 8 + ro.j; }
  const uint32_t st_full = bar_addr(sb, B_ST_FULL + w), st_empty = bar_addr(sb, B_ST_EMPTY + w);
  const uint32_t stg = sb + P1_STG + w * 16384;

  auto turn_begin = [&]() { named_sync(PP_BAR + w, 256); };
  auto turn_end = [&]() { named_arrive(PP_BAR + (w ^ 1), 256); };
  float acc[128];
#pragma unroll
  for (int i = 0; i < 128; i++) acc[i] = 0.f;
  uint32_t pk[64];
#pragma unroll
  for (int i = 0; i < 64; i++) pk[i] = 0;
  if (fresh_warp() != 4) named_sync(0, NTHREADS);
  const uint32_t qreg = q_region(sb, w);
  for (int t = 0; t < 5; t++) {
    const int nk = t < 4 ? 16 : 7;
#pragma unroll 1
    for (int k = 0; k < nk; k++) {
      const int it = t * 16 + k, s = k & 3;
      if (it == 0) { mbar_wait(bar_addr(sb, B_P1_FULL), 0); turn_begin(); }
      const uint64_t da = desc_k(sb + s * P1_STAGE + w * 8192), db = desc_mn(sb + s * P1_STAGE + 16384);
      wg_fence();
#pragma unroll
      for (int kk = 0; kk < 4; kk++) wgmma_ss_n256_tb(acc, desc_add(da, kk * 32), desc_add(db, kk * 2048), (k | kk) != 0);
      wg_commit();
      turn_end();
      wg_wait<1>();
      if (k > 0) release(bar_addr(sb, B_P1_EMPTY + ((k - 1) & 3)), lane);
      const int k1 = t < 4 ? STG_K1 : STG_Q1, k2 = t < 4 ? STG_K2 : STG_Q2;
      if (t > 0 && (k == k1 || k == k2)) {
        const int job = 2 * (t - 1) + (k != k1);
        mbar_wait(job > 0 ? st_empty : bar_addr(sb, B_SIDE + 1), job > 0 ? (job - 1) & 1 : 0);
        if (k == k1) store_blocks<0, 2>(stg, lb, pk); else store_blocks<32, 2>(stg, lb, pk);
      }
      if (t > 0 && (k == k1 + 1 || k == k2 + 1)) { fence_async_smem(); warp_arrive(st_full, lane); }
      if (it < 70) { mbar_wait(bar_addr(sb, B_P1_FULL + ((k + 1) & 3)), ((it + 1) >> 2) & 1); turn_begin(); }
      else mbar_wait(bar_addr(sb, B_RG_FULL + 4), 0);
    }
    wg_wait<0>();
    reg_fence(acc);
    release(bar_addr(sb, B_P1_EMPTY + ((nk - 1) & 3)), lane);
#pragma unroll
    for (int i = 0; i < 64; i++) pk[i] = pack_bf16(acc[2 * i], acc[2 * i + 1]);
  }
  {
    const uint32_t wq = lb >> 11, ln = lane, cx = sb + CV_X;
    float ca[8][4];
#pragma unroll
    for (int i = 0; i < 8; i++) { ca[i][0] = 0.f; ca[i][1] = 0.f; ca[i][2] = 0.f; ca[i][3] = 0.f; }
    const uint32_t xa = cx + cv_x_lane(ln) - wq * 32, ha = cv_h_lane(ln, cx + CV_HE, cx + CV_HE + CV_HCOPY) + wq * 32;
    if (w) conv_mma<1>(ca, xa, ha, sb, lb, pk, one); else conv_mma<0>(ca, xa, ha, sb, lb, pk, one);
    const uint32_t ex = sb + CV_R + w * 16384 + ln * 16;
#pragma unroll
    for (int u = 0; u < 8; u++)
      sts16(ex + (wq * 8 + u) * 512, __float_as_uint(ca[u][0]), __float_as_uint(ca[u][1]), __float_as_uint(ca[u][2]), __float_as_uint(ca[u][3]));
  }
  auto conv_finish = [&]() {
    const uint32_t wq = lb >> 11, cx = sb + CV_X, ex = sb + CV_R + w * 16384 + lane * 16;
    uint8_t* gz = xs_base + (size_t)cc * CV_BYTES;
    const uint32_t Dd = lds4(cx + CV_D);
#pragma unroll
    for (int e = 0; e < 2; e++) {
      const uint32_t u = 2 * wq + e, nt = 2 * u + ((e ^ w) & 1);
      float y[4] = {0.f, 0.f, 0.f, 0.f};
#pragma unroll
      for (int v = 0; v < 4; v++) {
        const uint4 t = lds16(ex + (v * 8 + u) * 512);
        y[0] += __uint_as_float(t.x); y[1] += __uint_as_float(t.y); y[2] += __uint_as_float(t.z); y[3] += __uint_as_float(t.w);
      }
      const uint32_t o = (16 + 16 * nt) * 16 + lane * 4;
      *reinterpret_cast<uint32_t*>(gz + o)       = badd(pack_bf16(y[0], y[1]), bmul(lds4(cx + o), Dd));
      *reinterpret_cast<uint32_t*>(gz + o + 128) = badd(pack_bf16(y[2], y[3]), bmul(lds4(cx + o + 128), Dd));
    }
    __syncwarp();
    release(bar_addr(sb, B_RG_EMPTY + 3), lane);
    release(bar_addr(sb, B_RG_EMPTY + 4), lane);
    if (lane == 0) mbar_arrive(bar_addr(sb, B_CONV));
  };
  Ring r{0, 1};
  auto take = [&]() { const uint32_t sl = r.slot; mbar_wait(bar_addr(sb, B_RG_FULL + sl), r.phase); r.next(); return sl; };
  constexpr float SC = 0.0625f * 1.4426950408889634f;
  uint32_t ws;
#pragma unroll 1
  for (int which = 0;; which++) {
    float s[32];
#pragma unroll
    for (int i = 0; i < 32; i++) s[i] = 0.f;
    uint32_t pa[16];
    float b0, b1, l0, l1;
    const uint64_t dq = desc_k(qreg);
    uint64_t dk = 0, dqq = 0, dv = 0;
    auto prep_qk = [&](uint32_t kaddr) { dk = desc_k(kaddr); dqq = dq + (kaddr >> 31); asm volatile("" : "+l"(dk), "+l"(dqq)); };
    auto prep_pv = [&](uint32_t vaddr) { dv = desc_mn(vaddr); asm volatile("" : "+l"(dv)); };
    auto issue_qk = [&]() {
#pragma unroll
      for (int kk = 0; kk < 16; kk++)
        wgmma_ss_n64(s, desc_add(dqq, (kk >> 2) * 8192 + (kk & 3) * 32), desc_add(dk, (kk >> 2) * 8192 + (kk & 3) * 32), kk != 0);
    };
    auto issue_pv = [&](int accumulate) {
#pragma unroll
      for (int kk = 0; kk < 4; kk++)
        wgmma_rs_n256_tb(acc, pa[4 * kk], pa[4 * kk + 1], pa[4 * kk + 2], pa[4 * kk + 3], desc_add(dv, kk * 2048), accumulate | kk);
    };
    auto mask_diag = [&]() {
      const int d = (int)((lb >> 11) << 4) + (lane >> 2) - 2 * (lane & 3);
#pragma unroll
      for (int jj = 0; jj < 8; jj++) {
        if (8 * jj > d)     s[4 * jj]     = -INFINITY;
        if (8 * jj + 1 > d) s[4 * jj + 1] = -INFINITY;
        if (8 * jj - 8 > d) s[4 * jj + 2] = -INFINITY;
        if (8 * jj - 7 > d) s[4 * jj + 3] = -INFINITY;
      }
    };
    auto row_max = [&](float& x0, float& x1) {
      x0 = fmaxf(s[0], s[1]); x1 = fmaxf(s[2], s[3]);
#pragma unroll
      for (int jj = 1; jj < 8; jj++) {
        x0 = fmaxf(x0, fmaxf(s[4 * jj], s[4 * jj + 1]));
        x1 = fmaxf(x1, fmaxf(s[4 * jj + 2], s[4 * jj + 3]));
      }
      x0 = fmaxf(x0, __shfl_xor_sync(0xffffffffu, x0, 1));
      x1 = fmaxf(x1, __shfl_xor_sync(0xffffffffu, x1, 1));
      x0 = fmaxf(x0, __shfl_xor_sync(0xffffffffu, x0, 2));
      x1 = fmaxf(x1, __shfl_xor_sync(0xffffffffu, x1, 2));
    };
    auto exps = [&](uint32_t (&pp)[16], float& r0, float& r1) {
      float t0, t1, t2, t3;
#pragma unroll
      for (int jj = 0; jj < 8; jj++) {
        const float e0 = ex2(fmaf(s[4 * jj], SC, b0)), e1 = ex2(fmaf(s[4 * jj + 1], SC, b0));
        const float e2 = ex2(fmaf(s[4 * jj + 2], SC, b1)), e3 = ex2(fmaf(s[4 * jj + 3], SC, b1));
        if (jj == 0) { t0 = e0; t1 = e1; t2 = e2; t3 = e3; } else { t0 += e0; t1 += e1; t2 += e2; t3 += e3; }
        pp[2 * jj] = pack_bf16(e0, e1); pp[2 * jj + 1] = pack_bf16(e2, e3);
      }
      r0 = t0 + t1; r1 = t2 + t3;
    };

    const bool up = w == which;
    const int n = 2 * qt + 2, nw = n - up;
    int fd = which ? 0 : 2 * n - 1;
    const int dir = which ? 1 : -1;
    auto skip = [&]() { r.next(); fd += dir; };
    auto give = [&](uint32_t sl, int d) {
      lane0_arrive(bar_addr(sb, B_RG_EMPTY + sl), (d & ~2) == 0 ? 2 : 1, lane);
    };
    if (which && up) skip();
    uint32_t ks = take();
    prep_qk(sb + ks * SLOT);
    turn_begin();
    wg_fence();
#pragma unroll
    for (int kk = 0; kk < 16; kk++)
      wgmma_rs_n64(s, pk[4 * kk], pk[4 * kk + 1], pk[4 * kk + 2], pk[4 * kk + 3], desc_add(dk, (kk >> 2) * 8192 + (kk & 3) * 32), kk != 0);
    wg_commit();
    turn_end();
    if (!which && up) conv_finish();
    if (which) mbar_wait(st_empty, 0);
    if (!up) store_blocks<0, Q_PRE>(qreg, lb, pk);
    wg_wait<0>();
    reg_fence(s);
    reg_fence(pk);
    give(ks, fd);
    fd += dir;
    if (which && up) { skip(); store_blocks<0, 4>(qreg, lb, pk); }
    if (which || nw == 1) mask_diag();
    row_max(b0, b1);
    if (!up) store_blocks<16 * Q_PRE, 4 - Q_PRE>(qreg + Q_PRE * 8192, lb, pk);
    b0 *= -SC; b1 *= -SC;
#pragma unroll
    for (int i = 0; i < 128; i++) acc[i] = 0.f;
    exps(pa, l0, l1);
    if (!which && !up) conv_finish();
    if (which && nw == 1) { fence_async_smem(); warp_arrive(bar_addr(sb, B_QFREE + w), lane); }
#pragma unroll 1
    for (int jj = 1; jj < nw; jj++) {
      ks = take();
      const uint32_t vs = take();
      if (jj == 1) fence_async_smem();
#pragma unroll
      for (int i = 0; i < 32; i++) s[i] = 0.f;
      prep_qk(sb + ks * SLOT);
      prep_pv(sb + vs * SLOT);
      turn_begin();
      wg_fence();
      issue_qk();
      wg_commit();
      issue_pv(1);
      wg_commit();
      turn_end();
      wg_wait<1>();
      reg_fence(s);
      give(ks, fd);
      if (jj == nw - 1) {
        if (!which) mask_diag();
        else if (lane == 0) mbar_arrive(bar_addr(sb, B_QFREE + w));
      }
      uint32_t pn[16];
      float t0, t1, a0 = 1.f, a1 = 1.f;
      exps(pn, t0, t1);
      const bool redo = __any_sync(0xffffffffu, !(t0 + t1 <= 0x1p30f));
      if (redo) {
        row_max(a0, a1);
        const float c0 = fminf(b0, -SC * a0), c1 = fminf(b1, -SC * a1);
        a0 = ex2(c0 - b0); a1 = ex2(c1 - b1);
        b0 = c0; b1 = c1;
        l0 *= a0; l1 *= a1;
        exps(pn, t0, t1);
      }
      l0 += t0; l1 += t1;
      wg_wait<0>();
      reg_fence(acc);
      reg_fence(pa);
      give(vs, fd + dir);
      fd += 2 * dir;
      if (redo) {
#pragma unroll
        for (int i = 0; i < 32; i++) { acc[4 * i] *= a0; acc[4 * i + 1] *= a0; acc[4 * i + 2] *= a1; acc[4 * i + 3] *= a1; }
      }
#pragma unroll
      for (int i = 0; i < 16; i++) pa[i] = (i & 1) ? pn[i] ^ (one - 1) : pn[i] * one;
    }
    if (!which && up) skip();
    const uint32_t vs = take();
    prep_pv(sb + vs * SLOT);
    turn_begin();
    wg_fence();
    issue_pv(1);
    wg_commit();
    turn_end();
    if (!which && up) r.next();
    ws = take();
    l0 += __shfl_xor_sync(0xffffffffu, l0, 1); l1 += __shfl_xor_sync(0xffffffffu, l1, 1);
    l0 += __shfl_xor_sync(0xffffffffu, l0, 2); l1 += __shfl_xor_sync(0xffffffffu, l1, 2);
    float i0, i1;
    asm volatile("rcp.approx.ftz.f32 %0, %1;" : "=f"(i0) : "f"(l0));
    asm volatile("rcp.approx.ftz.f32 %0, %1;" : "=f"(i1) : "f"(l1));
    uint32_t xs = 0;
    if (!which) xs = take();
    wg_wait<0>();
    reg_fence(acc);
    reg_fence(pa);
    give(vs, fd);
#pragma unroll
    for (int i = 0; i < 32; i++) {
      pk[2 * i]     = pack_bf16(acc[4 * i] * i0, acc[4 * i + 1] * i0);
      pk[2 * i + 1] = pack_bf16(acc[4 * i + 2] * i1, acc[4 * i + 3] * i1);
    }
    if (which) break;
    uint32_t xaddr = sb + xs * SLOT + (w ^ 1) * 8192;
#pragma unroll 1
    for (int kc = 0;; kc++) {
      const uint64_t da = desc_k(xaddr), db = desc_mn(sb + ws * SLOT);
      turn_begin();
      wg_fence();
#pragma unroll
      for (int kk = 0; kk < 4; kk++) wgmma_ss_n256_tb(acc, desc_add(da, kk * 32), desc_add(db, kk * 2048), (kc | kk) != 0);
      wg_commit();
      turn_end();
      const int cb = kc;
      if (cb >= 1 && cb <= 4) { fence_async_smem(); warp_arrive(bar_addr(sb, B_CTXS + 4 * w + cb - 1), lane); }
      if ((unsigned)cb < 4) {
        if (cb & 2) { if (cb & 1) store_blocks<48, 1>(qreg + 24576, lb, pk); else store_blocks<32, 1>(qreg + 16384, lb, pk); }
        else        { if (cb & 1) store_blocks<16, 1>(qreg + 8192, lb, pk);  else store_blocks<0, 1>(qreg, lb, pk); }
      }
      wg_wait<0>();
      release(bar_addr(sb, B_RG_EMPTY + ws), lane);
      if (!(kc & 1)) release(bar_addr(sb, B_RG_EMPTY + xs), lane);
      if (kc == 6) break;
      ws = take();
      if (!(kc & 1)) { xs = take(); xaddr = sb + xs * SLOT + (w ^ 1) * 8192; } else xaddr += 16384;
    }
    reg_fence(acc);
#pragma unroll
    for (int i = 0; i < 64; i++) pk[i] = pack_bf16(acc[2 * i], acc[2 * i + 1]);
    qt = 15 - qt;
  }

  {
    float oa[32], ob[32];
#pragma unroll
    for (int i = 0; i < 32; i++) { oa[i] = 0.f; ob[i] = 0.f; }
    auto stage_o = [&](float (&o)[32], int ch) {
      reg_fence(o);
      uint32_t q[16];
#pragma unroll
      for (int i = 0; i < 16; i++) q[i] = pack_bf16(o[2 * i], o[2 * i + 1]);
      if (ch >= 2) mbar_wait(bar_addr(sb, B_S2_EMPTY + w * 2 + (ch & 1)), ((ch >> 1) - 1) & 1);
      store_blocks<0, 1>(qreg + (ch & 1) * 8192, lb, q);
    };
    auto hand_over = [&](int ch) {
      fence_async_smem();
      warp_arrive(bar_addr(sb, B_S2_FULL + w * 2 + (ch & 1)), lane);
    };
    uint32_t pk2[64];
    uint32_t p2 = 0;
    auto chunk = [&](int ch, auto first, float (&o)[32], float (&oprev)[32]) {
      constexpr bool FIRST = decltype(first)::value;
      const uint32_t s1 = FIRST ? ws : take();
      const uint64_t d1 = desc_mn(sb + s1 * SLOT);
      turn_begin();
      wg_fence();
#pragma unroll
      for (int kk = 0; kk < 16; kk++) {
        wgmma_rs_n64_tb(o, pk[4 * kk], pk[4 * kk + 1], pk[4 * kk + 2], pk[4 * kk + 3], desc_add(d1, kk * 2048), kk != 0);
        if (kk == ARRIVE_KK) turn_end();
      }
      wg_commit();
      if constexpr (!FIRST) {
        wg_wait<1>();
        release(bar_addr(sb, B_RG_EMPTY + p2), lane);
        stage_o(oprev, ch - 1);
      } else {
        mbar_wait(bar_addr(sb, B_CTXF + w), 0);
#pragma unroll
        for (int kk = 0; kk < O_PRE; kk++) {
          uint32_t f[4];
          ldsm4(f, qreg + (kk >> 2) * 8192 + (lb ^ ((kk & 3) << 5)));
          pk2[4 * kk] = f[0]; pk2[4 * kk + 1] = f[1]; pk2[4 * kk + 2] = f[2]; pk2[4 * kk + 3] = f[3];
        }
      }
      const uint32_t s2 = take();
      const uint64_t d2 = desc_mn(sb + s2 * SLOT);
      turn_begin();
      wg_fence();
#pragma unroll
      for (int kk = 0; kk < 16; kk++) {
        if (FIRST && kk >= O_PRE) wgmma_ss_n64_tb(o, desc_add(desc_k(qreg), (kk >> 2) * 8192 + (kk & 3) * 32), desc_add(d2, kk * 2048), 1);
        else wgmma_rs_n64_tb(o, pk2[4 * kk], pk2[4 * kk + 1], pk2[4 * kk + 2], pk2[4 * kk + 3], desc_add(d2, kk * 2048), 1);
        if (kk == ARRIVE_KK && (ch < 6 || w == 1)) turn_end();
      }
      wg_commit();
      if (!FIRST) hand_over(ch - 1);
      if constexpr (FIRST) {
#pragma unroll
        for (int kk = O_PRE; kk < 16; kk++) {
          uint32_t f[4];
          ldsm4(f, qreg + (kk >> 2) * 8192 + (lb ^ ((kk & 3) << 5)));
          pk2[4 * kk] = f[0]; pk2[4 * kk + 1] = f[1]; pk2[4 * kk + 2] = f[2]; pk2[4 * kk + 3] = f[3];
        }
      }
      wg_wait<1>();
      release(bar_addr(sb, B_RG_EMPTY + s1), lane);
      p2 = s2;
    };
    chunk(0, Int<1>(), oa, ob);
#pragma unroll 1
    for (int ch = 1; ch < 7; ch += 2) { chunk(ch, Int<0>(), ob, oa); chunk(ch + 1, Int<0>(), oa, ob); }
    wg_wait<0>();
    reg_fence(pk);
    reg_fence(pk2);
    stage_o(oa, 6);
    hand_over(6);
  }

}

#define CONV_STAGGER_NS 1200
namespace ssm {
#define CONV_GROUPS (D_SPARE / 8 / NCONV)
constexpr int GROUPS = CONV_GROUPS;
constexpr uint32_t ZROWS = 16;
constexpr uint32_t CHAN = (ZROWS + 256 + 1) * 16;
constexpr uint32_t XBUF = 8 * CHAN;
constexpr uint32_t OFF_X = 0;
constexpr uint32_t HCOPY = 4160;
constexpr uint32_t OFF_H = 2 * XBUF;
constexpr uint32_t HWARP = 3 * HCOPY;
constexpr uint32_t IO_K = 128, IO_V = IO_K + 4096, IO_Q = IO_V + 4096, IOBUF = IO_Q + 4096;
constexpr uint32_t OFF_IO = (OFF_H + 8 * HWARP + 127) / 128 * 128;
constexpr uint32_t END = OFF_IO + 4 * IOBUF;
static_assert(IOBUF % 128 == 0 && OFF_H % 16 == 0, "TMA destination alignment");
static_assert(END <= BARS, "smem");
enum : uint32_t { B_XREADY = 0, B_ZDONE = 2, B_KV = 4, B_Q = 8, B_HRAW = 12, B_QLAST = 20 };
constexpr int CW_BAR = 4;

__device__ __forceinline__ int group_d0(int cidx, int grp) { return (grp * NCONV + cidx) * 8; }
__device__ __forceinline__ uint32_t x_lane(int lane) { return (lane & 7) * CHAN + (ZROWS + (lane >> 3)) * 16; }
__device__ __forceinline__ uint32_t t_lane(int lane) { return (uint32_t)(8 * (lane >> 3) + 7 - (lane & 7)) * 16; }
struct Taps { uint32_t s[4]; };
__device__ __forceinline__ Taps load_taps(const Params& p, int d0, int c) {
  const uint2 s0 = __ldg(reinterpret_cast<const uint2*>(p.a_shift + (d0 + 2 * c) * 4)), s1 = __ldg(reinterpret_cast<const uint2*>(p.a_shift + (d0 + 2 * c + 1) * 4));
  return Taps{{__byte_perm(s0.x, s1.x, 0x5410), __byte_perm(s0.x, s1.x, 0x7632), __byte_perm(s0.y, s1.y, 0x5410), __byte_perm(s0.y, s1.y, 0x7632)}};
}
__device__ __forceinline__ uint32_t short_conv(const Taps& t, uint32_t k0, uint32_t k1, uint32_t k2, uint32_t k3, uint32_t v) {
  return bmul(badd(badd(badd(bmul(k0, t.s[3]), bmul(k1, t.s[2])), bmul(k2, t.s[1])), bmul(k3, t.s[0])), v);
}
template <int U>
__device__ __forceinline__ void x_chunk(const Taps& taps, uint32_t ka, uint32_t xa) {
#pragma unroll 1
  for (int u0 = 0; u0 < 8; u0 += U) {
    uint32_t k0[U][4], k1[U][4], k2[U][4], k3[U][4], vv[U][4];
#pragma unroll
    for (int u = 0; u < U; u++) {
      const uint32_t a = ka + (u0 + u) * 512;
      ldsm4(k0[u], a - 48); ldsm4(k1[u], a - 32); ldsm4(k2[u], a - 16); ldsm4(k3[u], a); ldsm4(vv[u], a + 4096);
    }
#pragma unroll
    for (int u = 0; u < U; u++)
      stsm4t(xa + (u0 + u) * 64, short_conv(taps, k0[u][0], k1[u][0], k2[u][0], k3[u][0], vv[u][0]), short_conv(taps, k0[u][1], k1[u][1], k2[u][1], k3[u][1], vv[u][1]),
             short_conv(taps, k0[u][2], k1[u][2], k2[u][2], k3[u][2], vv[u][2]), short_conv(taps, k0[u][3], k1[u][3], k2[u][3], k3[u][3], vv[u][3]));
  }
}
template <int U>
__device__ __forceinline__ void shift_filter(uint32_t hE, uint32_t hO, int lane) {
#pragma unroll 1
  for (int i0 = 0; i0 < 8; i0 += U) {
    uint4 w[U]; uint32_t nx[U];
    const uint32_t o = 32 + lane * 16 + i0 * 512;
#pragma unroll
    for (int i = 0; i < U; i++) { w[i] = lds16(hE + o + i * 512); nx[i] = lds4(hE + o + i * 512 + 16); }
#pragma unroll
    for (int i = 0; i < U; i++)
      sts16(hO + o + i * 512, __byte_perm(w[i].x, w[i].y, 0x5432), __byte_perm(w[i].y, w[i].z, 0x5432), __byte_perm(w[i].z, w[i].w, 0x5432), __byte_perm(w[i].w, nx[i], 0x5432));
    if (o == 32) asm volatile("st.shared.u32 [%0], %1;" :: "r"(hO + 28), "r"(w[0].x << 16) : "memory");
  }
}
template <int U>
__device__ __forceinline__ void gate_chunk(uint32_t xa, uint32_t qa) {
#pragma unroll 1
  for (int i0 = 0; i0 < 8; i0 += U) {
    uint32_t zz[U][4], qq[U][4];
#pragma unroll
    for (int i = 0; i < U; i++) { ldsm4t(zz[i], xa + (i0 + i) * 64); ldsm4(qq[i], qa + (i0 + i) * 512); }
#pragma unroll
    for (int i = 0; i < U; i++) stsm4(qa + (i0 + i) * 512, bmul(qq[i][0], zz[i][0]), bmul(qq[i][1], zz[i][1]), bmul(qq[i][2], zz[i][2]), bmul(qq[i][3], zz[i][3]));
  }
}

__device__ __forceinline__ void io_warp(const Params& p, uint32_t sb, int cidx, int wq) {
  const int lane = threadIdx.x & 31;
  const uint32_t io = sb + OFF_IO + wq * IOBUF, bkv = bar_addr(sb, B_KV + wq), bq = bar_addr(sb, B_Q + wq);
  auto load_kv = [&](int e) {
    __syncwarp();
    if (lane != 0) return;
    const int d0 = group_d0(cidx, e >> 1), row = (2 * wq + (e & 1)) * 256;
    if (e < 2 * GROUPS) {
      mbar_expect_tx(bkv, IO_Q);
      tma_ld2(io, &p.ak8, bkv, d0, row - 8);
      tma_ld2(io + IO_K, &p.ak, bkv, d0, row);
      tma_ld2(io + IO_V, &p.av, bkv, d0, row);
    } else {
      const uint32_t bar = bar_addr(sb, B_QLAST + 2 * wq + 1);
      mbar_expect_tx(bar, 4096);
      tma_ld2(io + IO_K, &p.aq, bar, group_d0(cidx, GROUPS - 1), row + 256);
    }
  };
  auto load_q = [&](int e) {
    __syncwarp();
    if (lane != 0) return;
    const uint32_t bar = e < 2 * GROUPS - 2 ? bq : bar_addr(sb, B_QLAST + 2 * wq);
    mbar_expect_tx(bar, 4096);
    tma_ld2(io + IO_Q, &p.aq, bar, group_d0(cidx, e >> 1), (2 * wq + (e & 1)) * 256);
  };
  load_kv(0);
  const uint32_t xl = sb + OFF_X + x_lane(lane) + wq * 1024, tl = io + t_lane(lane);
#pragma unroll 1
  for (int grp = -2; grp + 1 < GROUPS; grp++) {
    const bool more = grp + 2 < GROUPS;
    const Taps taps = load_taps(p, group_d0(cidx, more ? grp + 2 : 0), lane & 3);
    if (grp >= 0) mbar_wait_nap(bar_addr(sb, B_ZDONE + (grp & 1)), (grp >> 1) & 1);

#pragma unroll 1
    for (int i = 0; i < 2; i++) {
      const uint32_t xa = xl + (grp & 1) * XBUF + i * 512;
      if (grp >= 0) {
        mbar_wait_nap(bq, i);
        gate_chunk<4>(xa, tl + IO_Q);
      }
      if (more) {
        mbar_wait_nap(bkv, i);
        x_chunk<2>(taps, tl + IO_K, xa);
        load_kv(2 * (grp + 2) + i + 1);
        if (i == 1) warp_arrive(bar_addr(sb, B_XREADY + (grp & 1)), lane);
      }
      if (grp >= 0) {
        fence_async_smem();
        __syncwarp();
        if (lane == 0) {
          tma_st2(&p.ao, io + IO_Q, group_d0(cidx, grp), (2 * wq + i) * 256);
          bulk_commit();
          bulk_wait_read();
        }
      }
      if (2 * grp + i + 1 >= 0) load_q(2 * grp + i + 1);
    }
  }
  if (lane == 0) bulk_wait_all();
}

__device__ __forceinline__ void conv_warp(const Params& p, uint32_t sb, int cidx, int ch) {
  const int lane = threadIdx.x & 31;
  const uint32_t hE0 = sb + OFF_H + ch * HWARP, hO = hE0 + HCOPY;
  const uint32_t hbar = bar_addr(sb, B_HRAW + ch);
  auto fetch_h = [&](int grp) {
    if (lane == 0) {
      mbar_expect_tx(hbar, 4096);
      asm volatile("cp.async.bulk.shared::cluster.global.mbarrier::complete_tx::bytes [%0], [%1], %2, [%3];"
                   :: "r"(hE0 + (grp & 1) * 2 * HCOPY + 32), "l"(p.a_ssmk + (size_t)(group_d0(cidx, grp) + ch) * SEQ), "r"(4096), "r"(hbar) : "memory");
    }
  };
  fetch_h(0);
#pragma unroll 1
  for (int grp = 0; grp < GROUPS; grp++) {
    const uint32_t xc = sb + OFF_X + (grp & 1) * XBUF + ch * CHAN;
    const uint32_t D1 = __ldg(reinterpret_cast<const unsigned short*>(p.a_D + group_d0(cidx, grp) + ch));
    mbar_wait(hbar, grp & 1);
    const uint32_t hE = hE0 + (grp & 1) * 2 * HCOPY;
    if (grp + 1 < GROUPS) fetch_h(grp + 1);
    shift_filter<8>(hE, hO, lane);
    __syncwarp();
    const uint32_t ha = cv_h_lane(lane, hE, hO), xa = xc + cv_x_lane(lane);
    mbar_wait(bar_addr(sb, B_XREADY + (grp & 1)), (grp >> 1) & 1);
    if (grp == 0 && ch >= 4) __nanosleep(CONV_STAGGER_NS);

    float acc[16][4];
#pragma unroll
    for (int i = 0; i < 16; i++) { acc[i][0] = 0.f; acc[i][1] = 0.f; acc[i][2] = 0.f; acc[i][3] = 0.f; }
#pragma unroll 1
    for (int r = 0; r < 8; r++) {
      uint32_t fx[16][4], fh[16][2];
#pragma unroll
      for (int i = 0; i < 16; i++) { fh[i][0] = lds4(ha + i * 256 + r * 32); fh[i][1] = lds4(ha + i * 256 + r * 32 + 16); }
#pragma unroll
      for (int i = 0; i < 16; i++) ldsm4(fx[i], xa + i * 256 - r * 32);
#pragma unroll
      for (int sx = 0; sx < 16; sx++)
#pragma unroll
        for (int jj = 0; jj < 16 - sx; jj++) mma16816(acc[jj + sx], fx[sx], fh[jj][0], fh[jj][1]);
    }

    {
      uint32_t x[8][4], Dd;
      asm volatile("prmt.b32 %0, %1, %1, 0x1010;" : "=r"(Dd) : "r"(D1));
      const uint32_t ad = xc + (ZROWS + lane) * 16;
#pragma unroll
      for (int i = 0; i < 8; i++) ldsm4(x[i], ad + i * 512);
#pragma unroll
      for (int i = 0; i < 8; i++)
        stsm4(ad + i * 512, add_skip(pack_bf16(acc[2 * i][0], acc[2 * i][1]), x[i][0], Dd), add_skip(pack_bf16(acc[2 * i][2], acc[2 * i][3]), x[i][1], Dd),
              add_skip(pack_bf16(acc[2 * i + 1][0], acc[2 * i + 1][1]), x[i][2], Dd), add_skip(pack_bf16(acc[2 * i + 1][2], acc[2 * i + 1][3]), x[i][3], Dd));
    }
    if (grp + 1 < GROUPS) warp_arrive(bar_addr(sb, B_ZDONE + (grp & 1)), lane);
  }
  {
    mbar_wait(bar_addr(sb, B_QLAST + ch), 0);
    named_sync(CW_BAR, 256);
    const uint32_t qb = sb + OFF_IO + (ch >> 1) * IOBUF + ((ch & 1) ? IO_K : IO_Q);
    gate_chunk<8>(sb + OFF_X + ((GROUPS - 1) & 1) * XBUF + x_lane(lane) + ch * 512, qb + t_lane(lane));
    fence_async_smem();
    __syncwarp();
    if (lane == 0) { tma_st2(&p.ao, qb, group_d0(cidx, GROUPS - 1), ch * 256); bulk_commit(); bulk_wait_read(); }
  }
}

__device__ __forceinline__ void init(uint32_t sb) {
  if (threadIdx.x < 16 * ZROWS) sts16(sb + OFF_X + (threadIdx.x >> 4) * CHAN + (threadIdx.x & 15) * 16, 0, 0, 0, 0);
  if (threadIdx.x < 96) sts16(sb + OFF_H + (threadIdx.x >> 2) * HCOPY + (threadIdx.x & 1) * 16 + ((threadIdx.x & 2) ? 4128 : 0), 0, 0, 0, 0);
  if (threadIdx.x == 0) {
    for (int i = 0; i < 2; i++) { mbar_init(bar_addr(sb, B_XREADY + i), 4); mbar_init(bar_addr(sb, B_ZDONE + i), 8); }
    for (int i = 0; i < 4; i++) { mbar_init(bar_addr(sb, B_KV + i), 1); mbar_init(bar_addr(sb, B_Q + i), 1); }
    for (int i = 0; i < 8; i++) { mbar_init(bar_addr(sb, B_HRAW + i), 1); mbar_init(bar_addr(sb, B_QLAST + i), 1); }
    fence_async_smem();
  }
  named_sync(0, NTHREADS);
}
}

__device__ __forceinline__ void ssm_side_work(const Params& p, uint32_t sb, unsigned epoch) {
  const Role ro = get_role();
  const int h = ro.h, j = ro.j;
  const int lane = threadIdx.x & 31;
  const int d0 = D_SPARE + 8 * h;
  constexpr uint32_t ZCH = 528;
  {
    const uint32_t kb = sb + P1_STG, xb = kb + 8320, hE = xb + 8 * ZCH, hO = hE + CV_HCOPY, zero = hO + CV_HCOPY, bar = bar_addr(sb, B_SIDE);
    if (lane == 0) {
      mbar_expect_tx(bar, 128 + 3 * 4096);
      tma_ld2(kb, &p.ak8, bar, d0, 256 * j - 8);
      tma_ld2(kb + 128, &p.ak, bar, d0, 256 * j);
      bulk_ld(hE + 32, p.a_ssmk + (size_t)(d0 + j) * SEQ, 4096, bar);
      __nanosleep(600);
      tma_ld2(kb + 128 + 4096, &p.av, bar, d0, 256 * j);
    }
    const ssm::Taps taps = ssm::load_taps(p, d0, lane & 3);
    const uint32_t Dd = (uint32_t)__ldg(reinterpret_cast<const unsigned short*>(p.a_D + d0 + j)) * 0x10001u;
    if (lane < 16) sts16(zero + lane * 16, 0, 0, 0, 0);
    else if (lane < 24) sts16(hE + ((lane >> 2) & 1) * CV_HCOPY + (lane & 1) * 16 + ((lane & 2) ? 4128 : 0), lane == 19 ? Dd : 0, 0, 0, 0);
    __syncwarp();
    mbar_wait_nap(bar, 0);
    ssm::x_chunk<1>(taps, kb + 128 + ssm::t_lane(lane), xb + (lane & 7) * ZCH + (lane >> 3) * 16);
    ssm::shift_filter<2>(hE, hO, lane);
    fence_async_smem();
    __syncwarp();
    if (lane == 0) {
      uint8_t* img = g_xs + (size_t)(h * 8) * CV_BYTES;
      for (int i = 0; i < 8; i++) bulk_st(img + i * CV_BYTES + (16 + 32 * j) * 16, xb + i * ZCH, 512);
      bulk_st(img + j * CV_BYTES, zero, 256);
      for (int i = 0; i < 4; i++) { __nanosleep(200); bulk_st(img + j * CV_BYTES + CV_HE + i * (CV_HCOPY / 2), hE + i * (CV_HCOPY / 2), CV_HCOPY / 2); }
      bulk_commit();
      bulk_wait_read();
      mbar_arrive(bar_addr(sb, B_SIDE + 1));
      bulk_wait_all();
      flag_signal(&g_flags.xs_ready[h].v);
      flag_wait(&g_flags.xs_ready[h].v, 8, epoch);
      fence_async_all();
      mbar_arrive(bar_addr(sb, B_XS));
    }
  }
  if (lane == 0) {
    for (int i = 0; i < 3; i++) {
      flag_wait(&g_flags.kv_ready[3 * h + i].v, 16, epoch);
      fence_async_all();
      mbar_arrive(bar_addr(sb, B_KV + i));
    }
    mbar_wait_nap(bar_addr(sb, B_CONV), 0);
    flag_signal(&g_flags.zs_ready[h].v);
    flag_wait(&g_flags.zs_ready[h].v, 8, epoch);
    asm volatile("red.relaxed.gpu.global.add.u64 [%0], 1;" :: "l"(&g_flags.done) : "memory");
  }
  __syncwarp();
  fence_async_all();
  const uint32_t qb = q_region(sb, 1) + 16384, zb = qb + 4096, bar = bar_addr(sb, B_GATE);
  mbar_wait_slow(bar_addr(sb, B_GFREE), 0);
  if (lane == 0) { mbar_expect_tx(bar, 8192); tma_ld2(qb, &p.aq, bar, d0, 256 * j); }
  __syncwarp();
  if (lane < 8) bulk_ld(zb + lane * ZCH, g_xs + (size_t)(h * 8 + lane) * CV_BYTES + (16 + 32 * j) * 16, 512, bar);
  mbar_wait(bar, 0);
  ssm::gate_chunk<2>(zb + (lane & 7) * ZCH + (lane >> 3) * 16, qb + ssm::t_lane(lane));
  fence_async_smem();
  __syncwarp();
  if (lane == 0) { tma_st2(&p.ao, qb, d0, 256 * j); bulk_commit(); bulk_wait_all(); }
}

__global__ void __cluster_dims__(2, 1, 1) __launch_bounds__(NTHREADS, 1)
concat_heads__ssm_conv_h3__compressed_kv_cla__prompt_kernel(uint8_t* xs, uint32_t one, const __grid_constant__ Params p) {
  if (threadIdx.x == 0) { prefetch_map(&p.wuk); prefetch_map(&p.ckv); }
  extern __shared__ uint8_t smem_raw[];
  const uint32_t sb = (smem_u32(smem_raw) + 1023) & ~1023u;
  const int warp = __shfl_sync(0xffffffffu, threadIdx.x >> 5, 0);
  const int wg = warp >> 2;
  const int cta = blockIdx.x;
  const bool attn = cta < NMAIN;
  if (attn && (threadIdx.x >> 5) == 4) {
    const Role ro = get_role();
    auto load = [&](int k) {
      const uint32_t full = bar_addr(sb, B_P1_FULL + k), dst = sb + k * P1_STAGE;
      mbar_expect_tx(full, P1_STAGE);
      tma_ld2(dst, &p.ckv, full, k * 64, kv_block(ro.j, 0) * 128);
      tma_ld3(dst + 16384, &p.wuk, full, 0, k * 64, ro.h * 4);
    };
    if (threadIdx.x == 128) {
      for (int i = 0; i < 4; i++) mbar_init(bar_addr(sb, B_P1_FULL + i), 1);
      asm volatile("fence.mbarrier_init.release.cluster;" ::: "memory");
      load(0);
    }
    __syncwarp();
    named_arrive(0, NTHREADS);
    if (threadIdx.x == 128) {
      for (int k = 1; k < EARLY_LD; k++) load(k);
    }
    __syncwarp();
  }
  const int lane = threadIdx.x & 31;
  if (wg == 0) {
    if (!attn) {
      asm volatile("setmaxnreg.dec.sync.aligned.u32 72;");
      if (one) { ssm::init(sb); ssm::io_warp(p, sb, cta - NMAIN, fresh_warp()); }
      return;
    }
    asm volatile("setmaxnreg.dec.sync.aligned.u32 40;");
    named_arrive(PP_BAR + 1, 256);
    if (warp == 2) {
      if (lane == 0) {
        for (int i = 0; i < 4; i++) mbar_init(bar_addr(sb, B_P1_EMPTY + i), 8);
        for (int i = 0; i < NSLOT; i++) {
          mbar_init(bar_addr(sb, B_RG_FULL + i), 1); mbar_init(bar_addr(sb, B_RG_EMPTY + i), 8);
        }
        for (int i = 0; i < 2; i++) { mbar_init(bar_addr(sb, B_ST_FULL + i), 4); mbar_init(bar_addr(sb, B_ST_EMPTY + i), 1); }
        mbar_init(bar_addr(sb, B_XS), 1); mbar_init(bar_addr(sb, B_SIDE), 1); mbar_init(bar_addr(sb, B_SIDE + 1), 1); mbar_init(bar_addr(sb, B_CONV), 8); mbar_init(bar_addr(sb, B_GATE), 1); mbar_init(bar_addr(sb, B_GFREE), 1);
        for (int i = 0; i < 3; i++) mbar_init(bar_addr(sb, B_KV + i), 1);
        for (int i = 0; i < 8; i++) mbar_init(bar_addr(sb, B_CTXS + i), 4);
        for (int i = 0; i < 4; i++) { mbar_arrive(bar_addr(sb, B_RG_FULL + i)); if (i < 3) mbar_arrive_n(bar_addr(sb, B_RG_EMPTY + i), 8); }
        for (int i = 0; i < 4; i++) { mbar_init(bar_addr(sb, B_S2_FULL + i), 4); mbar_init(bar_addr(sb, B_S2_EMPTY + i), 1); }
        for (int i = 0; i < 2; i++) { mbar_init(bar_addr(sb, B_QFREE + i), 4); mbar_init(bar_addr(sb, B_CTXF + i), 1); }
        asm volatile("fence.mbarrier_init.release.cluster;" ::: "memory");
      }
      __syncwarp();
      named_arrive(0, NTHREADS);
    } else {
      named_sync(0, NTHREADS);
    }
    if (warp == 0) {
      if (lane == 0) producer_main(p, sb);
    } else if (warp < 3) {
      storer_main(p, sb);
    } else {
      const unsigned epoch = load_epoch();
      mbar_wait(bar_addr(sb, B_P1_FULL + 3), 0);
      __nanosleep(SIDE_DELAY_NS);
      ssm_side_work(p, sb, epoch);
    }
  } else {
    if (attn) {
      asm volatile("setmaxnreg.inc.sync.aligned.u32 232;");
      if (one) consumer_main(p, sb, xs, one);
    } else {
      asm volatile("setmaxnreg.inc.sync.aligned.u32 216;");
      if (one) { ssm::init(sb); ssm::conv_warp(p, sb, cta - NMAIN, fresh_warp() - 4); }
    }
  }
}

typedef CUresult (*EncodeTiledFn)(CUtensorMap*, CUtensorMapDataType, cuuint32_t, void*, const cuuint64_t*, const cuuint64_t*,
                                  const cuuint32_t*, const cuuint32_t*, CUtensorMapInterleave, CUtensorMapSwizzle,
                                  CUtensorMapL2promotion, CUtensorMapFloatOOBfill);

void make_map(EncodeTiledFn enc, CUtensorMap* m, const void* ptr, int rank, const uint64_t* dims, const uint64_t* strides, const uint32_t* box) {
  cuuint64_t d[3], s[2]; cuuint32_t b[3], e[3] = {1, 1, 1};
  for (int i = 0; i < rank; i++) { d[i] = dims[i]; b[i] = box[i]; if (i) s[i - 1] = strides[i - 1]; }
  enc(m, CU_TENSOR_MAP_DATA_TYPE_BFLOAT16, rank, const_cast<void*>(ptr), d, s, b, e, CU_TENSOR_MAP_INTERLEAVE_NONE,
      CU_TENSOR_MAP_SWIZZLE_128B, CU_TENSOR_MAP_L2_PROMOTION_L2_256B, CU_TENSOR_MAP_FLOAT_OOB_FILL_NONE);
}
void map2(EncodeTiledFn enc, CUtensorMap* m, const void* ptr, uint64_t cols, uint64_t rows, uint32_t bc, uint32_t br) {
  const uint64_t dims[2] = {cols, rows}, st[1] = {cols * 2}; const uint32_t box[2] = {bc, br};
  make_map(enc, m, ptr, 2, dims, st, box);
}
void map2_plain(EncodeTiledFn enc, CUtensorMap* m, const void* ptr, uint64_t cols, uint64_t rows, uint32_t bc, uint32_t br) {
  cuuint64_t d[2] = {cols, rows}, st[1] = {cols * 2}; cuuint32_t b[2] = {bc, br}, e[2] = {1, 1};
  enc(m, CU_TENSOR_MAP_DATA_TYPE_BFLOAT16, 2, const_cast<void*>(ptr), d, st, b, e, CU_TENSOR_MAP_INTERLEAVE_NONE,
      CU_TENSOR_MAP_SWIZZLE_NONE, CU_TENSOR_MAP_L2_PROMOTION_L2_128B, CU_TENSOR_MAP_FLOAT_OOB_FILL_NONE);
}
void map3(EncodeTiledFn enc, CUtensorMap* m, const void* ptr, uint64_t rows, uint32_t nblk) {
  const uint64_t dims[3] = {64, rows, 64}, st[2] = {8192, 128}; const uint32_t box[3] = {64, 64, nblk};
  make_map(enc, m, ptr, 3, dims, st, box);
}

}

extern "C" void kernel_launch(void* const* d_in, const int* in_sizes, int n_in, void* d_out, int out_size) {
  (void)in_sizes; (void)n_in; (void)out_size;
  static EncodeTiledFn enc = nullptr;
  static void *kv_ptr = nullptr, *acc_ptr = nullptr, *xs_ptr = nullptr;
  if (!enc) {
    void* fn = nullptr; cudaDriverEntryPointQueryResult qr;
    cudaGetDriverEntryPoint("cuTensorMapEncodeTiled", &fn, cudaEnableDefault, &qr);
    enc = (EncodeTiledFn)fn;
    cudaGetSymbolAddress(&kv_ptr, g_kv);
    cudaGetSymbolAddress(&acc_ptr, g_ctx);
    cudaGetSymbolAddress(&xs_ptr, g_xs);
    cudaFuncSetAttribute(concat_heads__ssm_conv_h3__compressed_kv_cla__prompt_kernel, cudaFuncAttributeMaxDynamicSharedMemorySize, SMEM_BYTES);
  }
  Params p;
  map2_plain(enc, &p.aq, d_in[0], DA, SEQ, 8, 256);
  map2_plain(enc, &p.ak, d_in[1], DA, SEQ, 8, 256);
  map2_plain(enc, &p.ak8, d_in[1], DA, SEQ, 8, 8);
  map2_plain(enc, &p.av, d_in[2], DA, SEQ, 8, 256);
  map2_plain(enc, &p.ao, d_out, OUTW, SEQ, 8, 256);
  p.a_shift = (const bf16*)d_in[3]; p.a_ssmk = (const bf16*)d_in[4]; p.a_D = (const bf16*)d_in[5];
  p.out = (bf16*)d_out; p.b_x = (const bf16*)d_in[6]; p.b_wo = (const bf16*)d_in[11];
  map2(enc, &p.x, d_in[6], DM, SEQ, 64, 128);
  map2(enc, &p.ckv, d_in[7], DC, SEQ, 64, 128);
  map3(enc, &p.wq, d_in[8], DM, 4);
  map2_plain(enc, &p.wqp, d_in[8], NH * HD, DM, 256, 4);
  map3(enc, &p.wuk, d_in[9], DC, 4);
  map3(enc, &p.wuv, d_in[10], DC, 4);
  map2(enc, &p.wo, d_in[11], DM, NH * HD, 64, 256);
  map2(enc, &p.part, d_out, OUTW, SEQ, 64, 64);
  p.kv = (uint8_t*)kv_ptr; p.ctx = (uint8_t*)acc_ptr;
  concat_heads__ssm_conv_h3__compressed_kv_cla__prompt_kernel<<<NCTA, NTHREADS, SMEM_BYTES>>>((uint8_t*)xs_ptr, 1u, p);
}
```

```cpp
#include <cuda_runtime.h>
#include <cuda_bf16.h>
#include <cuda.h>
#include <stdint.h>

namespace {

typedef __nv_bfloat16 bf16;

constexpr int SEQ  = 2048;
constexpr int DA   = 448;
constexpr int NH   = 16;
constexpr int HD   = 256;
constexpr int DM   = 448;
constexpr int DC   = 1024;
constexpr int OUTW = DA + DM;
constexpr int NMAIN = 128;
constexpr int NCONV = 4;
constexpr int NCTA  = NMAIN + NCONV;
constexpr int NTHREADS = 384;
constexpr int D_SPARE = 320;

__device__ __align__(1024) bf16 g_kv[2ull * SEQ * NH * HD];
__device__ __align__(1024) bf16 g_ctx[(size_t)NMAIN * 128 * HD];
constexpr uint32_t CV_HE = 272 * 16, CV_HCOPY = 4160, CV_D = CV_HE + 4144, CV_BYTES = CV_HE + 2 * CV_HCOPY;
__device__ __align__(128) uint8_t g_xs[NMAIN * CV_BYTES];
struct alignas(128) Flag { unsigned v; unsigned pad[31]; };
struct Flags {
  Flag kv_ready[3 * NH];
  Flag ctx_ready[NMAIN];
  Flag out_ready[16];
  Flag xs_ready[NH];
  Flag zs_ready[NH];
  alignas(128) unsigned long long done;
};
__device__ Flags g_flags;

struct alignas(64) Params {
  CUtensorMap ckv;
  CUtensorMap wuk;
  CUtensorMap wuv;
  CUtensorMap x;
  CUtensorMap wq;
  CUtensorMap wqp;
  CUtensorMap part;
  CUtensorMap wo;
  CUtensorMap ak, ak8, av, aq, ao;
  const bf16 *a_shift, *a_ssmk, *a_D, *b_x, *b_wo;
  bf16* out;
  uint8_t *kv, *ctx;
};

constexpr uint32_t P1_STAGE = 49152;
constexpr uint32_t P1_STG   = 196608;
constexpr uint32_t SLOT     = 32768;
constexpr int      NSLOT    = 5;
constexpr uint32_t QREG     = 163840;
constexpr uint32_t CV_X = 4 * SLOT + 16384, CV_R = 3 * SLOT;
static_assert(CV_BYTES <= 16384 && CV_BYTES % 128 == 0, "SSM operands");
constexpr uint32_t BARS     = 229376;
constexpr uint32_t ZEROS    = BARS + 512;
constexpr uint32_t SMEM_BYTES = ZEROS + 1024 + 1024;
enum : uint32_t {
  B_P1_FULL = 0, B_P1_EMPTY = 4, B_RG_FULL = 8, B_RG_EMPTY = 13, B_ST_FULL = 18, B_ST_EMPTY = 20,
  B_XS = 22, B_SIDE = 23, B_CTXD = 25, B_S2_FULL = 28, B_S2_EMPTY = 32, B_QFREE = 36, B_CTXF = 38, B_KV = 40, B_GATE = 43, B_CTXS = 44, B_GFREE = 52, B_CONV = 53, B_COUNT = 54
};

__device__ __forceinline__ uint32_t smem_u32(const void* p) { return (uint32_t)__cvta_generic_to_shared(p); }
__device__ __forceinline__ void mbar_init(uint32_t bar, uint32_t cnt) {
  asm volatile("mbarrier.init.shared::cta.b64 [%0], %1;" :: "r"(bar), "r"(cnt) : "memory");
}
__device__ __forceinline__ void mbar_expect_tx(uint32_t bar, uint32_t bytes) {
  asm volatile("mbarrier.arrive.expect_tx.shared::cta.b64 _, [%0], %1;" :: "r"(bar), "r"(bytes) : "memory");
}
__device__ __forceinline__ void mbar_arrive(uint32_t bar) {
  asm volatile("mbarrier.arrive.shared::cta.b64 _, [%0];" :: "r"(bar) : "memory");
}
__device__ __forceinline__ void mbar_arrive_n(uint32_t bar, uint32_t n) {
  asm volatile("mbarrier.arrive.shared::cta.b64 _, [%0], %1;" :: "r"(bar), "r"(n) : "memory");
}
__device__ __forceinline__ void lane0_arrive(uint32_t bar, uint32_t n, int lane) {
  asm volatile("{\n.reg .pred p;\nsetp.eq.s32 p, %2, 0;\n@p mbarrier.arrive.shared::cta.b64 _, [%0], %1;\n}" :: "r"(bar), "r"(n), "r"(lane) : "memory");
}
__device__ __forceinline__ bool mbar_try(uint32_t bar, uint32_t parity) {
  uint32_t ok;
  asm volatile("{\n.reg .pred p;\nmbarrier.try_wait.parity.shared::cta.b64 p, [%1], %2;\nselp.u32 %0, 1, 0, p;\n}"
               : "=r"(ok) : "r"(bar), "r"(parity) : "memory");
  return ok;
}
#define FLAG_NS 100
#define NAP_NS 100
constexpr uint32_t SPIN_LIMIT = 1u << 24;
__device__ __forceinline__ void mbar_wait(uint32_t bar, uint32_t parity) {
  if (mbar_try(bar, parity)) return;
  uint32_t n = 0;
  while (!mbar_try(bar, parity)) { if (++n > SPIN_LIMIT) __trap(); }
}
__device__ __forceinline__ void mbar_wait_nap(uint32_t bar, uint32_t parity) {
  uint32_t n = 0;
  while (!mbar_try(bar, parity)) { if (++n > (SPIN_LIMIT >> 2)) __trap(); __nanosleep(NAP_NS); }
}
__device__ __forceinline__ void mbar_wait_slow(uint32_t bar, uint32_t parity) {
  uint32_t n = 0;
  while (!mbar_try(bar, parity)) { if (++n > (SPIN_LIMIT >> 4)) __trap(); __nanosleep(500); }
}
__device__ __forceinline__ unsigned load_epoch() {
  unsigned long long e; asm volatile("ld.relaxed.gpu.global.u64 %0, [%1];" : "=l"(e) : "l"(&g_flags.done) : "memory"); return (unsigned)(e / NMAIN);
}
__device__ __forceinline__ void flag_wait(const unsigned* f, unsigned count, unsigned epoch) {
  const unsigned target = (epoch + 1) * count;
  uint32_t n = 0;
  while (true) {
    unsigned v;
    asm volatile("ld.acquire.gpu.global.u32 %0, [%1];" : "=r"(v) : "l"(f) : "memory");
    if ((int)(v - target) >= 0) break;
    if (++n > SPIN_LIMIT) __trap();
    __nanosleep(FLAG_NS);
  }
}
__device__ __forceinline__ void fence_async_all() { asm volatile("fence.proxy.async;" ::: "memory"); }
__device__ __forceinline__ void flag_signal(unsigned* f) {
  asm volatile("fence.acq_rel.gpu;" ::: "memory");
  asm volatile("red.relaxed.gpu.global.add.u32 [%0], 1;" :: "l"(f) : "memory");
}
__device__ __forceinline__ void flag_signal_again(unsigned* f) {
  asm volatile("red.relaxed.gpu.global.add.u32 [%0], 1;" :: "l"(f) : "memory");
}
__device__ __forceinline__ void fence_async_smem() { asm volatile("fence.proxy.async.shared::cta;" ::: "memory"); }
__device__ __forceinline__ void tma_ld2(uint32_t dst, const CUtensorMap* m, uint32_t bar, int c0, int c1) {
  asm volatile("cp.async.bulk.tensor.2d.shared::cluster.global.mbarrier::complete_tx::bytes [%0], [%1, {%3, %4}], [%2];"
               :: "r"(dst), "l"(m), "r"(bar), "r"(c0), "r"(c1) : "memory");
}
__device__ __forceinline__ void tma_ld3(uint32_t dst, const CUtensorMap* m, uint32_t bar, int c0, int c1, int c2) {
  asm volatile("cp.async.bulk.tensor.3d.shared::cluster.global.mbarrier::complete_tx::bytes [%0], [%1, {%3, %4, %5}], [%2];"
               :: "r"(dst), "l"(m), "r"(bar), "r"(c0), "r"(c1), "r"(c2) : "memory");
}
__device__ __forceinline__ void bulk_ld(uint32_t dst, const void* src, uint32_t bytes, uint32_t bar) {
  asm volatile("cp.async.bulk.shared::cluster.global.mbarrier::complete_tx::bytes [%0], [%1], %2, [%3];"
               :: "r"(dst), "l"(src), "r"(bytes), "r"(bar) : "memory");
}
__device__ __forceinline__ void bulk_st(void* dst, uint32_t src, uint32_t bytes) {
  asm volatile("cp.async.bulk.global.shared::cta.bulk_group [%0], [%1], %2;" :: "l"(dst), "r"(src), "r"(bytes) : "memory");
}
__device__ __forceinline__ void tma_st2(const CUtensorMap* m, uint32_t src, int c0, int c1) {
  asm volatile("cp.async.bulk.tensor.2d.global.shared::cta.bulk_group [%0, {%2, %3}], [%1];"
               :: "l"(m), "r"(src), "r"(c0), "r"(c1) : "memory");
}
__device__ __forceinline__ void tma_red2(const CUtensorMap* m, uint32_t src, int c0, int c1) {
  asm volatile("cp.reduce.async.bulk.tensor.2d.global.shared::cta.add.tile.bulk_group [%0, {%2, %3}], [%1];"
               :: "l"(m), "r"(src), "r"(c0), "r"(c1) : "memory");
}
__device__ __forceinline__ void tma_pf2(const CUtensorMap* m, int c0, int c1) {
  asm volatile("cp.async.bulk.prefetch.tensor.2d.L2.global.tile [%0, {%1, %2}];" :: "l"(m), "r"(c0), "r"(c1) : "memory");
}
__device__ __forceinline__ void bulk_prefetch(const void* src, uint32_t bytes) {
  asm volatile("cp.async.bulk.prefetch.L2.global [%0], %1;" :: "l"(src), "r"(bytes) : "memory");
}
__device__ __forceinline__ void bulk_commit() { asm volatile("cp.async.bulk.commit_group;" ::: "memory"); }
__device__ __forceinline__ void bulk_wait_read() { asm volatile("cp.async.bulk.wait_group.read 0;" ::: "memory"); }
__device__ __forceinline__ void bulk_wait_all() { asm volatile("cp.async.bulk.wait_group 0;" ::: "memory"); }
__device__ __forceinline__ void prefetch_map(const CUtensorMap* m) { asm volatile("prefetch.tensormap [%0];" :: "l"(m) : "memory"); }
__device__ __forceinline__ void wg_fence() { asm volatile("wgmma.fence.sync.aligned;" ::: "memory"); }
__device__ __forceinline__ void wg_commit() { asm volatile("wgmma.commit_group.sync.aligned;" ::: "memory"); }
template <int N> __device__ __forceinline__ void wg_wait() { asm volatile("wgmma.wait_group.sync.aligned %0;" :: "n"(N) : "memory"); }
template <int N> __device__ __forceinline__ void reg_fence(float (&d)[N]) {
#pragma unroll
  for (int i = 0; i < N; i++) asm volatile("" : "+f"(d[i]) :: "memory");
}
template <int N> __device__ __forceinline__ void reg_fence(uint32_t (&d)[N]) {
#pragma unroll
  for (int i = 0; i < N; i++) asm volatile("" : "+r"(d[i]) :: "memory");
}
__device__ __forceinline__ uint32_t fresh_tid() { uint32_t t; asm volatile("mov.u32 %0, %%tid.x;" : "=r"(t)); return t; }
__device__ __forceinline__ uint32_t lane_base16() {
  const uint32_t t = fresh_tid(), lane = t & 31, wq = (t >> 5) & 3;
  return (16 * wq + (lane & 7) + 8 * ((lane >> 3) & 1)) * 128 + (((lane >> 4) ^ (lane & 7)) << 4);
}
__device__ __forceinline__ void named_sync(int id, int n) { asm volatile("bar.sync %0, %1;" :: "r"(id), "r"(n) : "memory"); }
__device__ __forceinline__ void named_arrive(int id, int n) { asm volatile("bar.arrive %0, %1;" :: "r"(id), "r"(n) : "memory"); }
__device__ __forceinline__ uint32_t pack_bf16(float lo, float hi) {
  uint32_t r; asm("cvt.rn.bf16x2.f32 %0, %1, %2;" : "=r"(r) : "f"(hi), "f"(lo)); return r;
}
__device__ __forceinline__ float ex2(float x) { float y; asm("ex2.approx.ftz.f32 %0, %1;" : "=f"(y) : "f"(x)); return y; }
__device__ __forceinline__ void stsm4(uint32_t addr, uint32_t a, uint32_t b, uint32_t c, uint32_t d) {
  asm volatile("stmatrix.sync.aligned.m8n8.x4.shared.b16 [%0], {%1, %2, %3, %4};" :: "r"(addr), "r"(a), "r"(b), "r"(c), "r"(d) : "memory");
}
__device__ __forceinline__ void stsm4t(uint32_t addr, uint32_t a, uint32_t b, uint32_t c, uint32_t d) {
  asm volatile("stmatrix.sync.aligned.m8n8.x4.trans.shared.b16 [%0], {%1, %2, %3, %4};" :: "r"(addr), "r"(a), "r"(b), "r"(c), "r"(d) : "memory");
}
__device__ __forceinline__ uint64_t mk_desc(uint32_t addr, uint32_t lbo, uint32_t sbo) {
  return (uint64_t)(((addr & 0x3FFFF) >> 4) | ((lbo >> 4) << 16)) | ((uint64_t)((sbo >> 4) | (1u << 30)) << 32);
}
__device__ __forceinline__ uint64_t desc_k(uint32_t addr)  { return mk_desc(addr, 16, 1024); }
__device__ __forceinline__ uint64_t desc_mn(uint32_t addr) { return mk_desc(addr, 8192, 1024); }
__device__ __forceinline__ uint64_t desc_add(uint64_t d, uint32_t bytes) { return d + (bytes >> 4); }

__device__ __forceinline__ void wgmma_ss_n256_tb(float (&d)[128], uint64_t da, uint64_t db, int sd) {
  asm volatile("{\n.reg .pred p;\nsetp.ne.b32 p, %130, 0;\n"
    "wgmma.mma_async.sync.aligned.m64n256k16.f32.bf16.bf16 "
    "{%0, %1, %2, %3, %4, %5, %6, %7, %8, %9, %10, %11, %12, %13, %14, %15, "
    "%16, %17, %18, %19, %20, %21, %22, %23, %24, %25, %26, %27, %28, %29, %30, %31, "
    "%32, %33, %34, %35, %36, %37, %38, %39, %40, %41, %42, %43, %44, %45, %46, %47, "
    "%48, %49, %50, %51, %52, %53, %54, %55, %56, %57, %58, %59, %60, %61, %62, %63, "
    "%64, %65, %66, %67, %68, %69, %70, %71, %72, %73, %74, %75, %76, %77, %78, %79, "
    "%80, %81, %82, %83, %84, %85, %86, %87, %88, %89, %90, %91, %92, %93, %94, %95, "
    "%96, %97, %98, %99, %100, %101, %102, %103, %104, %105, %106, %107, %108, %109, %110, %111, "
    "%112, %113, %114, %115, %116, %117, %118, %119, %120, %121, %122, %123, %124, %125, %126, %127}, "
    "%128, %129, p, 1, 1, 0, 1;\n}"
    : "+f"(d[0]), "+f"(d[1]), "+f"(d[2]), "+f"(d[3]), "+f"(d[4]), "+f"(d[5]), "+f"(d[6]), "+f"(d[7]),
      "+f"(d[8]), "+f"(d[9]), "+f"(d[10]), "+f"(d[11]), "+f"(d[12]), "+f"(d[13]), "+f"(d[14]), "+f"(d[15]),
      "+f"(d[16]), "+f"(d[17]), "+f"(d[18]), "+f"(d[19]), "+f"(d[20]), "+f"(d[21]), "+f"(d[22]), "+f"(d[23]),
      "+f"(d[24]), "+f"(d[25]), "+f"(d[26]), "+f"(d[27]), "+f"(d[28]), "+f"(d[29]), "+f"(d[30]), "+f"(d[31]),
      "+f"(d[32]), "+f"(d[33]), "+f"(d[34]), "+f"(d[35]), "+f"(d[36]), "+f"(d[37]), "+f"(d[38]), "+f"(d[39]),
      "+f"(d[40]), "+f"(d[41]), "+f"(d[42]), "+f"(d[43]), "+f"(d[44]), "+f"(d[45]), "+f"(d[46]), "+f"(d[47]),
      "+f"(d[48]), "+f"(d[49]), "+f"(d[50]), "+f"(d[51]), "+f"(d[52]), "+f"(d[53]), "+f"(d[54]), "+f"(d[55]),
      "+f"(d[56]), "+f"(d[57]), "+f"(d[58]), "+f"(d[59]), "+f"(d[60]), "+f"(d[61]), "+f"(d[62]), "+f"(d[63]),
      "+f"(d[64]), "+f"(d[65]), "+f"(d[66]), "+f"(d[67]), "+f"(d[68]), "+f"(d[69]), "+f"(d[70]), "+f"(d[71]),
      "+f"(d[72]), "+f"(d[73]), "+f"(d[74]), "+f"(d[75]), "+f"(d[76]), "+f"(d[77]), "+f"(d[78]), "+f"(d[79]),
      "+f"(d[80]), "+f"(d[81]), "+f"(d[82]), "+f"(d[83]), "+f"(d[84]), "+f"(d[85]), "+f"(d[86]), "+f"(d[87]),
      "+f"(d[88]), "+f"(d[89]), "+f"(d[90]), "+f"(d[91]), "+f"(d[92]), "+f"(d[93]), "+f"(d[94]), "+f"(d[95]),
      "+f"(d[96]), "+f"(d[97]), "+f"(d[98]), "+f"(d[99]), "+f"(d[100]), "+f"(d[101]), "+f"(d[102]), "+f"(d[103]),
      "+f"(d[104]), "+f"(d[105]), "+f"(d[106]), "+f"(d[107]), "+f"(d[108]), "+f"(d[109]), "+f"(d[110]), "+f"(d[111]),
      "+f"(d[112]), "+f"(d[113]), "+f"(d[114]), "+f"(d[115]), "+f"(d[116]), "+f"(d[117]), "+f"(d[118]), "+f"(d[119]),
      "+f"(d[120]), "+f"(d[121]), "+f"(d[122]), "+f"(d[123]), "+f"(d[124]), "+f"(d[125]), "+f"(d[126]), "+f"(d[127])
    : "l"(da), "l"(db), "r"(sd));
}
__device__ __forceinline__ void wgmma_ss_n64(float (&d)[32], uint64_t da, uint64_t db, int sd) {
  asm volatile("{\n.reg .pred p;\nsetp.ne.b32 p, %34, 0;\n"
    "wgmma.mma_async.sync.aligned.m64n64k16.f32.bf16.bf16 "
    "{%0, %1, %2, %3, %4, %5, %6, %7, %8, %9, %10, %11, %12, %13, %14, %15, "
    "%16, %17, %18, %19, %20, %21, %22, %23, %24, %25, %26, %27, %28, %29, %30, %31}, "
    "%32, %33, p, 1, 1, 0, 0;\n}"
    : "+f"(d[0]), "+f"(d[1]), "+f"(d[2]), "+f"(d[3]), "+f"(d[4]), "+f"(d[5]), "+f"(d[6]), "+f"(d[7]),
      "+f"(d[8]), "+f"(d[9]), "+f"(d[10]), "+f"(d[11]), "+f"(d[12]), "+f"(d[13]), "+f"(d[14]), "+f"(d[15]),
      "+f"(d[16]), "+f"(d[17]), "+f"(d[18]), "+f"(d[19]), "+f"(d[20]), "+f"(d[21]), "+f"(d[22]), "+f"(d[23]),
      "+f"(d[24]), "+f"(d[25]), "+f"(d[26]), "+f"(d[27]), "+f"(d[28]), "+f"(d[29]), "+f"(d[30]), "+f"(d[31])
    : "l"(da), "l"(db), "r"(sd));
}
__device__ __forceinline__ void wgmma_ss_n64_tb(float (&d)[32], uint64_t da, uint64_t db, int sd) {
  asm volatile("{\n.reg .pred p;\nsetp.ne.b32 p, %34, 0;\n"
    "wgmma.mma_async.sync.aligned.m64n64k16.f32.bf16.bf16 "
    "{%0, %1, %2, %3, %4, %5, %6, %7, %8, %9, %10, %11, %12, %13, %14, %15, "
    "%16, %17, %18, %19, %20, %21, %22, %23, %24, %25, %26, %27, %28, %29, %30, %31}, "
    "%32, %33, p, 1, 1, 0, 1;\n}"
    : "+f"(d[0]), "+f"(d[1]), "+f"(d[2]), "+f"(d[3]), "+f"(d[4]), "+f"(d[5]), "+f"(d[6]), "+f"(d[7]),
      "+f"(d[8]), "+f"(d[9]), "+f"(d[10]), "+f"(d[11]), "+f"(d[12]), "+f"(d[13]), "+f"(d[14]), "+f"(d[15]),
      "+f"(d[16]), "+f"(d[17]), "+f"(d[18]), "+f"(d[19]), "+f"(d[20]), "+f"(d[21]), "+f"(d[22]), "+f"(d[23]),
      "+f"(d[24]), "+f"(d[25]), "+f"(d[26]), "+f"(d[27]), "+f"(d[28]), "+f"(d[29]), "+f"(d[30]), "+f"(d[31])
    : "l"(da), "l"(db), "r"(sd));
}
__device__ __forceinline__ void wgmma_rs_n256_tb(float (&d)[128], uint32_t a0, uint32_t a1, uint32_t a2, uint32_t a3, uint64_t db, int sd) {
  asm volatile("{\n.reg .pred p;\nsetp.ne.b32 p, %133, 0;\n"
    "wgmma.mma_async.sync.aligned.m64n256k16.f32.bf16.bf16 "
    "{%0, %1, %2, %3, %4, %5, %6, %7, %8, %9, %10, %11, %12, %13, %14, %15, "
    "%16, %17, %18, %19, %20, %21, %22, %23, %24, %25, %26, %27, %28, %29, %30, %31, "
    "%32, %33, %34, %35, %36, %37, %38, %39, %40, %41, %42, %43, %44, %45, %46, %47, "
    "%48, %49, %50, %51, %52, %53, %54, %55, %56, %57, %58, %59, %60, %61, %62, %63, "
    "%64, %65, %66, %67, %68, %69, %70, %71, %72, %73, %74, %75, %76, %77, %78, %79, "
    "%80, %81, %82, %83, %84, %85, %86, %87, %88, %89, %90, %91, %92, %93, %94, %95, "
    "%96, %97, %98, %99, %100, %101, %102, %103, %104, %105, %106, %107, %108, %109, %110, %111, "
    "%112, %113, %114, %115, %116, %117, %118, %119, %120, %121, %122, %123, %124, %125, %126, %127}, "
    "{%128, %129, %130, %131}, %132, p, 1, 1, 1;\n}"
    : "+f"(d[0]), "+f"(d[1]), "+f"(d[2]), "+f"(d[3]), "+f"(d[4]), "+f"(d[5]), "+f"(d[6]), "+f"(d[7]),
      "+f"(d[8]), "+f"(d[9]), "+f"(d[10]), "+f"(d[11]), "+f"(d[12]), "+f"(d[13]), "+f"(d[14]), "+f"(d[15]),
      "+f"(d[16]), "+f"(d[17]), "+f"(d[18]), "+f"(d[19]), "+f"(d[20]), "+f"(d[21]), "+f"(d[22]), "+f"(d[23]),
      "+f"(d[24]), "+f"(d[25]), "+f"(d[26]), "+f"(d[27]), "+f"(d[28]), "+f"(d[29]), "+f"(d[30]), "+f"(d[31]),
      "+f"(d[32]), "+f"(d[33]), "+f"(d[34]), "+f"(d[35]), "+f"(d[36]), "+f"(d[37]), "+f"(d[38]), "+f"(d[39]),
      "+f"(d[40]), "+f"(d[41]), "+f"(d[42]), "+f"(d[43]), "+f"(d[44]), "+f"(d[45]), "+f"(d[46]), "+f"(d[47]),
      "+f"(d[48]), "+f"(d[49]), "+f"(d[50]), "+f"(d[51]), "+f"(d[52]), "+f"(d[53]), "+f"(d[54]), "+f"(d[55]),
      "+f"(d[56]), "+f"(d[57]), "+f"(d[58]), "+f"(d[59]), "+f"(d[60]), "+f"(d[61]), "+f"(d[62]), "+f"(d[63]),
      "+f"(d[64]), "+f"(d[65]), "+f"(d[66]), "+f"(d[67]), "+f"(d[68]), "+f"(d[69]), "+f"(d[70]), "+f"(d[71]),
      "+f"(d[72]), "+f"(d[73]), "+f"(d[74]), "+f"(d[75]), "+f"(d[76]), "+f"(d[77]), "+f"(d[78]), "+f"(d[79]),
      "+f"(d[80]), "+f"(d[81]), "+f"(d[82]), "+f"(d[83]), "+f"(d[84]), "+f"(d[85]), "+f"(d[86]), "+f"(d[87]),
      "+f"(d[88]), "+f"(d[89]), "+f"(d[90]), "+f"(d[91]), "+f"(d[92]), "+f"(d[93]), "+f"(d[94]), "+f"(d[95]),
      "+f"(d[96]), "+f"(d[97]), "+f"(d[98]), "+f"(d[99]), "+f"(d[100]), "+f"(d[101]), "+f"(d[102]), "+f"(d[103]),
      "+f"(d[104]), "+f"(d[105]), "+f"(d[106]), "+f"(d[107]), "+f"(d[108]), "+f"(d[109]), "+f"(d[110]), "+f"(d[111]),
      "+f"(d[112]), "+f"(d[113]), "+f"(d[114]), "+f"(d[115]), "+f"(d[116]), "+f"(d[117]), "+f"(d[118]), "+f"(d[119]),
      "+f"(d[120]), "+f"(d[121]), "+f"(d[122]), "+f"(d[123]), "+f"(d[124]), "+f"(d[125]), "+f"(d[126]), "+f"(d[127])
    : "r"(a0), "r"(a1), "r"(a2), "r"(a3), "l"(db), "r"(sd));
}
__device__ __forceinline__ void wgmma_rs_n64_tb(float (&d)[32], uint32_t a0, uint32_t a1, uint32_t a2, uint32_t a3, uint64_t db, int sd) {
  asm volatile("{\n.reg .pred p;\nsetp.ne.b32 p, %37, 0;\n"
    "wgmma.mma_async.sync.aligned.m64n64k16.f32.bf16.bf16 "
    "{%0, %1, %2, %3, %4, %5, %6, %7, %8, %9, %10, %11, %12, %13, %14, %15, "
    "%16, %17, %18, %19, %20, %21, %22, %23, %24, %25, %26, %27, %28, %29, %30, %31}, "
    "{%32, %33, %34, %35}, %36, p, 1, 1, 1;\n}"
    : "+f"(d[0]), "+f"(d[1]), "+f"(d[2]), "+f"(d[3]), "+f"(d[4]), "+f"(d[5]), "+f"(d[6]), "+f"(d[7]),
      "+f"(d[8]), "+f"(d[9]), "+f"(d[10]), "+f"(d[11]), "+f"(d[12]), "+f"(d[13]), "+f"(d[14]), "+f"(d[15]),
      "+f"(d[16]), "+f"(d[17]), "+f"(d[18]), "+f"(d[19]), "+f"(d[20]), "+f"(d[21]), "+f"(d[22]), "+f"(d[23]),
      "+f"(d[24]), "+f"(d[25]), "+f"(d[26]), "+f"(d[27]), "+f"(d[28]), "+f"(d[29]), "+f"(d[30]), "+f"(d[31])
    : "r"(a0), "r"(a1), "r"(a2), "r"(a3), "l"(db), "r"(sd));
}
__device__ __forceinline__ void wgmma_rs_n64(float (&d)[32], uint32_t a0, uint32_t a1, uint32_t a2, uint32_t a3, uint64_t db, int sd) {
  asm volatile("{\n.reg .pred p;\nsetp.ne.b32 p, %37, 0;\n"
    "wgmma.mma_async.sync.aligned.m64n64k16.f32.bf16.bf16 "
    "{%0, %1, %2, %3, %4, %5, %6, %7, %8, %9, %10, %11, %12, %13, %14, %15, "
    "%16, %17, %18, %19, %20, %21, %22, %23, %24, %25, %26, %27, %28, %29, %30, %31}, "
    "{%32, %33, %34, %35}, %36, p, 1, 1, 0;\n}"
    : "+f"(d[0]), "+f"(d[1]), "+f"(d[2]), "+f"(d[3]), "+f"(d[4]), "+f"(d[5]), "+f"(d[6]), "+f"(d[7]),
      "+f"(d[8]), "+f"(d[9]), "+f"(d[10]), "+f"(d[11]), "+f"(d[12]), "+f"(d[13]), "+f"(d[14]), "+f"(d[15]),
      "+f"(d[16]), "+f"(d[17]), "+f"(d[18]), "+f"(d[19]), "+f"(d[20]), "+f"(d[21]), "+f"(d[22]), "+f"(d[23]),
      "+f"(d[24]), "+f"(d[25]), "+f"(d[26]), "+f"(d[27]), "+f"(d[28]), "+f"(d[29]), "+f"(d[30]), "+f"(d[31])
    : "r"(a0), "r"(a1), "r"(a2), "r"(a3), "l"(db), "r"(sd));
}

__device__ __forceinline__ uint4 lds16(uint32_t a) {
  uint4 v; asm volatile("ld.shared.v4.u32 {%0, %1, %2, %3}, [%4];" : "=r"(v.x), "=r"(v.y), "=r"(v.z), "=r"(v.w) : "r"(a) : "memory"); return v;
}
__device__ __forceinline__ void sts16(uint32_t a, uint32_t x, uint32_t y, uint32_t z, uint32_t w) {
  asm volatile("st.shared.v4.u32 [%0], {%1, %2, %3, %4};" :: "r"(a), "r"(x), "r"(y), "r"(z), "r"(w) : "memory");
}
__device__ __forceinline__ uint32_t lds4(uint32_t a) { uint32_t v; asm volatile("ld.shared.u32 %0, [%1];" : "=r"(v) : "r"(a) : "memory"); return v; }
__device__ __forceinline__ uint32_t lds4v(uint32_t a) { uint32_t v; asm volatile("ld.volatile.shared.u32 %0, [%1];" : "=r"(v) : "r"(a) : "memory"); return v; }
__device__ __forceinline__ uint32_t bmul(uint32_t a, uint32_t b) { uint32_t r; asm("mul.rn.bf16x2 %0, %1, %2;" : "=r"(r) : "r"(a), "r"(b)); return r; }
__device__ __forceinline__ uint32_t badd(uint32_t a, uint32_t b) { uint32_t r; asm("add.rn.bf16x2 %0, %1, %2;" : "=r"(r) : "r"(a), "r"(b)); return r; }

__device__ __forceinline__ uint32_t add_skip(uint32_t y, uint32_t x, uint32_t d) { return badd(y, bmul(x, d)); }
__device__ __forceinline__ void ldsm4(uint32_t (&r)[4], uint32_t a) {
  asm volatile("ldmatrix.sync.aligned.m8n8.x4.shared.b16 {%0, %1, %2, %3}, [%4];" : "=r"(r[0]), "=r"(r[1]), "=r"(r[2]), "=r"(r[3]) : "r"(a) : "memory");
}
__device__ __forceinline__ void ldsm4t(uint32_t (&r)[4], uint32_t a) {
  asm volatile("ldmatrix.sync.aligned.m8n8.x4.trans.shared.b16 {%0, %1, %2, %3}, [%4];" : "=r"(r[0]), "=r"(r[1]), "=r"(r[2]), "=r"(r[3]) : "r"(a) : "memory");
}
__device__ __forceinline__ uint32_t transpose8(uint32_t a) { uint32_t d; asm volatile("movmatrix.sync.aligned.m8n8.trans.b16 %0, %1;" : "=r"(d) : "r"(a)); return d; }

__device__ __forceinline__ void mma16816(float (&d)[4], const uint32_t (&a)[4], uint32_t b0, uint32_t b1) {
  asm volatile("mma.sync.aligned.m16n8k16.row.col.f32.bf16.bf16.f32 {%0, %1, %2, %3}, {%4, %5, %6, %7}, {%8, %9}, {%0, %1, %2, %3};"
               : "+f"(d[0]), "+f"(d[1]), "+f"(d[2]), "+f"(d[3]) : "r"(a[0]), "r"(a[1]), "r"(a[2]), "r"(a[3]), "r"(b0), "r"(b1));
}

#define STG_K1 2
#define STG_K2 10
#define STG_Q1 1
#define STG_Q2 5
#define PACE_A 400
#define PACE_B 100
#define PF_QA 48
#define PF_CV 64
#define PF_X 1
#define PF_WO 11
#define Q_PRE 2
#define O_PRE 12
#define CTX_PIECE 1024
#define PACE_C 50
#define ARRIVE_KK 12
#define SIDE_DELAY_NS 2000
#define EARLY_LD 2
#define HI_ORDER 9
constexpr int PP_BAR = 3;
template <int V> struct Int { static constexpr int value = V; };
struct Ring {
  uint32_t slot, phase;
  __device__ __forceinline__ void next() { if (++slot == NSLOT) { slot = 0; phase ^= 1; } }
};
__device__ __forceinline__ uint32_t bar_addr(uint32_t sb, uint32_t i) { return sb + BARS + 8 * i; }
__device__ __forceinline__ uint32_t q_region(uint32_t sb, int w) { return sb + QREG + (w ^ 1) * 32768; }

struct Role { int h, j; };
__device__ __forceinline__ Role get_role() {
  int cta; asm volatile("mov.u32 %0, %%ctaid.x;" : "=r"(cta));
  const int c = cta >> 1;
  int h, u;
  const int a = c - 4, b = c - 36, q = (b * 37) >> 8;
  h = a < 0 ? 8 : b < 0 ? a & 7 : 9 + b - 7 * q;
  u = a < 0 ? c : b < 0 ? a >> 3 : q;
  return Role{h, 2 * u + (cta & 1)};
}
__device__ __forceinline__ int fresh_warp() { return __shfl_sync(0xffffffffu, fresh_tid() >> 5, 0); }

__device__ __forceinline__ int q_tile(int h, int j, int which) { return ((h < 8) == (which == 0)) ? 15 - j : j; }

__device__ __forceinline__ int o_chunk(int h, int c) { const int x = c + (h & 7); return x % 7; }

__device__ __forceinline__ int kv_block(int j, int t) { return j + 8 * ((HI_ORDER >> t) & 1); }
__device__ __forceinline__ uint8_t* kv_tile(const Params& p, int v, int h, int tile) {
  return p.kv + (size_t)((v * NH + h) * 32 + tile) * 32768;
}

__device__ __forceinline__ void ring_acquire(uint32_t sb, Ring& r, uint32_t bytes) {
  mbar_wait(bar_addr(sb, B_RG_EMPTY + r.slot), r.phase ^ 1);
  mbar_expect_tx(bar_addr(sb, B_RG_FULL + r.slot), bytes);
}
__device__ __forceinline__ void producer_main(const Params& p, uint32_t sb) {
  const Role ro = get_role();
  const int h = ro.h, j = ro.j;
  for (int it = EARLY_LD; it < 71; it++) {
    const int t = it >> 4, k = it & 15, s = it & 3;
    mbar_wait(bar_addr(sb, B_P1_EMPTY + s), ((it >> 2) & 1) ^ 1);
    const uint32_t full = bar_addr(sb, B_P1_FULL + s), dst = sb + s * P1_STAGE;
    mbar_expect_tx(full, P1_STAGE);
    if (t < 4) {
      tma_ld2(dst, &p.ckv, full, k * 64, kv_block(j, t) * 128);
      tma_ld3(dst + 16384, (t >> 1) ? &p.wuv : &p.wuk, full, 0, k * 64, h * 4);
    } else {
      tma_ld2(dst, &p.x, full, k * 64, q_tile(h, j, 0) * 128);
      tma_ld3(dst + 16384, &p.wq, full, 0, k * 64, h * 4);
    }
    if (it >= PF_QA && it < PF_QA + 14) {
      const int i = it - PF_QA;
      bulk_prefetch(p.b_x + (size_t)(q_tile(h, j, 0) * 128 + (h & 7) * 16) * DM + i * 512, 1024);
      tma_pf2(&p.wqp, h * HD, (i * 8 + j) * 4);
    }
    if (it >= PF_CV && it < PF_CV + 3) {
      mbar_wait(bar_addr(sb, B_XS), 0);
      bulk_prefetch(g_xs + (size_t)(h * 8 + j) * CV_BYTES + (it - PF_CV) * (CV_BYTES / 3), CV_BYTES / 3);
    }
  }
  mbar_wait(bar_addr(sb, B_P1_EMPTY + 3), 0);
  mbar_wait(bar_addr(sb, B_XS), 0);
  mbar_expect_tx(bar_addr(sb, B_RG_FULL + 4), CV_BYTES);
  bulk_ld(sb + CV_X, g_xs + (size_t)(h * 8 + j) * CV_BYTES, CV_BYTES, bar_addr(sb, B_RG_FULL + 4));
  Ring r{0, 1};
  auto prefetch_q = [&](int kc, int qt) {
    if (PF_X && kc >= 0 && kc < 7) tma_pf2(&p.x, kc * 64, qt * 128);
  };
  auto prefetch_wo = [&](int left) {
    const int i = PF_WO - left;
    if (PF_WO && i >= 0 && i < 8) bulk_prefetch(p.b_wo + (size_t)(h * HD + j * 32 + 4 * i) * DM, 4 * DM * 2);
  };
  mbar_wait(bar_addr(sb, B_KV), 0);
  for (int which = 0; which < 2; which++) {
    const int qt = q_tile(h, j, which);
    if (which == 1) {
      uint32_t xdst = 0;
      for (int kc = 0; kc < 7; kc++) {
        prefetch_wo(4 * qt + 4 + 7 - kc);
        ring_acquire(sb, r, P1_STAGE);
        const uint32_t full = bar_addr(sb, B_RG_FULL + r.slot);
        tma_ld3(sb + r.slot * SLOT, &p.wq, full, 0, kc * 64, h * 4);
        r.next();
        if (kc == 0 || (kc & 1)) {
          mbar_wait(bar_addr(sb, B_RG_EMPTY + r.slot), r.phase ^ 1);
          mbar_arrive(bar_addr(sb, B_RG_FULL + r.slot));
          xdst = sb + r.slot * SLOT;
          r.next();
        } else xdst += 16384;
        tma_ld2(xdst, &p.x, full, kc * 64, qt * 128);
        prefetch_q(kc + PF_X, qt);
      }
    }
    const int n = 2 * qt + 2;
    for (int f = 0; f < 2 * n; f++) {
      if (which == 0) prefetch_q(f - 2 * n + PF_X, 15 - qt); else prefetch_wo(2 * n - f);
      const bool isK = (f == 0) || ((f & 1) && f < 2 * n - 1);
      const int i = isK ? (f + 1) >> 1 : (f == 2 * n - 1 ? n - 1 : (f >> 1) - 1);
      const int tile = which ? n - 1 - i : i;
      if (!isK) mbar_wait(bar_addr(sb, B_KV + 1 + ((tile >> 4) ^ ((HI_ORDER >> 2) & 1))), 0);
      if (which == 0 && f < 2) mbar_wait(bar_addr(sb, B_P1_EMPTY + f), 1);
      ring_acquire(sb, r, 32768);
      bulk_ld(sb + r.slot * SLOT, kv_tile(p, !isK, h, tile), 32768, bar_addr(sb, B_RG_FULL + r.slot));
      r.next();
    }
  }
  for (int i = 0; i < 14; i++) {
    ring_acquire(sb, r, 32768);
    tma_ld2(sb + r.slot * SLOT, &p.wo, bar_addr(sb, B_RG_FULL + r.slot), o_chunk(h, i >> 1) * 64, ((i & 1) ? h ^ 8 : h) * HD);
    r.next();
  }
}

__device__ __forceinline__ void storer_main(const Params& p, uint32_t sb) {
  const Role ro = get_role();
  const int h = ro.h, j = ro.j, w = fresh_warp() - 1;
  const uint32_t full = bar_addr(sb, B_ST_FULL + w), empty = bar_addr(sb, B_ST_EMPTY + w);
  if ((threadIdx.x & 31) != 0) return;
  for (int job = 0; job < 8; job++) {
    const int t = job >> 1;
    uint8_t* dst = kv_tile(p, t >> 1, h, 2 * kv_block(j, t) + w) + (job & 1) * 16384;
    mbar_wait_nap(full, job & 1);
    for (int i = 0; i < 8; i++) {
      if (i) __nanosleep(job < 6 ? PACE_A : PACE_B);
      bulk_st(dst + i * 2048, sb + P1_STG + w * 16384 + i * 2048, 2048);
    }
    bulk_commit();
    bulk_wait_read();
    mbar_arrive(empty);
    if (job >= 3 && (job & 1)) { bulk_wait_all(); flag_signal(&g_flags.kv_ready[3 * h + t - 1].v); }
  }
  const int cta = h * 8 + j, qt = q_tile(h, j, 1);
  const uint32_t qreg = q_region(sb, w);
  {
    mbar_wait_nap(bar_addr(sb, B_CTXS + 4 * w), 0);
    for (int b = 0; b < 4; b++) {
      mbar_wait(bar_addr(sb, B_CTXS + 4 * w + b), 0);
      for (int i = 0; i < 8192 / CTX_PIECE; i++) {
        bulk_st(p.ctx + (size_t)(cta * 2 + w) * 32768 + b * 8192 + i * CTX_PIECE, qreg + b * 8192 + i * CTX_PIECE, CTX_PIECE);
        if (PACE_C) __nanosleep(PACE_C);
      }
      bulk_commit();
    }
    bulk_wait_read();
    mbar_arrive(empty);
    bulk_wait_all();
    mbar_arrive(bar_addr(sb, B_CTXD));
  }
  {
    const int wx = w ^ 1;
    mbar_wait_nap(bar_addr(sb, B_CTXD + 1), 0);
    mbar_wait_nap(bar_addr(sb, B_QFREE + w), 0);
    mbar_expect_tx(bar_addr(sb, B_CTXF + w), 32768);
    bulk_ld(qreg, p.ctx + (size_t)((cta ^ 64) * 2 + wx) * 32768, 32768, bar_addr(sb, B_CTXF + w));
    for (int ch = 0; ch < 7; ch++) {
      const int b = ch & 1;
      mbar_wait(bar_addr(sb, B_S2_FULL + w * 2 + b), (ch >> 1) & 1);
      tma_red2(&p.part, qreg + b * 8192, DA + o_chunk(h, ch) * 64, qt * 128 + wx * 64);
      bulk_commit();
      if (ch == 0 && w == 1) mbar_arrive(bar_addr(sb, B_GFREE));
      bulk_wait_read();
      mbar_arrive(bar_addr(sb, B_S2_EMPTY + w * 2 + b));
    }
  }
}

template <int OFF, int NB, int NREG>
__device__ __forceinline__ void store_blocks(uint32_t base, uint32_t lanebase, const uint32_t (&pk)[NREG]) {
#pragma unroll
  for (int J = 0; J < NB * 8; J += 2) {
    const uint32_t a = base + (J >> 3) * 8192 + (lanebase ^ ((J & 7) << 4));
    stsm4(a, pk[OFF + 2 * J], pk[OFF + 2 * J + 1], pk[OFF + 2 * J + 2], pk[OFF + 2 * J + 3]);
  }
}
__device__ __forceinline__ void warp_arrive(uint32_t bar, int lane) { __syncwarp(); if (lane == 0) mbar_arrive(bar); }
__device__ __forceinline__ void release(uint32_t bar, int lane) { lane0_arrive(bar, 1, lane); }

template <int W> __device__ __forceinline__ constexpr int cv_tile(int u) { return 2 * u + ((u ^ W) & 1); }
__device__ __forceinline__ uint32_t cv_x_lane(uint32_t lane) { return (16 + (lane & 15) - (lane >> 4)) * 16; }
__device__ __forceinline__ uint32_t cv_h_lane(uint32_t lane, uint32_t hE, uint32_t hO) {
  const uint32_t g = lane >> 2, c = lane & 3;
  return (g & 1) ? hO + (15 + 2 * c - g) * 2 : hE + (16 + 2 * c - g) * 2;
}
template <int W>
__device__ __forceinline__ void conv_mma(float (&ca)[8][4], uint32_t xa, uint32_t ha, uint32_t sb, uint32_t lb, const uint32_t (&pk)[64], uint32_t one) {
  constexpr int N = 16 - W;
  uint32_t fx[N][4], fh[N][2];
  auto ld_h = [&](int i, int rr) { fh[i][0] = lds4(ha + i * 256 + rr * 128); fh[i][1] = lds4(ha + i * 256 + rr * 128 + 16); };
  uint32_t c1 = 0, c3 = 0;
  ldsm4(fx[0], xa);
#pragma unroll
  for (int u = 0; u < 8; u++) ld_h(cv_tile<W>(u), 0);
  ldsm4(fx[1], xa + 256);
#pragma unroll
  for (int u = 0; u < 8; u++) if (cv_tile<W ^ 1>(u) < N) ld_h(cv_tile<W ^ 1>(u), 0);
#pragma unroll
  for (int i = 2; i < N; i++) ldsm4(fx[i], xa + i * 256);
#pragma unroll
  for (int sx = 0; sx < N; sx++) {
#pragma unroll
    for (int u = 0; u < 8; u++) {
      const int jj = cv_tile<W>(u) - sx;
      if (jj >= 0) mma16816(ca[u], fx[sx], fh[jj < 0 ? 0 : jj][0], fh[jj < 0 ? 0 : jj][1]);
    }
    {
      const uint32_t t1 = fx[sx][1], t3 = fx[sx][3];
      fx[sx][1] = fx[sx][0] * one; fx[sx][3] = fx[sx][2] ^ (one - 1); fx[sx][0] = c1 * one; fx[sx][2] = c3 ^ (one - 1);
      c1 = t1; c3 = t3;
    }
    ld_h(N - 1 - sx, 1);
  }
  mbar_wait(bar_addr(sb, B_P1_EMPTY + 2), 1);
  if (W == 0) { mbar_wait(bar_addr(sb, B_ST_EMPTY), 1); mbar_wait(bar_addr(sb, B_ST_EMPTY + 1), 1); }
#pragma unroll
  for (int jj = 15; jj >= 0; jj--) {
    if (W == 0) stsm4(q_region(sb, W) + (jj >> 2) * 8192 + (lb ^ ((jj & 3) << 5)), pk[4 * jj], pk[4 * jj + 1], pk[4 * jj + 2], pk[4 * jj + 3]);
#pragma unroll
    for (int u = 0; u < 8; u++) {
      const int sx = cv_tile<W>(u) - jj;
      if (sx >= 0) mma16816(ca[u], fx[sx < 0 ? 0 : sx], fh[jj < N ? jj : 0][0], fh[jj < N ? jj : 0][1]);
    }
  }
}

__device__ __forceinline__ void consumer_main(const Params& p, uint32_t sb, uint8_t* xs_base, uint32_t one) {
  const int lane = fresh_tid() & 31, w = (fresh_warp() >> 2) - 1;
  const uint32_t lb = lane_base16();
  int qt, cc;
  { const Role ro = get_role(); qt = q_tile(ro.h, ro.j, 0); cc = ro.h * 8 + ro.j; }
  const uint32_t st_full = bar_addr(sb, B_ST_FULL + w), st_empty = bar_addr(sb, B_ST_EMPTY + w);
  const uint32_t stg = sb + P1_STG + w * 16384;

  auto turn_begin = [&]() { named_sync(PP_BAR + w, 256); };
  auto turn_end = [&]() { named_arrive(PP_BAR + (w ^ 1), 256); };
  float acc[128];
#pragma unroll
  for (int i = 0; i < 128; i++) acc[i] = 0.f;
  uint32_t pk[64];
#pragma unroll
  for (int i = 0; i < 64; i++) pk[i] = 0;
  if (fresh_warp() != 4) named_sync(0, NTHREADS);
  const uint32_t qreg = q_region(sb, w);
  for (int t = 0; t < 5; t++) {
    const int nk = t < 4 ? 16 : 7;
#pragma unroll 1
    for (int k = 0; k < nk; k++) {
      const int it = t * 16 + k, s = k & 3;
      if (it == 0) { mbar_wait(bar_addr(sb, B_P1_FULL), 0); turn_begin(); }
      const uint64_t da = desc_k(sb + s * P1_STAGE + w * 8192), db = desc_mn(sb + s * P1_STAGE + 16384);
      wg_fence();
#pragma unroll
      for (int kk = 0; kk < 4; kk++) wgmma_ss_n256_tb(acc, desc_add(da, kk * 32), desc_add(db, kk * 2048), (k | kk) != 0);
      wg_commit();
      turn_end();
      wg_wait<1>();
      if (k > 0) release(bar_addr(sb, B_P1_EMPTY + ((k - 1) & 3)), lane);
      const int k1 = t < 4 ? STG_K1 : STG_Q1, k2 = t < 4 ? STG_K2 : STG_Q2;
      if (t > 0 && (k == k1 || k == k2)) {
        const int job = 2 * (t - 1) + (k != k1);
        mbar_wait(job > 0 ? st_empty : bar_addr(sb, B_SIDE + 1), job > 0 ? (job - 1) & 1 : 0);
        if (k == k1) store_blocks<0, 2>(stg, lb, pk); else store_blocks<32, 2>(stg, lb, pk);
      }
      if (t > 0 && (k == k1 + 1 || k == k2 + 1)) { fence_async_smem(); warp_arrive(st_full, lane); }
      if (it < 70) { mbar_wait(bar_addr(sb, B_P1_FULL + ((k + 1) & 3)), ((it + 1) >> 2) & 1); turn_begin(); }
      else mbar_wait(bar_addr(sb, B_RG_FULL + 4), 0);
    }
    wg_wait<0>();
    reg_fence(acc);
    release(bar_addr(sb, B_P1_EMPTY + ((nk - 1) & 3)), lane);
#pragma unroll
    for (int i = 0; i < 64; i++) pk[i] = pack_bf16(acc[2 * i], acc[2 * i + 1]);
  }
  {
    const uint32_t wq = lb >> 11, ln = lane, cx = sb + CV_X;
    float ca[8][4];
#pragma unroll
    for (int i = 0; i < 8; i++) { ca[i][0] = 0.f; ca[i][1] = 0.f; ca[i][2] = 0.f; ca[i][3] = 0.f; }
    const uint32_t xa = cx + cv_x_lane(ln) - wq * 32, ha = cv_h_lane(ln, cx + CV_HE, cx + CV_HE + CV_HCOPY) + wq * 32;
    if (w) conv_mma<1>(ca, xa, ha, sb, lb, pk, one); else conv_mma<0>(ca, xa, ha, sb, lb, pk, one);
    const uint32_t ex = sb + CV_R + w * 16384 + ln * 16;
#pragma unroll
    for (int u = 0; u < 8; u++)
      sts16(ex + (wq * 8 + u) * 512, __float_as_uint(ca[u][0]), __float_as_uint(ca[u][1]), __float_as_uint(ca[u][2]), __float_as_uint(ca[u][3]));
  }
  auto conv_finish = [&]() {
    const uint32_t wq = lb >> 11, cx = sb + CV_X, ex = sb + CV_R + w * 16384 + lane * 16;
    uint8_t* gz = xs_base + (size_t)cc * CV_BYTES;
    const uint32_t Dd = lds4(cx + CV_D);
#pragma unroll
    for (int e = 0; e < 2; e++) {
      const uint32_t u = 2 * wq + e, nt = 2 * u + ((e ^ w) & 1);
      float y[4] = {0.f, 0.f, 0.f, 0.f};
#pragma unroll
      for (int v = 0; v < 4; v++) {
        const uint4 t = lds16(ex + (v * 8 + u) * 512);
        y[0] += __uint_as_float(t.x); y[1] += __uint_as_float(t.y); y[2] += __uint_as_float(t.z); y[3] += __uint_as_float(t.w);
      }
      const uint32_t o = (16 + 16 * nt) * 16 + lane * 4;
      *reinterpret_cast<uint32_t*>(gz + o)       = badd(pack_bf16(y[0], y[1]), bmul(lds4(cx + o), Dd));
      *reinterpret_cast<uint32_t*>(gz + o + 128) = badd(pack_bf16(y[2], y[3]), bmul(lds4(cx + o + 128), Dd));
    }
    __syncwarp();
    release(bar_addr(sb, B_RG_EMPTY + 3), lane);
    release(bar_addr(sb, B_RG_EMPTY + 4), lane);
    if (lane == 0) mbar_arrive(bar_addr(sb, B_CONV));
  };
  Ring r{0, 1};
  auto take = [&]() { const uint32_t sl = r.slot; mbar_wait(bar_addr(sb, B_RG_FULL + sl), r.phase); r.next(); return sl; };
  constexpr float SC = 0.0625f * 1.4426950408889634f;
  uint32_t ws;
#pragma unroll 1
  for (int which = 0;; which++) {
    float s[32];
#pragma unroll
    for (int i = 0; i < 32; i++) s[i] = 0.f;
    uint32_t pa[16];
    float b0, b1, l0, l1;
    const uint64_t dq = desc_k(qreg);
    uint64_t dk = 0, dqq = 0, dv = 0;
    auto prep_qk = [&](uint32_t kaddr) { dk = desc_k(kaddr); dqq = dq + (kaddr >> 31); asm volatile("" : "+l"(dk), "+l"(dqq)); };
    auto prep_pv = [&](uint32_t vaddr) { dv = desc_mn(vaddr); asm volatile("" : "+l"(dv)); };
    auto issue_qk = [&]() {
#pragma unroll
      for (int kk = 0; kk < 16; kk++)
        wgmma_ss_n64(s, desc_add(dqq, (kk >> 2) * 8192 + (kk & 3) * 32), desc_add(dk, (kk >> 2) * 8192 + (kk & 3) * 32), kk != 0);
    };
    auto issue_pv = [&](int accumulate) {
#pragma unroll
      for (int kk = 0; kk < 4; kk++)
        wgmma_rs_n256_tb(acc, pa[4 * kk], pa[4 * kk + 1], pa[4 * kk + 2], pa[4 * kk + 3], desc_add(dv, kk * 2048), accumulate | kk);
    };
    auto mask_diag = [&]() {
      const int d = (int)((lb >> 11) << 4) + (lane >> 2) - 2 * (lane & 3);
#pragma unroll
      for (int jj = 0; jj < 8; jj++) {
        if (8 * jj > d)     s[4 * jj]     = -INFINITY;
        if (8 * jj + 1 > d) s[4 * jj + 1] = -INFINITY;
        if (8 * jj - 8 > d) s[4 * jj + 2] = -INFINITY;
        if (8 * jj - 7 > d) s[4 * jj + 3] = -INFINITY;
      }
    };
    auto row_max = [&](float& x0, float& x1) {
      x0 = fmaxf(s[0], s[1]); x1 = fmaxf(s[2], s[3]);
#pragma unroll
      for (int jj = 1; jj < 8; jj++) {
        x0 = fmaxf(x0, fmaxf(s[4 * jj], s[4 * jj + 1]));
        x1 = fmaxf(x1, fmaxf(s[4 * jj + 2], s[4 * jj + 3]));
      }
      x0 = fmaxf(x0, __shfl_xor_sync(0xffffffffu, x0, 1));
      x1 = fmaxf(x1, __shfl_xor_sync(0xffffffffu, x1, 1));
      x0 = fmaxf(x0, __shfl_xor_sync(0xffffffffu, x0, 2));
      x1 = fmaxf(x1, __shfl_xor_sync(0xffffffffu, x1, 2));
    };
    auto exps = [&](uint32_t (&pp)[16], float& r0, float& r1) {
      float t0, t1, t2, t3;
#pragma unroll
      for (int jj = 0; jj < 8; jj++) {
        const float e0 = ex2(fmaf(s[4 * jj], SC, b0)), e1 = ex2(fmaf(s[4 * jj + 1], SC, b0));
        const float e2 = ex2(fmaf(s[4 * jj + 2], SC, b1)), e3 = ex2(fmaf(s[4 * jj + 3], SC, b1));
        if (jj == 0) { t0 = e0; t1 = e1; t2 = e2; t3 = e3; } else { t0 += e0; t1 += e1; t2 += e2; t3 += e3; }
        pp[2 * jj] = pack_bf16(e0, e1); pp[2 * jj + 1] = pack_bf16(e2, e3);
      }
      r0 = t0 + t1; r1 = t2 + t3;
    };

    const bool up = w == which;
    const int n = 2 * qt + 2, nw = n - up;
    int fd = which ? 0 : 2 * n - 1;
    const int dir = which ? 1 : -1;
    auto skip = [&]() { r.next(); fd += dir; };
    auto give = [&](uint32_t sl, int d) {
      lane0_arrive(bar_addr(sb, B_RG_EMPTY + sl), (d & ~2) == 0 ? 2 : 1, lane);
    };
    if (which && up) skip();
    uint32_t ks = take();
    prep_qk(sb + ks * SLOT);
    turn_begin();
    wg_fence();
#pragma unroll
    for (int kk = 0; kk < 16; kk++)
      wgmma_rs_n64(s, pk[4 * kk], pk[4 * kk + 1], pk[4 * kk + 2], pk[4 * kk + 3], desc_add(dk, (kk >> 2) * 8192 + (kk & 3) * 32), kk != 0);
    wg_commit();
    turn_end();
    if (!which && up) conv_finish();
    if (which) mbar_wait(st_empty, 0);
    if (!up) store_blocks<0, Q_PRE>(qreg, lb, pk);
    wg_wait<0>();
    reg_fence(s);
    reg_fence(pk);
    give(ks, fd);
    fd += dir;
    if (which && up) { skip(); store_blocks<0, 4>(qreg, lb, pk); }
    if (which || nw == 1) mask_diag();
    row_max(b0, b1);
    if (!up) store_blocks<16 * Q_PRE, 4 - Q_PRE>(qreg + Q_PRE * 8192, lb, pk);
    b0 *= -SC; b1 *= -SC;
#pragma unroll
    for (int i = 0; i < 128; i++) acc[i] = 0.f;
    exps(pa, l0, l1);
    if (!which && !up) conv_finish();
    if (which && nw == 1) { fence_async_smem(); warp_arrive(bar_addr(sb, B_QFREE + w), lane); }
#pragma unroll 1
    for (int jj = 1; jj < nw; jj++) {
      ks = take();
      const uint32_t vs = take();
      if (jj == 1) fence_async_smem();
#pragma unroll
      for (int i = 0; i < 32; i++) s[i] = 0.f;
      prep_qk(sb + ks * SLOT);
      prep_pv(sb + vs * SLOT);
      turn_begin();
      wg_fence();
      issue_qk();
      wg_commit();
      issue_pv(1);
      wg_commit();
      turn_end();
      wg_wait<1>();
      reg_fence(s);
      give(ks, fd);
      if (jj == nw - 1) {
        if (!which) mask_diag();
        else if (lane == 0) mbar_arrive(bar_addr(sb, B_QFREE + w));
      }
      uint32_t pn[16];
      float t0, t1, a0 = 1.f, a1 = 1.f;
      exps(pn, t0, t1);
      const bool redo = __any_sync(0xffffffffu, !(t0 + t1 <= 0x1p30f));
      if (redo) {
        row_max(a0, a1);
        const float c0 = fminf(b0, -SC * a0), c1 = fminf(b1, -SC * a1);
        a0 = ex2(c0 - b0); a1 = ex2(c1 - b1);
        b0 = c0; b1 = c1;
        l0 *= a0; l1 *= a1;
        exps(pn, t0, t1);
      }
      l0 += t0; l1 += t1;
      wg_wait<0>();
      reg_fence(acc);
      reg_fence(pa);
      give(vs, fd + dir);
      fd += 2 * dir;
      if (redo) {
#pragma unroll
        for (int i = 0; i < 32; i++) { acc[4 * i] *= a0; acc[4 * i + 1] *= a0; acc[4 * i + 2] *= a1; acc[4 * i + 3] *= a1; }
      }
#pragma unroll
      for (int i = 0; i < 16; i++) pa[i] = (i & 1) ? pn[i] ^ (one - 1) : pn[i] * one;
    }
    if (!which && up) skip();
    const uint32_t vs = take();
    prep_pv(sb + vs * SLOT);
    turn_begin();
    wg_fence();
    issue_pv(1);
    wg_commit();
    turn_end();
    if (!which && up) r.next();
    ws = take();
    l0 += __shfl_xor_sync(0xffffffffu, l0, 1); l1 += __shfl_xor_sync(0xffffffffu, l1, 1);
    l0 += __shfl_xor_sync(0xffffffffu, l0, 2); l1 += __shfl_xor_sync(0xffffffffu, l1, 2);
    float i0, i1;
    asm volatile("rcp.approx.ftz.f32 %0, %1;" : "=f"(i0) : "f"(l0));
    asm volatile("rcp.approx.ftz.f32 %0, %1;" : "=f"(i1) : "f"(l1));
    if (one == 2) mbar_wait(st_empty, 0);
    wg_wait<0>();
    reg_fence(acc);
    reg_fence(pa);
    give(vs, fd);
#pragma unroll
    for (int i = 0; i < 32; i++) {
      pk[2 * i]     = pack_bf16(acc[4 * i] * i0, acc[4 * i + 1] * i0);
      pk[2 * i + 1] = pack_bf16(acc[4 * i + 2] * i1, acc[4 * i + 3] * i1);
    }
    if (which) break;
    uint32_t xs = r.slot, xaddr = sb + xs * SLOT + (w ^ 1) * 8192;
    r.next();
#pragma unroll 1
    for (int kc = 0;; kc++) {
      const uint64_t da = desc_k(xaddr), db = desc_mn(sb + ws * SLOT);
      turn_begin();
      wg_fence();
#pragma unroll
      for (int kk = 0; kk < 4; kk++) wgmma_ss_n256_tb(acc, desc_add(da, kk * 32), desc_add(db, kk * 2048), (kc | kk) != 0);
      wg_commit();
      turn_end();
      const int cb = kc;
      if (cb >= 1 && cb <= 4) { fence_async_smem(); warp_arrive(bar_addr(sb, B_CTXS + 4 * w + cb - 1), lane); }
      if ((unsigned)cb < 4) {
        if (cb & 2) { if (cb & 1) store_blocks<48, 1>(qreg + 24576, lb, pk); else store_blocks<32, 1>(qreg + 16384, lb, pk); }
        else        { if (cb & 1) store_blocks<16, 1>(qreg + 8192, lb, pk);  else store_blocks<0, 1>(qreg, lb, pk); }
      }
      wg_wait<0>();
      release(bar_addr(sb, B_RG_EMPTY + ws), lane);
      if (!(kc & 1)) release(bar_addr(sb, B_RG_EMPTY + xs), lane);
      if (kc == 6) break;
      ws = take();
      if (!(kc & 1)) { xs = r.slot; r.next(); xaddr = sb + xs * SLOT + (w ^ 1) * 8192; } else xaddr += 16384;
    }
    reg_fence(acc);
#pragma unroll
    for (int i = 0; i < 64; i++) pk[i] = pack_bf16(acc[2 * i], acc[2 * i + 1]);
    qt = 15 - qt;
  }

  {
    float oa[32], ob[32];
#pragma unroll
    for (int i = 0; i < 32; i++) { oa[i] = 0.f; ob[i] = 0.f; }
    auto stage_o = [&](float (&o)[32], int ch) {
      reg_fence(o);
      uint32_t q[16];
#pragma unroll
      for (int i = 0; i < 16; i++) q[i] = pack_bf16(o[2 * i], o[2 * i + 1]);
      if (ch >= 2) mbar_wait(bar_addr(sb, B_S2_EMPTY + w * 2 + (ch & 1)), ((ch >> 1) - 1) & 1);
      store_blocks<0, 1>(qreg + (ch & 1) * 8192, lb, q);
    };
    auto hand_over = [&](int ch) {
      fence_async_smem();
      warp_arrive(bar_addr(sb, B_S2_FULL + w * 2 + (ch & 1)), lane);
    };
    uint32_t pk2[64];
    uint32_t p2 = 0;
    auto chunk = [&](int ch, auto first, float (&o)[32], float (&oprev)[32]) {
      constexpr bool FIRST = decltype(first)::value;
      const uint32_t s1 = FIRST ? ws : take();
      const uint64_t d1 = desc_mn(sb + s1 * SLOT);
      turn_begin();
      wg_fence();
#pragma unroll
      for (int kk = 0; kk < 16; kk++) {
        wgmma_rs_n64_tb(o, pk[4 * kk], pk[4 * kk + 1], pk[4 * kk + 2], pk[4 * kk + 3], desc_add(d1, kk * 2048), kk != 0);
        if (kk == ARRIVE_KK) turn_end();
      }
      wg_commit();
      if constexpr (!FIRST) {
        wg_wait<1>();
        release(bar_addr(sb, B_RG_EMPTY + p2), lane);
        stage_o(oprev, ch - 1);
      } else {
        mbar_wait(bar_addr(sb, B_CTXF + w), 0);
#pragma unroll
        for (int kk = 0; kk < O_PRE; kk++) {
          uint32_t f[4];
          ldsm4(f, qreg + (kk >> 2) * 8192 + (lb ^ ((kk & 3) << 5)));
          pk2[4 * kk] = f[0]; pk2[4 * kk + 1] = f[1]; pk2[4 * kk + 2] = f[2]; pk2[4 * kk + 3] = f[3];
        }
      }
      const uint32_t s2 = take();
      const uint64_t d2 = desc_mn(sb + s2 * SLOT);
      turn_begin();
      wg_fence();
#pragma unroll
      for (int kk = 0; kk < 16; kk++) {
        if (FIRST && kk >= O_PRE) wgmma_ss_n64_tb(o, desc_add(desc_k(qreg), (kk >> 2) * 8192 + (kk & 3) * 32), desc_add(d2, kk * 2048), 1);
        else wgmma_rs_n64_tb(o, pk2[4 * kk], pk2[4 * kk + 1], pk2[4 * kk + 2], pk2[4 * kk + 3], desc_add(d2, kk * 2048), 1);
        if (kk == ARRIVE_KK && (ch < 6 || w == 1)) turn_end();
      }
      wg_commit();
      if (!FIRST) hand_over(ch - 1);
      if constexpr (FIRST) {
#pragma unroll
        for (int kk = O_PRE; kk < 16; kk++) {
          uint32_t f[4];
          ldsm4(f, qreg + (kk >> 2) * 8192 + (lb ^ ((kk & 3) << 5)));
          pk2[4 * kk] = f[0]; pk2[4 * kk + 1] = f[1]; pk2[4 * kk + 2] = f[2]; pk2[4 * kk + 3] = f[3];
        }
      }
      wg_wait<1>();
      release(bar_addr(sb, B_RG_EMPTY + s1), lane);
      p2 = s2;
    };
    chunk(0, Int<1>(), oa, ob);
#pragma unroll 1
    for (int ch = 1; ch < 7; ch += 2) { chunk(ch, Int<0>(), ob, oa); chunk(ch + 1, Int<0>(), oa, ob); }
    wg_wait<0>();
    reg_fence(pk);
    reg_fence(pk2);
    stage_o(oa, 6);
    hand_over(6);
  }

}

#define CONV_STAGGER_NS 1200
namespace ssm {
#define CONV_GROUPS (D_SPARE / 8 / NCONV)
constexpr int GROUPS = CONV_GROUPS;
constexpr uint32_t ZROWS = 16;
constexpr uint32_t CHAN = (ZROWS + 256 + 1) * 16;
constexpr uint32_t XBUF = 8 * CHAN;
constexpr uint32_t OFF_X = 0;
constexpr uint32_t HCOPY = 4160;
constexpr uint32_t OFF_H = 2 * XBUF;
constexpr uint32_t HWARP = 3 * HCOPY;
constexpr uint32_t IO_K = 128, IO_V = IO_K + 4096, IO_Q = IO_V + 4096, IOBUF = IO_Q + 4096;
constexpr uint32_t OFF_IO = (OFF_H + 8 * HWARP + 127) / 128 * 128;
constexpr uint32_t END = OFF_IO + 4 * IOBUF;
static_assert(IOBUF % 128 == 0 && OFF_H % 16 == 0, "TMA destination alignment");
static_assert(END <= BARS, "smem");
enum : uint32_t { B_XREADY = 0, B_ZDONE = 2, B_KV = 4, B_Q = 8, B_HRAW = 12, B_QLAST = 20 };
constexpr int CW_BAR = 4;

__device__ __forceinline__ int group_d0(int cidx, int grp) { return (grp * NCONV + cidx) * 8; }
__device__ __forceinline__ uint32_t x_lane(int lane) { return (lane & 7) * CHAN + (ZROWS + (lane >> 3)) * 16; }
__device__ __forceinline__ uint32_t t_lane(int lane) { return (uint32_t)(8 * (lane >> 3) + 7 - (lane & 7)) * 16; }
struct Taps { uint32_t s[4]; };
__device__ __forceinline__ Taps load_taps(const Params& p, int d0, int c) {
  const uint2 s0 = __ldg(reinterpret_cast<const uint2*>(p.a_shift + (d0 + 2 * c) * 4)), s1 = __ldg(reinterpret_cast<const uint2*>(p.a_shift + (d0 + 2 * c + 1) * 4));
  return Taps{{__byte_perm(s0.x, s1.x, 0x5410), __byte_perm(s0.x, s1.x, 0x7632), __byte_perm(s0.y, s1.y, 0x5410), __byte_perm(s0.y, s1.y, 0x7632)}};
}
__device__ __forceinline__ uint32_t short_conv(const Taps& t, uint32_t k0, uint32_t k1, uint32_t k2, uint32_t k3, uint32_t v) {
  return bmul(badd(badd(badd(bmul(k0, t.s[3]), bmul(k1, t.s[2])), bmul(k2, t.s[1])), bmul(k3, t.s[0])), v);
}
template <int U>
__device__ __forceinline__ void x_chunk(const Taps& taps, uint32_t ka, uint32_t xa) {
#pragma unroll 1
  for (int u0 = 0; u0 < 8; u0 += U) {
    uint32_t k0[U][4], k1[U][4], k2[U][4], k3[U][4], vv[U][4];
#pragma unroll
    for (int u = 0; u < U; u++) {
      const uint32_t a = ka + (u0 + u) * 512;
      ldsm4(k0[u], a - 48); ldsm4(k1[u], a - 32); ldsm4(k2[u], a - 16); ldsm4(k3[u], a); ldsm4(vv[u], a + 4096);
    }
#pragma unroll
    for (int u = 0; u < U; u++)
      stsm4t(xa + (u0 + u) * 64, short_conv(taps, k0[u][0], k1[u][0], k2[u][0], k3[u][0], vv[u][0]), short_conv(taps, k0[u][1], k1[u][1], k2[u][1], k3[u][1], vv[u][1]),
             short_conv(taps, k0[u][2], k1[u][2], k2[u][2], k3[u][2], vv[u][2]), short_conv(taps, k0[u][3], k1[u][3], k2[u][3], k3[u][3], vv[u][3]));
  }
}
template <int U>
__device__ __forceinline__ void shift_filter(uint32_t hE, uint32_t hO, int lane) {
#pragma unroll 1
  for (int i0 = 0; i0 < 8; i0 += U) {
    uint4 w[U]; uint32_t nx[U];
    const uint32_t o = 32 + lane * 16 + i0 * 512;
#pragma unroll
    for (int i = 0; i < U; i++) { w[i] = lds16(hE + o + i * 512); nx[i] = lds4(hE + o + i * 512 + 16); }
#pragma unroll
    for (int i = 0; i < U; i++)
      sts16(hO + o + i * 512, __byte_perm(w[i].x, w[i].y, 0x5432), __byte_perm(w[i].y, w[i].z, 0x5432), __byte_perm(w[i].z, w[i].w, 0x5432), __byte_perm(w[i].w, nx[i], 0x5432));
    if (o == 32) asm volatile("st.shared.u32 [%0], %1;" :: "r"(hO + 28), "r"(w[0].x << 16) : "memory");
  }
}
template <int U>
__device__ __forceinline__ void gate_chunk(uint32_t xa, uint32_t qa) {
#pragma unroll 1
  for (int i0 = 0; i0 < 8; i0 += U) {
    uint32_t zz[U][4], qq[U][4];
#pragma unroll
    for (int i = 0; i < U; i++) { ldsm4t(zz[i], xa + (i0 + i) * 64); ldsm4(qq[i], qa + (i0 + i) * 512); }
#pragma unroll
    for (int i = 0; i < U; i++) stsm4(qa + (i0 + i) * 512, bmul(qq[i][0], zz[i][0]), bmul(qq[i][1], zz[i][1]), bmul(qq[i][2], zz[i][2]), bmul(qq[i][3], zz[i][3]));
  }
}

__device__ __forceinline__ void io_warp(const Params& p, uint32_t sb, int cidx, int wq) {
  const int lane = threadIdx.x & 31;
  const uint32_t io = sb + OFF_IO + wq * IOBUF, bkv = bar_addr(sb, B_KV + wq), bq = bar_addr(sb, B_Q + wq);
  auto load_kv = [&](int e) {
    __syncwarp();
    if (lane != 0) return;
    const int d0 = group_d0(cidx, e >> 1), row = (2 * wq + (e & 1)) * 256;
    if (e < 2 * GROUPS) {
      mbar_expect_tx(bkv, IO_Q);
      tma_ld2(io, &p.ak8, bkv, d0, row - 8);
      tma_ld2(io + IO_K, &p.ak, bkv, d0, row);
      tma_ld2(io + IO_V, &p.av, bkv, d0, row);
    } else {
      const uint32_t bar = bar_addr(sb, B_QLAST + 2 * wq + 1);
      mbar_expect_tx(bar, 4096);
      tma_ld2(io + IO_K, &p.aq, bar, group_d0(cidx, GROUPS - 1), row + 256);
    }
  };
  auto load_q = [&](int e) {
    __syncwarp();
    if (lane != 0) return;
    const uint32_t bar = e < 2 * GROUPS - 2 ? bq : bar_addr(sb, B_QLAST + 2 * wq);
    mbar_expect_tx(bar, 4096);
    tma_ld2(io + IO_Q, &p.aq, bar, group_d0(cidx, e >> 1), (2 * wq + (e & 1)) * 256);
  };
  load_kv(0);
  const uint32_t xl = sb + OFF_X + x_lane(lane) + wq * 1024, tl = io + t_lane(lane);
#pragma unroll 1
  for (int grp = -2; grp + 1 < GROUPS; grp++) {
    const bool more = grp + 2 < GROUPS;
    const Taps taps = load_taps(p, group_d0(cidx, more ? grp + 2 : 0), lane & 3);
    if (grp >= 0) mbar_wait_nap(bar_addr(sb, B_ZDONE + (grp & 1)), (grp >> 1) & 1);

#pragma unroll 1
    for (int i = 0; i < 2; i++) {
      const uint32_t xa = xl + (grp & 1) * XBUF + i * 512;
      if (grp >= 0) {
        mbar_wait_nap(bq, i);
        gate_chunk<4>(xa, tl + IO_Q);
      }
      if (more) {
        mbar_wait_nap(bkv, i);
        x_chunk<2>(taps, tl + IO_K, xa);
        load_kv(2 * (grp + 2) + i + 1);
        if (i == 1) warp_arrive(bar_addr(sb, B_XREADY + (grp & 1)), lane);
      }
      if (grp >= 0) {
        fence_async_smem();
        __syncwarp();
        if (lane == 0) {
          tma_st2(&p.ao, io + IO_Q, group_d0(cidx, grp), (2 * wq + i) * 256);
          bulk_commit();
          bulk_wait_read();
        }
      }
      if (2 * grp + i + 1 >= 0) load_q(2 * grp + i + 1);
    }
  }
  if (lane == 0) bulk_wait_all();
}

__device__ __forceinline__ void conv_warp(const Params& p, uint32_t sb, int cidx, int ch) {
  const int lane = threadIdx.x & 31;
  const uint32_t hE0 = sb + OFF_H + ch * HWARP, hO = hE0 + HCOPY;
  const uint32_t hbar = bar_addr(sb, B_HRAW + ch);
  auto fetch_h = [&](int grp) {
    if (lane == 0) {
      mbar_expect_tx(hbar, 4096);
      asm volatile("cp.async.bulk.shared::cluster.global.mbarrier::complete_tx::bytes [%0], [%1], %2, [%3];"
                   :: "r"(hE0 + (grp & 1) * 2 * HCOPY + 32), "l"(p.a_ssmk + (size_t)(group_d0(cidx, grp) + ch) * SEQ), "r"(4096), "r"(hbar) : "memory");
    }
  };
  fetch_h(0);
#pragma unroll 1
  for (int grp = 0; grp < GROUPS; grp++) {
    const uint32_t xc = sb + OFF_X + (grp & 1) * XBUF + ch * CHAN;
    const uint32_t D1 = __ldg(reinterpret_cast<const unsigned short*>(p.a_D + group_d0(cidx, grp) + ch));
    mbar_wait(hbar, grp & 1);
    const uint32_t hE = hE0 + (grp & 1) * 2 * HCOPY;
    if (grp + 1 < GROUPS) fetch_h(grp + 1);
    shift_filter<8>(hE, hO, lane);
    __syncwarp();
    const uint32_t ha = cv_h_lane(lane, hE, hO), xa = xc + cv_x_lane(lane);
    mbar_wait(bar_addr(sb, B_XREADY + (grp & 1)), (grp >> 1) & 1);
    if (grp == 0 && ch >= 4) __nanosleep(CONV_STAGGER_NS);

    float acc[16][4];
#pragma unroll
    for (int i = 0; i < 16; i++) { acc[i][0] = 0.f; acc[i][1] = 0.f; acc[i][2] = 0.f; acc[i][3] = 0.f; }
#pragma unroll 1
    for (int r = 0; r < 8; r++) {
      uint32_t fx[16][4], fh[16][2];
#pragma unroll
      for (int i = 0; i < 16; i++) { fh[i][0] = lds4(ha + i * 256 + r * 32); fh[i][1] = lds4(ha + i * 256 + r * 32 + 16); }
#pragma unroll
      for (int i = 0; i < 16; i++) ldsm4(fx[i], xa + i * 256 - r * 32);
#pragma unroll
      for (int sx = 0; sx < 16; sx++)
#pragma unroll
        for (int jj = 0; jj < 16 - sx; jj++) mma16816(acc[jj + sx], fx[sx], fh[jj][0], fh[jj][1]);
    }

    {
      uint32_t x[8][4], Dd;
      asm volatile("prmt.b32 %0, %1, %1, 0x1010;" : "=r"(Dd) : "r"(D1));
      const uint32_t ad = xc + (ZROWS + lane) * 16;
#pragma unroll
      for (int i = 0; i < 8; i++) ldsm4(x[i], ad + i * 512);
#pragma unroll
      for (int i = 0; i < 8; i++)
        stsm4(ad + i * 512, add_skip(pack_bf16(acc[2 * i][0], acc[2 * i][1]), x[i][0], Dd), add_skip(pack_bf16(acc[2 * i][2], acc[2 * i][3]), x[i][1], Dd),
              add_skip(pack_bf16(acc[2 * i + 1][0], acc[2 * i + 1][1]), x[i][2], Dd), add_skip(pack_bf16(acc[2 * i + 1][2], acc[2 * i + 1][3]), x[i][3], Dd));
    }
    if (grp + 1 < GROUPS) warp_arrive(bar_addr(sb, B_ZDONE + (grp & 1)), lane);
  }
  {
    mbar_wait(bar_addr(sb, B_QLAST + ch), 0);
    named_sync(CW_BAR, 256);
    const uint32_t qb = sb + OFF_IO + (ch >> 1) * IOBUF + ((ch & 1) ? IO_K : IO_Q);
    gate_chunk<8>(sb + OFF_X + ((GROUPS - 1) & 1) * XBUF + x_lane(lane) + ch * 512, qb + t_lane(lane));
    fence_async_smem();
    __syncwarp();
    if (lane == 0) { tma_st2(&p.ao, qb, group_d0(cidx, GROUPS - 1), ch * 256); bulk_commit(); bulk_wait_read(); }
  }
}

__device__ __forceinline__ void init(uint32_t sb) {
  if (threadIdx.x < 16 * ZROWS) sts16(sb + OFF_X + (threadIdx.x >> 4) * CHAN + (threadIdx.x & 15) * 16, 0, 0, 0, 0);
  if (threadIdx.x < 96) sts16(sb + OFF_H + (threadIdx.x >> 2) * HCOPY + (threadIdx.x & 1) * 16 + ((threadIdx.x & 2) ? 4128 : 0), 0, 0, 0, 0);
  if (threadIdx.x == 0) {
    for (int i = 0; i < 2; i++) { mbar_init(bar_addr(sb, B_XREADY + i), 4); mbar_init(bar_addr(sb, B_ZDONE + i), 8); }
    for (int i = 0; i < 4; i++) { mbar_init(bar_addr(sb, B_KV + i), 1); mbar_init(bar_addr(sb, B_Q + i), 1); }
    for (int i = 0; i < 8; i++) { mbar_init(bar_addr(sb, B_HRAW + i), 1); mbar_init(bar_addr(sb, B_QLAST + i), 1); }
    fence_async_smem();
  }
  named_sync(0, NTHREADS);
}
}

__device__ __forceinline__ void ssm_side_work(const Params& p, uint32_t sb, unsigned epoch) {
  const Role ro = get_role();
  const int h = ro.h, j = ro.j;
  const int lane = threadIdx.x & 31;
  const int d0 = D_SPARE + 8 * h;
  constexpr uint32_t ZCH = 528;
  {
    const uint32_t kb = sb + P1_STG, xb = kb + 8320, hE = xb + 8 * ZCH, hO = hE + CV_HCOPY, zero = sb + ZEROS, bar = bar_addr(sb, B_SIDE);
    if (lane == 0) {
      mbar_expect_tx(bar, 128 + 3 * 4096);
      tma_ld2(kb, &p.ak8, bar, d0, 256 * j - 8);
      tma_ld2(kb + 128, &p.ak, bar, d0, 256 * j);
      bulk_ld(hE + 32, p.a_ssmk + (size_t)(d0 + j) * SEQ, 4096, bar);
      __nanosleep(600);
      tma_ld2(kb + 128 + 4096, &p.av, bar, d0, 256 * j);
    }
    const ssm::Taps taps = ssm::load_taps(p, d0, lane & 3);
    const uint32_t Dd = (uint32_t)__ldg(reinterpret_cast<const unsigned short*>(p.a_D + d0 + j)) * 0x10001u;
    sts16(zero + lane * 16, 0, 0, 0, 0); sts16(zero + 512 + lane * 16, 0, 0, 0, 0);
    if (lane < 8) sts16(hE + (lane >> 2) * CV_HCOPY + (lane & 1) * 16 + ((lane & 2) ? 4128 : 0), lane == 3 ? Dd : 0, 0, 0, 0);
    __syncwarp();
    mbar_wait_nap(bar, 0);
    ssm::x_chunk<1>(taps, kb + 128 + ssm::t_lane(lane), xb + (lane & 7) * ZCH + (lane >> 3) * 16);
    ssm::shift_filter<2>(hE, hO, lane);
    fence_async_smem();
    __syncwarp();
    if (lane == 0) {
      uint8_t* img = g_xs + (size_t)(h * 8) * CV_BYTES;
      for (int i = 0; i < 8; i++) bulk_st(img + i * CV_BYTES + (16 + 32 * j) * 16, xb + i * ZCH, 512);
      bulk_st(img + j * CV_BYTES, zero, 256);
      for (int i = 0; i < 4; i++) { __nanosleep(200); bulk_st(img + j * CV_BYTES + CV_HE + i * (CV_HCOPY / 2), hE + i * (CV_HCOPY / 2), CV_HCOPY / 2); }
      bulk_commit();
      bulk_wait_read();
      mbar_arrive(bar_addr(sb, B_SIDE + 1));
      bulk_wait_all();
      flag_signal(&g_flags.xs_ready[h].v);
      flag_wait(&g_flags.xs_ready[h].v, 8, epoch);
      fence_async_all();
      mbar_arrive(bar_addr(sb, B_XS));
    }
  }
  if (lane == 0) {
    for (int i = 0; i < 3; i++) {
      flag_wait(&g_flags.kv_ready[3 * h + i].v, 16, epoch);
      fence_async_all();
      mbar_arrive(bar_addr(sb, B_KV + i));
    }
    const int qt = q_tile(h, j, 1), cta = h * 8 + j;
    mbar_wait_nap(bar_addr(sb, B_CONV), 0);
    for (int i = 0; i < 16; i++) { bulk_st(p.out + (size_t)(qt * 128 + (h & 7) * 16 + i) * OUTW + DA, sb + ZEROS, DM * 2); __nanosleep(50); }
    bulk_commit();
    bulk_wait_all();
    flag_signal(&g_flags.zs_ready[h].v);
    flag_signal_again(&g_flags.out_ready[qt].v);
    flag_wait(&g_flags.zs_ready[h].v, 8, epoch);
    flag_wait(&g_flags.out_ready[qt].v, 8, epoch);
    for (int i = 0; i < 2; i++) {
      if ((i == 0) == (h >= 8)) {
        mbar_wait_nap(bar_addr(sb, B_CTXD), 0);
        flag_signal(&g_flags.ctx_ready[cta].v);
      } else {
        flag_wait(&g_flags.ctx_ready[cta ^ 64].v, 1, epoch);
        fence_async_all();
        mbar_arrive(bar_addr(sb, B_CTXD + 1));
      }
    }
    asm volatile("red.relaxed.gpu.global.add.u64 [%0], 1;" :: "l"(&g_flags.done) : "memory");
  }
  __syncwarp();
  fence_async_all();
  const uint32_t qb = q_region(sb, 1) + 16384, zb = qb + 4096, bar = bar_addr(sb, B_GATE);
  mbar_wait_slow(bar_addr(sb, B_GFREE), 0);
  if (lane == 0) { mbar_expect_tx(bar, 8192); tma_ld2(qb, &p.aq, bar, d0, 256 * j); }
  __syncwarp();
  if (lane < 8) bulk_ld(zb + lane * ZCH, g_xs + (size_t)(h * 8 + lane) * CV_BYTES + (16 + 32 * j) * 16, 512, bar);
  mbar_wait(bar, 0);
  ssm::gate_chunk<2>(zb + (lane & 7) * ZCH + (lane >> 3) * 16, qb + ssm::t_lane(lane));
  fence_async_smem();
  __syncwarp();
  if (lane == 0) { tma_st2(&p.ao, qb, d0, 256 * j); bulk_commit(); bulk_wait_all(); }
}

__global__ void __cluster_dims__(2, 1, 1) __launch_bounds__(NTHREADS, 1)
concat_heads__ssm_conv_h3__compressed_kv_cla__prompt_kernel(uint8_t* xs, uint32_t one, const __grid_constant__ Params p) {
  if (threadIdx.x == 0) { prefetch_map(&p.wuk); prefetch_map(&p.ckv); }
  extern __shared__ uint8_t smem_raw[];
  const uint32_t sb = (smem_u32(smem_raw) + 1023) & ~1023u;
  const int warp = __shfl_sync(0xffffffffu, threadIdx.x >> 5, 0);
  const int wg = warp >> 2;
  const int cta = blockIdx.x;
  const bool attn = cta < NMAIN;
  if (attn && (threadIdx.x >> 5) == 4) {
    const Role ro = get_role();
    auto load = [&](int k) {
      const uint32_t full = bar_addr(sb, B_P1_FULL + k), dst = sb + k * P1_STAGE;
      mbar_expect_tx(full, P1_STAGE);
      tma_ld2(dst, &p.ckv, full, k * 64, kv_block(ro.j, 0) * 128);
      tma_ld3(dst + 16384, &p.wuk, full, 0, k * 64, ro.h * 4);
    };
    if (threadIdx.x == 128) {
      for (int i = 0; i < 4; i++) mbar_init(bar_addr(sb, B_P1_FULL + i), 1);
      asm volatile("fence.mbarrier_init.release.cluster;" ::: "memory");
      load(0);
    }
    __syncwarp();
    named_arrive(0, NTHREADS);
    if (threadIdx.x == 128) {
      for (int k = 1; k < EARLY_LD; k++) load(k);
    }
    __syncwarp();
  }
  const int lane = threadIdx.x & 31;
  if (wg == 0) {
    if (!attn) {
      asm volatile("setmaxnreg.dec.sync.aligned.u32 72;");
      if (one) { ssm::init(sb); ssm::io_warp(p, sb, cta - NMAIN, fresh_warp()); }
      return;
    }
    asm volatile("setmaxnreg.dec.sync.aligned.u32 40;");
    named_arrive(PP_BAR + 1, 256);
    if (warp == 2) {
      if (lane == 0) {
        for (int i = 0; i < 4; i++) mbar_init(bar_addr(sb, B_P1_EMPTY + i), 8);
        for (int i = 0; i < NSLOT; i++) {
          mbar_init(bar_addr(sb, B_RG_FULL + i), 1); mbar_init(bar_addr(sb, B_RG_EMPTY + i), 8);
        }
        for (int i = 0; i < 2; i++) { mbar_init(bar_addr(sb, B_ST_FULL + i), 4); mbar_init(bar_addr(sb, B_ST_EMPTY + i), 1); }
        mbar_init(bar_addr(sb, B_XS), 1); mbar_init(bar_addr(sb, B_SIDE), 1); mbar_init(bar_addr(sb, B_SIDE + 1), 1);
        mbar_init(bar_addr(sb, B_CTXD), 2); mbar_init(bar_addr(sb, B_CTXD + 1), 1); mbar_init(bar_addr(sb, B_CONV), 8); mbar_init(bar_addr(sb, B_GATE), 1); mbar_init(bar_addr(sb, B_GFREE), 1);
        for (int i = 0; i < 3; i++) mbar_init(bar_addr(sb, B_KV + i), 1);
        for (int i = 0; i < 8; i++) mbar_init(bar_addr(sb, B_CTXS + i), 4);
        for (int i = 0; i < 4; i++) { mbar_arrive(bar_addr(sb, B_RG_FULL + i)); if (i < 3) mbar_arrive_n(bar_addr(sb, B_RG_EMPTY + i), 8); }
        for (int i = 0; i < 4; i++) { mbar_init(bar_addr(sb, B_S2_FULL + i), 4); mbar_init(bar_addr(sb, B_S2_EMPTY + i), 1); }
        for (int i = 0; i < 2; i++) { mbar_init(bar_addr(sb, B_QFREE + i), 4); mbar_init(bar_addr(sb, B_CTXF + i), 1); }
        asm volatile("fence.mbarrier_init.release.cluster;" ::: "memory");
      }
      __syncwarp();
      named_arrive(0, NTHREADS);
    } else {
      named_sync(0, NTHREADS);
    }
    if (warp == 0) {
      if (lane == 0) producer_main(p, sb);
    } else if (warp < 3) {
      storer_main(p, sb);
    } else {
      const unsigned epoch = load_epoch();
      mbar_wait(bar_addr(sb, B_P1_FULL + 3), 0);
      __nanosleep(SIDE_DELAY_NS);
      ssm_side_work(p, sb, epoch);
    }
  } else {
    if (attn) {
      asm volatile("setmaxnreg.inc.sync.aligned.u32 232;");
      if (one) consumer_main(p, sb, xs, one);
    } else {
      asm volatile("setmaxnreg.inc.sync.aligned.u32 216;");
      if (one) { ssm::init(sb); ssm::conv_warp(p, sb, cta - NMAIN, fresh_warp() - 4); }
    }
  }
}

typedef CUresult (*EncodeTiledFn)(CUtensorMap*, CUtensorMapDataType, cuuint32_t, void*, const cuuint64_t*, const cuuint64_t*,
                                  const cuuint32_t*, const cuuint32_t*, CUtensorMapInterleave, CUtensorMapSwizzle,
                                  CUtensorMapL2promotion, CUtensorMapFloatOOBfill);

void make_map(EncodeTiledFn enc, CUtensorMap* m, const void* ptr, int rank, const uint64_t* dims, const uint64_t* strides, const uint32_t* box) {
  cuuint64_t d[3], s[2]; cuuint32_t b[3], e[3] = {1, 1, 1};
  for (int i = 0; i < rank; i++) { d[i] = dims[i]; b[i] = box[i]; if (i) s[i - 1] = strides[i - 1]; }
  enc(m, CU_TENSOR_MAP_DATA_TYPE_BFLOAT16, rank, const_cast<void*>(ptr), d, s, b, e, CU_TENSOR_MAP_INTERLEAVE_NONE,
      CU_TENSOR_MAP_SWIZZLE_128B, CU_TENSOR_MAP_L2_PROMOTION_L2_256B, CU_TENSOR_MAP_FLOAT_OOB_FILL_NONE);
}
void map2(EncodeTiledFn enc, CUtensorMap* m, const void* ptr, uint64_t cols, uint64_t rows, uint32_t bc, uint32_t br) {
  const uint64_t dims[2] = {cols, rows}, st[1] = {cols * 2}; const uint32_t box[2] = {bc, br};
  make_map(enc, m, ptr, 2, dims, st, box);
}
void map2_plain(EncodeTiledFn enc, CUtensorMap* m, const void* ptr, uint64_t cols, uint64_t rows, uint32_t bc, uint32_t br) {
  cuuint64_t d[2] = {cols, rows}, st[1] = {cols * 2}; cuuint32_t b[2] = {bc, br}, e[2] = {1, 1};
  enc(m, CU_TENSOR_MAP_DATA_TYPE_BFLOAT16, 2, const_cast<void*>(ptr), d, st, b, e, CU_TENSOR_MAP_INTERLEAVE_NONE,
      CU_TENSOR_MAP_SWIZZLE_NONE, CU_TENSOR_MAP_L2_PROMOTION_L2_128B, CU_TENSOR_MAP_FLOAT_OOB_FILL_NONE);
}
void map3(EncodeTiledFn enc, CUtensorMap* m, const void* ptr, uint64_t rows, uint32_t nblk) {
  const uint64_t dims[3] = {64, rows, 64}, st[2] = {8192, 128}; const uint32_t box[3] = {64, 64, nblk};
  make_map(enc, m, ptr, 3, dims, st, box);
}

}

extern "C" void kernel_launch(void* const* d_in, const int* in_sizes, int n_in, void* d_out, int out_size) {
  (void)in_sizes; (void)n_in; (void)out_size;
  static EncodeTiledFn enc = nullptr;
  static void *kv_ptr = nullptr, *acc_ptr = nullptr, *xs_ptr = nullptr;
  if (!enc) {
    void* fn = nullptr; cudaDriverEntryPointQueryResult qr;
    cudaGetDriverEntryPoint("cuTensorMapEncodeTiled", &fn, cudaEnableDefault, &qr);
    enc = (EncodeTiledFn)fn;
    cudaGetSymbolAddress(&kv_ptr, g_kv);
    cudaGetSymbolAddress(&acc_ptr, g_ctx);
    cudaGetSymbolAddress(&xs_ptr, g_xs);
    cudaFuncSetAttribute(concat_heads__ssm_conv_h3__compressed_kv_cla__prompt_kernel, cudaFuncAttributeMaxDynamicSharedMemorySize, SMEM_BYTES);
  }
  Params p;
  map2_plain(enc, &p.aq, d_in[0], DA, SEQ, 8, 256);
  map2_plain(enc, &p.ak, d_in[1], DA, SEQ, 8, 256);
  map2_plain(enc, &p.ak8, d_in[1], DA, SEQ, 8, 8);
  map2_plain(enc, &p.av, d_in[2], DA, SEQ, 8, 256);
  map2_plain(enc, &p.ao, d_out, OUTW, SEQ, 8, 256);
  p.a_shift = (const bf16*)d_in[3]; p.a_ssmk = (const bf16*)d_in[4]; p.a_D = (const bf16*)d_in[5];
  p.out = (bf16*)d_out; p.b_x = (const bf16*)d_in[6]; p.b_wo = (const bf16*)d_in[11];
  map2(enc, &p.x, d_in[6], DM, SEQ, 64, 128);
  map2(enc, &p.ckv, d_in[7], DC, SEQ, 64, 128);
  map3(enc, &p.wq, d_in[8], DM, 4);
  map2_plain(enc, &p.wqp, d_in[8], NH * HD, DM, 256, 4);
  map3(enc, &p.wuk, d_in[9], DC, 4);
  map3(enc, &p.wuv, d_in[10], DC, 4);
  map2(enc, &p.wo, d_in[11], DM, NH * HD, 64, 256);
  map2(enc, &p.part, d_out, OUTW, SEQ, 64, 64);
  p.kv = (uint8_t*)kv_ptr; p.ctx = (uint8_t*)acc_ptr;
  concat_heads__ssm_conv_h3__compressed_kv_cla__prompt_kernel<<<NCTA, NTHREADS, SMEM_BYTES>>>((uint8_t*)xs_ptr, 1u, p);
}
```

```cpp
#include <cuda_runtime.h>
#include <cuda_bf16.h>
#include <cuda.h>
#include <stdint.h>

namespace {

typedef __nv_bfloat16 bf16;

constexpr int SEQ  = 2048;
constexpr int DA   = 448;
constexpr int NH   = 16;
constexpr int HD   = 256;
constexpr int DM   = 448;
constexpr int DC   = 1024;
constexpr int OUTW = DA + DM;
constexpr int NMAIN = 128;
constexpr int NCONV = 4;
constexpr int NCTA  = NMAIN + NCONV;
constexpr int NTHREADS = 384;
constexpr int D_SPARE = 320;

constexpr int CTX_TILE0 = 2 * NH * 32, NTILES = CTX_TILE0 + 2 * NMAIN;
__device__ __align__(1024) uint8_t g_tiles[(size_t)NTILES * 32768];
constexpr uint32_t CV_HCOPY = 4160, CV_D = 4144, CV_XO = 2 * CV_HCOPY, CV_BYTES = CV_XO + 272 * 16, CV_LINES = CV_BYTES / 128, CV_OWN = (CV_XO + 256) / 128;
__device__ __align__(128) uint8_t g_xs[NMAIN * CV_BYTES];
struct alignas(128) Flag { unsigned v; unsigned pad[31]; };
struct Flags {
  Flag kv_ready[3 * NH];
  Flag ctx_ready[NMAIN];
  Flag out_ready[16];
  Flag xs_ready[NH];
  Flag zs_ready[NH];
  alignas(128) unsigned long long done;
};
__device__ Flags g_flags;

struct alignas(64) Params {
  CUtensorMap ckv;
  CUtensorMap wuk;
  CUtensorMap wuv;
  CUtensorMap x;
  CUtensorMap wq;
  CUtensorMap wqp;
  CUtensorMap wkp, wvp, ckp, xp, wop;
  CUtensorMap tl, ts;
  CUtensorMap xs3, xso, xsx;
  CUtensorMap oz;
  CUtensorMap part;
  CUtensorMap wo;
  CUtensorMap ak, ak8, av, aq, ao;
  const bf16 *a_shift, *a_ssmk, *a_D;
};

constexpr uint32_t P1_STAGE = 49152;
constexpr uint32_t P1_STG   = 196608;
constexpr uint32_t SLOT     = 32768;
constexpr int      NSLOT    = 5;
constexpr uint32_t QREG     = 163840;
constexpr uint32_t CV_X = 4 * SLOT + 16384, CV_R = 3 * SLOT;
static_assert(CV_BYTES <= 16384 && CV_BYTES % 128 == 0, "SSM operands");
constexpr uint32_t BARS     = 229376;
constexpr uint32_t SMEM_BYTES = BARS + 512 + 1024;
enum : uint32_t {
  B_P1_FULL = 0, B_P1_EMPTY = 4, B_RG_FULL = 8, B_RG_EMPTY = 13, B_ST_FULL = 18, B_ST_EMPTY = 20,
  B_XS = 22, B_SIDE = 23, B_CTXD = 25, B_S2_FULL = 28, B_S2_EMPTY = 32, B_QFREE = 36, B_CTXF = 38, B_KV = 40, B_GATE = 43, B_CTXS = 44, B_GFREE = 52, B_CONV = 53, B_COUNT = 54
};

__device__ __forceinline__ uint32_t smem_u32(const void* p) { return (uint32_t)__cvta_generic_to_shared(p); }
__device__ __forceinline__ void mbar_init(uint32_t bar, uint32_t cnt) {
  asm volatile("mbarrier.init.shared::cta.b64 [%0], %1;" :: "r"(bar), "r"(cnt) : "memory");
}
__device__ __forceinline__ void mbar_expect_tx(uint32_t bar, uint32_t bytes) {
  asm volatile("mbarrier.arrive.expect_tx.shared::cta.b64 _, [%0], %1;" :: "r"(bar), "r"(bytes) : "memory");
}
__device__ __forceinline__ void mbar_arrive(uint32_t bar) {
  asm volatile("mbarrier.arrive.shared::cta.b64 _, [%0];" :: "r"(bar) : "memory");
}
__device__ __forceinline__ void mbar_arrive_n(uint32_t bar, uint32_t n) {
  asm volatile("mbarrier.arrive.shared::cta.b64 _, [%0], %1;" :: "r"(bar), "r"(n) : "memory");
}
__device__ __forceinline__ void lane0_arrive(uint32_t bar, uint32_t n, int lane) {
  asm volatile("{\n.reg .pred p;\nsetp.eq.s32 p, %2, 0;\n@p mbarrier.arrive.shared::cta.b64 _, [%0], %1;\n}" :: "r"(bar), "r"(n), "r"(lane) : "memory");
}
__device__ __forceinline__ bool mbar_try(uint32_t bar, uint32_t parity) {
  uint32_t ok;
  asm volatile("{\n.reg .pred p;\nmbarrier.try_wait.parity.shared::cta.b64 p, [%1], %2;\nselp.u32 %0, 1, 0, p;\n}"
               : "=r"(ok) : "r"(bar), "r"(parity) : "memory");
  return ok;
}
#define FLAG_NS 100
#define NAP_NS 100
constexpr uint32_t SPIN_LIMIT = 1u << 24;
__device__ __forceinline__ void mbar_wait(uint32_t bar, uint32_t parity) {
  if (mbar_try(bar, parity)) return;
  uint32_t n = 0;
  while (!mbar_try(bar, parity)) { if (++n > SPIN_LIMIT) __trap(); }
}
__device__ __forceinline__ void mbar_wait_nap(uint32_t bar, uint32_t parity) {
  uint32_t n = 0;
  while (!mbar_try(bar, parity)) { if (++n > (SPIN_LIMIT >> 2)) __trap(); __nanosleep(NAP_NS); }
}
__device__ __forceinline__ void mbar_wait_slow(uint32_t bar, uint32_t parity) {
  uint32_t n = 0;
  while (!mbar_try(bar, parity)) { if (++n > (SPIN_LIMIT >> 4)) __trap(); __nanosleep(500); }
}
__device__ __forceinline__ unsigned load_epoch() {
  unsigned long long e; asm volatile("ld.relaxed.gpu.global.u64 %0, [%1];" : "=l"(e) : "l"(&g_flags.done) : "memory"); return (unsigned)(e / NMAIN);
}
__device__ __forceinline__ void flag_wait(const unsigned* f, unsigned count, unsigned epoch) {
  const unsigned target = (epoch + 1) * count;
  uint32_t n = 0;
  while (true) {
    unsigned v;
    asm volatile("ld.acquire.gpu.global.u32 %0, [%1];" : "=r"(v) : "l"(f) : "memory");
    if ((int)(v - target) >= 0) break;
    if (++n > SPIN_LIMIT) __trap();
    __nanosleep(FLAG_NS);
  }
}
__device__ __forceinline__ void fence_async_all() { asm volatile("fence.proxy.async;" ::: "memory"); }
__device__ __forceinline__ void flag_signal(unsigned* f) {
  asm volatile("fence.acq_rel.gpu;" ::: "memory");
  asm volatile("red.relaxed.gpu.global.add.u32 [%0], 1;" :: "l"(f) : "memory");
}
__device__ __forceinline__ void flag_signal_again(unsigned* f) {
  asm volatile("red.relaxed.gpu.global.add.u32 [%0], 1;" :: "l"(f) : "memory");
}
__device__ __forceinline__ void fence_async_smem() { asm volatile("fence.proxy.async.shared::cta;" ::: "memory"); }
__device__ __forceinline__ void tma_ld2(uint32_t dst, const CUtensorMap* m, uint32_t bar, int c0, int c1) {
  asm volatile("cp.async.bulk.tensor.2d.shared::cluster.global.mbarrier::complete_tx::bytes [%0], [%1, {%3, %4}], [%2];"
               :: "r"(dst), "l"(m), "r"(bar), "r"(c0), "r"(c1) : "memory");
}
__device__ __forceinline__ void tma_ld3(uint32_t dst, const CUtensorMap* m, uint32_t bar, int c0, int c1, int c2) {
  asm volatile("cp.async.bulk.tensor.3d.shared::cluster.global.mbarrier::complete_tx::bytes [%0], [%1, {%3, %4, %5}], [%2];"
               :: "r"(dst), "l"(m), "r"(bar), "r"(c0), "r"(c1), "r"(c2) : "memory");
}
__device__ __forceinline__ void bulk_ld(uint32_t dst, const void* src, uint32_t bytes, uint32_t bar) {
  asm volatile("cp.async.bulk.shared::cluster.global.mbarrier::complete_tx::bytes [%0], [%1], %2, [%3];"
               :: "r"(dst), "l"(src), "r"(bytes), "r"(bar) : "memory");
}
__device__ __forceinline__ void tma_st3(const CUtensorMap* m, uint32_t src, int c0, int c1, int c2) {
  asm volatile("cp.async.bulk.tensor.3d.global.shared::cta.bulk_group [%0, {%2, %3, %4}], [%1];"
               :: "l"(m), "r"(src), "r"(c0), "r"(c1), "r"(c2) : "memory");
}
__device__ __forceinline__ void tma_st2(const CUtensorMap* m, uint32_t src, int c0, int c1) {
  asm volatile("cp.async.bulk.tensor.2d.global.shared::cta.bulk_group [%0, {%2, %3}], [%1];"
               :: "l"(m), "r"(src), "r"(c0), "r"(c1) : "memory");
}
__device__ __forceinline__ void tma_red2(const CUtensorMap* m, uint32_t src, int c0, int c1) {
  asm volatile("cp.reduce.async.bulk.tensor.2d.global.shared::cta.add.tile.bulk_group [%0, {%2, %3}], [%1];"
               :: "l"(m), "r"(src), "r"(c0), "r"(c1) : "memory");
}
__device__ __forceinline__ void tma_pf2(const CUtensorMap* m, int c0, int c1) {
  asm volatile("cp.async.bulk.prefetch.tensor.2d.L2.global.tile [%0, {%1, %2}];" :: "l"(m), "r"(c0), "r"(c1) : "memory");
}
__device__ __forceinline__ void bulk_commit() { asm volatile("cp.async.bulk.commit_group;" ::: "memory"); }
__device__ __forceinline__ void bulk_wait_read() { asm volatile("cp.async.bulk.wait_group.read 0;" ::: "memory"); }
__device__ __forceinline__ void bulk_wait_all() { asm volatile("cp.async.bulk.wait_group 0;" ::: "memory"); }
__device__ __forceinline__ void prefetch_map(const CUtensorMap* m) { asm volatile("prefetch.tensormap [%0];" :: "l"(m) : "memory"); }
__device__ __forceinline__ void wg_fence() { asm volatile("wgmma.fence.sync.aligned;" ::: "memory"); }
__device__ __forceinline__ void wg_commit() { asm volatile("wgmma.commit_group.sync.aligned;" ::: "memory"); }
template <int N> __device__ __forceinline__ void wg_wait() { asm volatile("wgmma.wait_group.sync.aligned %0;" :: "n"(N) : "memory"); }
template <int N> __device__ __forceinline__ void reg_fence(float (&d)[N]) {
#pragma unroll
  for (int i = 0; i < N; i++) asm volatile("" : "+f"(d[i]) :: "memory");
}
template <int N> __device__ __forceinline__ void reg_fence(uint32_t (&d)[N]) {
#pragma unroll
  for (int i = 0; i < N; i++) asm volatile("" : "+r"(d[i]) :: "memory");
}
__device__ __forceinline__ uint32_t fresh_tid() { uint32_t t; asm volatile("mov.u32 %0, %%tid.x;" : "=r"(t)); return t; }
__device__ __forceinline__ uint32_t lane_base16() {
  const uint32_t t = fresh_tid(), lane = t & 31, wq = (t >> 5) & 3;
  return (16 * wq + (lane & 7) + 8 * ((lane >> 3) & 1)) * 128 + (((lane >> 4) ^ (lane & 7)) << 4);
}
__device__ __forceinline__ void named_sync(int id, int n) { asm volatile("bar.sync %0, %1;" :: "r"(id), "r"(n) : "memory"); }
__device__ __forceinline__ void named_arrive(int id, int n) { asm volatile("bar.arrive %0, %1;" :: "r"(id), "r"(n) : "memory"); }
__device__ __forceinline__ uint32_t pack_bf16(float lo, float hi) {
  uint32_t r; asm("cvt.rn.bf16x2.f32 %0, %1, %2;" : "=r"(r) : "f"(hi), "f"(lo)); return r;
}
__device__ __forceinline__ float ex2(float x) { float y; asm("ex2.approx.ftz.f32 %0, %1;" : "=f"(y) : "f"(x)); return y; }
__device__ __forceinline__ void stsm4(uint32_t addr, uint32_t a, uint32_t b, uint32_t c, uint32_t d) {
  asm volatile("stmatrix.sync.aligned.m8n8.x4.shared.b16 [%0], {%1, %2, %3, %4};" :: "r"(addr), "r"(a), "r"(b), "r"(c), "r"(d) : "memory");
}
__device__ __forceinline__ void stsm4t(uint32_t addr, uint32_t a, uint32_t b, uint32_t c, uint32_t d) {
  asm volatile("stmatrix.sync.aligned.m8n8.x4.trans.shared.b16 [%0], {%1, %2, %3, %4};" :: "r"(addr), "r"(a), "r"(b), "r"(c), "r"(d) : "memory");
}
__device__ __forceinline__ uint64_t mk_desc(uint32_t addr, uint32_t lbo, uint32_t sbo) {
  return (uint64_t)(((addr & 0x3FFFF) >> 4) | ((lbo >> 4) << 16)) | ((uint64_t)((sbo >> 4) | (1u << 30)) << 32);
}
__device__ __forceinline__ uint64_t desc_k(uint32_t addr)  { return mk_desc(addr, 16, 1024); }
__device__ __forceinline__ uint64_t desc_mn(uint32_t addr) { return mk_desc(addr, 8192, 1024); }
__device__ __forceinline__ uint64_t desc_add(uint64_t d, uint32_t bytes) { return d + (bytes >> 4); }

__device__ __forceinline__ void wgmma_ss_n256_tb(float (&d)[128], uint64_t da, uint64_t db, int sd) {
  asm volatile("{\n.reg .pred p;\nsetp.ne.b32 p, %130, 0;\n"
    "wgmma.mma_async.sync.aligned.m64n256k16.f32.bf16.bf16 "
    "{%0, %1, %2, %3, %4, %5, %6, %7, %8, %9, %10, %11, %12, %13, %14, %15, "
    "%16, %17, %18, %19, %20, %21, %22, %23, %24, %25, %26, %27, %28, %29, %30, %31, "
    "%32, %33, %34, %35, %36, %37, %38, %39, %40, %41, %42, %43, %44, %45, %46, %47, "
    "%48, %49, %50, %51, %52, %53, %54, %55, %56, %57, %58, %59, %60, %61, %62, %63, "
    "%64, %65, %66, %67, %68, %69, %70, %71, %72, %73, %74, %75, %76, %77, %78, %79, "
    "%80, %81, %82, %83, %84, %85, %86, %87, %88, %89, %90, %91, %92, %93, %94, %95, "
    "%96, %97, %98, %99, %100, %101, %102, %103, %104, %105, %106, %107, %108, %109, %110, %111, "
    "%112, %113, %114, %115, %116, %117, %118, %119, %120, %121, %122, %123, %124, %125, %126, %127}, "
    "%128, %129, p, 1, 1, 0, 1;\n}"
    : "+f"(d[0]), "+f"(d[1]), "+f"(d[2]), "+f"(d[3]), "+f"(d[4]), "+f"(d[5]), "+f"(d[6]), "+f"(d[7]),
      "+f"(d[8]), "+f"(d[9]), "+f"(d[10]), "+f"(d[11]), "+f"(d[12]), "+f"(d[13]), "+f"(d[14]), "+f"(d[15]),
      "+f"(d[16]), "+f"(d[17]), "+f"(d[18]), "+f"(d[19]), "+f"(d[20]), "+f"(d[21]), "+f"(d[22]), "+f"(d[23]),
      "+f"(d[24]), "+f"(d[25]), "+f"(d[26]), "+f"(d[27]), "+f"(d[28]), "+f"(d[29]), "+f"(d[30]), "+f"(d[31]),
      "+f"(d[32]), "+f"(d[33]), "+f"(d[34]), "+f"(d[35]), "+f"(d[36]), "+f"(d[37]), "+f"(d[38]), "+f"(d[39]),
      "+f"(d[40]), "+f"(d[41]), "+f"(d[42]), "+f"(d[43]), "+f"(d[44]), "+f"(d[45]), "+f"(d[46]), "+f"(d[47]),
      "+f"(d[48]), "+f"(d[49]), "+f"(d[50]), "+f"(d[51]), "+f"(d[52]), "+f"(d[53]), "+f"(d[54]), "+f"(d[55]),
      "+f"(d[56]), "+f"(d[57]), "+f"(d[58]), "+f"(d[59]), "+f"(d[60]), "+f"(d[61]), "+f"(d[62]), "+f"(d[63]),
      "+f"(d[64]), "+f"(d[65]), "+f"(d[66]), "+f"(d[67]), "+f"(d[68]), "+f"(d[69]), "+f"(d[70]), "+f"(d[71]),
      "+f"(d[72]), "+f"(d[73]), "+f"(d[74]), "+f"(d[75]), "+f"(d[76]), "+f"(d[77]), "+f"(d[78]), "+f"(d[79]),
      "+f"(d[80]), "+f"(d[81]), "+f"(d[82]), "+f"(d[83]), "+f"(d[84]), "+f"(d[85]), "+f"(d[86]), "+f"(d[87]),
      "+f"(d[88]), "+f"(d[89]), "+f"(d[90]), "+f"(d[91]), "+f"(d[92]), "+f"(d[93]), "+f"(d[94]), "+f"(d[95]),
      "+f"(d[96]), "+f"(d[97]), "+f"(d[98]), "+f"(d[99]), "+f"(d[100]), "+f"(d[101]), "+f"(d[102]), "+f"(d[103]),
      "+f"(d[104]), "+f"(d[105]), "+f"(d[106]), "+f"(d[107]), "+f"(d[108]), "+f"(d[109]), "+f"(d[110]), "+f"(d[111]),
      "+f"(d[112]), "+f"(d[113]), "+f"(d[114]), "+f"(d[115]), "+f"(d[116]), "+f"(d[117]), "+f"(d[118]), "+f"(d[119]),
      "+f"(d[120]), "+f"(d[121]), "+f"(d[122]), "+f"(d[123]), "+f"(d[124]), "+f"(d[125]), "+f"(d[126]), "+f"(d[127])
    : "l"(da), "l"(db), "r"(sd));
}
__device__ __forceinline__ void wgmma_ss_n64(float (&d)[32], uint64_t da, uint64_t db, int sd) {
  asm volatile("{\n.reg .pred p;\nsetp.ne.b32 p, %34, 0;\n"
    "wgmma.mma_async.sync.aligned.m64n64k16.f32.bf16.bf16 "
    "{%0, %1, %2, %3, %4, %5, %6, %7, %8, %9, %10, %11, %12, %13, %14, %15, "
    "%16, %17, %18, %19, %20, %21, %22, %23, %24, %25, %26, %27, %28, %29, %30, %31}, "
    "%32, %33, p, 1, 1, 0, 0;\n}"
    : "+f"(d[0]), "+f"(d[1]), "+f"(d[2]), "+f"(d[3]), "+f"(d[4]), "+f"(d[5]), "+f"(d[6]), "+f"(d[7]),
      "+f"(d[8]), "+f"(d[9]), "+f"(d[10]), "+f"(d[11]), "+f"(d[12]), "+f"(d[13]), "+f"(d[14]), "+f"(d[15]),
      "+f"(d[16]), "+f"(d[17]), "+f"(d[18]), "+f"(d[19]), "+f"(d[20]), "+f"(d[21]), "+f"(d[22]), "+f"(d[23]),
      "+f"(d[24]), "+f"(d[25]), "+f"(d[26]), "+f"(d[27]), "+f"(d[28]), "+f"(d[29]), "+f"(d[30]), "+f"(d[31])
    : "l"(da), "l"(db), "r"(sd));
}
__device__ __forceinline__ void wgmma_ss_n64_tb(float (&d)[32], uint64_t da, uint64_t db, int sd) {
  asm volatile("{\n.reg .pred p;\nsetp.ne.b32 p, %34, 0;\n"
    "wgmma.mma_async.sync.aligned.m64n64k16.f32.bf16.bf16 "
    "{%0, %1, %2, %3, %4, %5, %6, %7, %8, %9, %10, %11, %12, %13, %14, %15, "
    "%16, %17, %18, %19, %20, %21, %22, %23, %24, %25, %26, %27, %28, %29, %30, %31}, "
    "%32, %33, p, 1, 1, 0, 1;\n}"
    : "+f"(d[0]), "+f"(d[1]), "+f"(d[2]), "+f"(d[3]), "+f"(d[4]), "+f"(d[5]), "+f"(d[6]), "+f"(d[7]),
      "+f"(d[8]), "+f"(d[9]), "+f"(d[10]), "+f"(d[11]), "+f"(d[12]), "+f"(d[13]), "+f"(d[14]), "+f"(d[15]),
      "+f"(d[16]), "+f"(d[17]), "+f"(d[18]), "+f"(d[19]), "+f"(d[20]), "+f"(d[21]), "+f"(d[22]), "+f"(d[23]),
      "+f"(d[24]), "+f"(d[25]), "+f"(d[26]), "+f"(d[27]), "+f"(d[28]), "+f"(d[29]), "+f"(d[30]), "+f"(d[31])
    : "l"(da), "l"(db), "r"(sd));
}
__device__ __forceinline__ void wgmma_rs_n256_tb(float (&d)[128], uint32_t a0, uint32_t a1, uint32_t a2, uint32_t a3, uint64_t db, int sd) {
  asm volatile("{\n.reg .pred p;\nsetp.ne.b32 p, %133, 0;\n"
    "wgmma.mma_async.sync.aligned.m64n256k16.f32.bf16.bf16 "
    "{%0, %1, %2, %3, %4, %5, %6, %7, %8, %9, %10, %11, %12, %13, %14, %15, "
    "%16, %17, %18, %19, %20, %21, %22, %23, %24, %25, %26, %27, %28, %29, %30, %31, "
    "%32, %33, %34, %35, %36, %37, %38, %39, %40, %41, %42, %43, %44, %45, %46, %47, "
    "%48, %49, %50, %51, %52, %53, %54, %55, %56, %57, %58, %59, %60, %61, %62, %63, "
    "%64, %65, %66, %67, %68, %69, %70, %71, %72, %73, %74, %75, %76, %77, %78, %79, "
    "%80, %81, %82, %83, %84, %85, %86, %87, %88, %89, %90, %91, %92, %93, %94, %95, "
    "%96, %97, %98, %99, %100, %101, %102, %103, %104, %105, %106, %107, %108, %109, %110, %111, "
    "%112, %113, %114, %115, %116, %117, %118, %119, %120, %121, %122, %123, %124, %125, %126, %127}, "
    "{%128, %129, %130, %131}, %132, p, 1, 1, 1;\n}"
    : "+f"(d[0]), "+f"(d[1]), "+f"(d[2]), "+f"(d[3]), "+f"(d[4]), "+f"(d[5]), "+f"(d[6]), "+f"(d[7]),
      "+f"(d[8]), "+f"(d[9]), "+f"(d[10]), "+f"(d[11]), "+f"(d[12]), "+f"(d[13]), "+f"(d[14]), "+f"(d[15]),
      "+f"(d[16]), "+f"(d[17]), "+f"(d[18]), "+f"(d[19]), "+f"(d[20]), "+f"(d[21]), "+f"(d[22]), "+f"(d[23]),
      "+f"(d[24]), "+f"(d[25]), "+f"(d[26]), "+f"(d[27]), "+f"(d[28]), "+f"(d[29]), "+f"(d[30]), "+f"(d[31]),
      "+f"(d[32]), "+f"(d[33]), "+f"(d[34]), "+f"(d[35]), "+f"(d[36]), "+f"(d[37]), "+f"(d[38]), "+f"(d[39]),
      "+f"(d[40]), "+f"(d[41]), "+f"(d[42]), "+f"(d[43]), "+f"(d[44]), "+f"(d[45]), "+f"(d[46]), "+f"(d[47]),
      "+f"(d[48]), "+f"(d[49]), "+f"(d[50]), "+f"(d[51]), "+f"(d[52]), "+f"(d[53]), "+f"(d[54]), "+f"(d[55]),
      "+f"(d[56]), "+f"(d[57]), "+f"(d[58]), "+f"(d[59]), "+f"(d[60]), "+f"(d[61]), "+f"(d[62]), "+f"(d[63]),
      "+f"(d[64]), "+f"(d[65]), "+f"(d[66]), "+f"(d[67]), "+f"(d[68]), "+f"(d[69]), "+f"(d[70]), "+f"(d[71]),
      "+f"(d[72]), "+f"(d[73]), "+f"(d[74]), "+f"(d[75]), "+f"(d[76]), "+f"(d[77]), "+f"(d[78]), "+f"(d[79]),
      "+f"(d[80]), "+f"(d[81]), "+f"(d[82]), "+f"(d[83]), "+f"(d[84]), "+f"(d[85]), "+f"(d[86]), "+f"(d[87]),
      "+f"(d[88]), "+f"(d[89]), "+f"(d[90]), "+f"(d[91]), "+f"(d[92]), "+f"(d[93]), "+f"(d[94]), "+f"(d[95]),
      "+f"(d[96]), "+f"(d[97]), "+f"(d[98]), "+f"(d[99]), "+f"(d[100]), "+f"(d[101]), "+f"(d[102]), "+f"(d[103]),
      "+f"(d[104]), "+f"(d[105]), "+f"(d[106]), "+f"(d[107]), "+f"(d[108]), "+f"(d[109]), "+f"(d[110]), "+f"(d[111]),
      "+f"(d[112]), "+f"(d[113]), "+f"(d[114]), "+f"(d[115]), "+f"(d[116]), "+f"(d[117]), "+f"(d[118]), "+f"(d[119]),
      "+f"(d[120]), "+f"(d[121]), "+f"(d[122]), "+f"(d[123]), "+f"(d[124]), "+f"(d[125]), "+f"(d[126]), "+f"(d[127])
    : "r"(a0), "r"(a1), "r"(a2), "r"(a3), "l"(db), "r"(sd));
}
__device__ __forceinline__ void wgmma_rs_n64_tb(float (&d)[32], uint32_t a0, uint32_t a1, uint32_t a2, uint32_t a3, uint64_t db, int sd) {
  asm volatile("{\n.reg .pred p;\nsetp.ne.b32 p, %37, 0;\n"
    "wgmma.mma_async.sync.aligned.m64n64k16.f32.bf16.bf16 "
    "{%0, %1, %2, %3, %4, %5, %6, %7, %8, %9, %10, %11, %12, %13, %14, %15, "
    "%16, %17, %18, %19, %20, %21, %22, %23, %24, %25, %26, %27, %28, %29, %30, %31}, "
    "{%32, %33, %34, %35}, %36, p, 1, 1, 1;\n}"
    : "+f"(d[0]), "+f"(d[1]), "+f"(d[2]), "+f"(d[3]), "+f"(d[4]), "+f"(d[5]), "+f"(d[6]), "+f"(d[7]),
      "+f"(d[8]), "+f"(d[9]), "+f"(d[10]), "+f"(d[11]), "+f"(d[12]), "+f"(d[13]), "+f"(d[14]), "+f"(d[15]),
      "+f"(d[16]), "+f"(d[17]), "+f"(d[18]), "+f"(d[19]), "+f"(d[20]), "+f"(d[21]), "+f"(d[22]), "+f"(d[23]),
      "+f"(d[24]), "+f"(d[25]), "+f"(d[26]), "+f"(d[27]), "+f"(d[28]), "+f"(d[29]), "+f"(d[30]), "+f"(d[31])
    : "r"(a0), "r"(a1), "r"(a2), "r"(a3), "l"(db), "r"(sd));
}
__device__ __forceinline__ void wgmma_rs_n64(float (&d)[32], uint32_t a0, uint32_t a1, uint32_t a2, uint32_t a3, uint64_t db, int sd) {
  asm volatile("{\n.reg .pred p;\nsetp.ne.b32 p, %37, 0;\n"
    "wgmma.mma_async.sync.aligned.m64n64k16.f32.bf16.bf16 "
    "{%0, %1, %2, %3, %4, %5, %6, %7, %8, %9, %10, %11, %12, %13, %14, %15, "
    "%16, %17, %18, %19, %20, %21, %22, %23, %24, %25, %26, %27, %28, %29, %30, %31}, "
    "{%32, %33, %34, %35}, %36, p, 1, 1, 0;\n}"
    : "+f"(d[0]), "+f"(d[1]), "+f"(d[2]), "+f"(d[3]), "+f"(d[4]), "+f"(d[5]), "+f"(d[6]), "+f"(d[7]),
      "+f"(d[8]), "+f"(d[9]), "+f"(d[10]), "+f"(d[11]), "+f"(d[12]), "+f"(d[13]), "+f"(d[14]), "+f"(d[15]),
      "+f"(d[16]), "+f"(d[17]), "+f"(d[18]), "+f"(d[19]), "+f"(d[20]), "+f"(d[21]), "+f"(d[22]), "+f"(d[23]),
      "+f"(d[24]), "+f"(d[25]), "+f"(d[26]), "+f"(d[27]), "+f"(d[28]), "+f"(d[29]), "+f"(d[30]), "+f"(d[31])
    : "r"(a0), "r"(a1), "r"(a2), "r"(a3), "l"(db), "r"(sd));
}

__device__ __forceinline__ uint4 lds16(uint32_t a) {
  uint4 v; asm volatile("ld.shared.v4.u32 {%0, %1, %2, %3}, [%4];" : "=r"(v.x), "=r"(v.y), "=r"(v.z), "=r"(v.w) : "r"(a) : "memory"); return v;
}
__device__ __forceinline__ void sts16(uint32_t a, uint32_t x, uint32_t y, uint32_t z, uint32_t w) {
  asm volatile("st.shared.v4.u32 [%0], {%1, %2, %3, %4};" :: "r"(a), "r"(x), "r"(y), "r"(z), "r"(w) : "memory");
}
__device__ __forceinline__ uint32_t lds4(uint32_t a) { uint32_t v; asm volatile("ld.shared.u32 %0, [%1];" : "=r"(v) : "r"(a) : "memory"); return v; }
__device__ __forceinline__ uint32_t lds4v(uint32_t a) { uint32_t v; asm volatile("ld.volatile.shared.u32 %0, [%1];" : "=r"(v) : "r"(a) : "memory"); return v; }
__device__ __forceinline__ uint32_t bmul(uint32_t a, uint32_t b) { uint32_t r; asm("mul.rn.bf16x2 %0, %1, %2;" : "=r"(r) : "r"(a), "r"(b)); return r; }
__device__ __forceinline__ uint32_t badd(uint32_t a, uint32_t b) { uint32_t r; asm("add.rn.bf16x2 %0, %1, %2;" : "=r"(r) : "r"(a), "r"(b)); return r; }

__device__ __forceinline__ uint32_t add_skip(uint32_t y, uint32_t x, uint32_t d) { return badd(y, bmul(x, d)); }
__device__ __forceinline__ void ldsm4(uint32_t (&r)[4], uint32_t a) {
  asm volatile("ldmatrix.sync.aligned.m8n8.x4.shared.b16 {%0, %1, %2, %3}, [%4];" : "=r"(r[0]), "=r"(r[1]), "=r"(r[2]), "=r"(r[3]) : "r"(a) : "memory");
}
__device__ __forceinline__ void ldsm4t(uint32_t (&r)[4], uint32_t a) {
  asm volatile("ldmatrix.sync.aligned.m8n8.x4.trans.shared.b16 {%0, %1, %2, %3}, [%4];" : "=r"(r[0]), "=r"(r[1]), "=r"(r[2]), "=r"(r[3]) : "r"(a) : "memory");
}
__device__ __forceinline__ uint32_t transpose8(uint32_t a) { uint32_t d; asm volatile("movmatrix.sync.aligned.m8n8.trans.b16 %0, %1;" : "=r"(d) : "r"(a)); return d; }

__device__ __forceinline__ void mma16816(float (&d)[4], const uint32_t (&a)[4], uint32_t b0, uint32_t b1) {
  asm volatile("mma.sync.aligned.m16n8k16.row.col.f32.bf16.bf16.f32 {%0, %1, %2, %3}, {%4, %5, %6, %7}, {%8, %9}, {%0, %1, %2, %3};"
               : "+f"(d[0]), "+f"(d[1]), "+f"(d[2]), "+f"(d[3]) : "r"(a[0]), "r"(a[1]), "r"(a[2]), "r"(a[3]), "r"(b0), "r"(b1));
}

#define STG_K1 2
#define STG_K2 10
#define STG_Q1 1
#define STG_Q2 5
#define PACE_A 400
#define PACE_B 100
#define PF_QA 55
#define PF_CV 64
#define PF_X 1
#define Q_PRE 2
#define O_PRE 12
#define PACE_C 100
#define PF_D 2
#define PF_WO 4
#define ARRIVE_KK 12
#define SIDE_DELAY_NS 2000
#define EARLY_LD 3
#define HI_ORDER 9
constexpr int PP_BAR = 3;
template <int V> struct Int { static constexpr int value = V; };
struct Ring {
  uint32_t slot, phase;
  __device__ __forceinline__ void next() { if (++slot == NSLOT) { slot = 0; phase ^= 1; } }
};
__device__ __forceinline__ uint32_t bar_addr(uint32_t sb, uint32_t i) { return sb + BARS + 8 * i; }
__device__ __forceinline__ uint32_t q_region(uint32_t sb, int w) { return sb + QREG + (w ^ 1) * 32768; }

struct Role { int h, j; };
__device__ __forceinline__ Role get_role() {
  int cta; asm volatile("mov.u32 %0, %%ctaid.x;" : "=r"(cta));
  const int c = cta >> 1;
  int h, u;
  const int a = c - 4, b = c - 36, q = (b * 37) >> 8;
  h = a < 0 ? 8 : b < 0 ? a & 7 : 9 + b - 7 * q;
  u = a < 0 ? c : b < 0 ? a >> 3 : q;
  return Role{h, 2 * u + (cta & 1)};
}
__device__ __forceinline__ int fresh_warp() { return __shfl_sync(0xffffffffu, fresh_tid() >> 5, 0); }

__device__ __forceinline__ int q_tile(int h, int j, int which) { return ((h < 8) == (which == 0)) ? 15 - j : j; }

__device__ __forceinline__ int o_chunk(int h, int c) { const int x = c + (h & 7); return x % 7; }

__device__ __forceinline__ int kv_block(int j, int t) { return j + 8 * ((HI_ORDER >> t) & 1); }
__device__ __forceinline__ int kv_tile(int v, int h, int tile) { return (v * NH + h) * 32 + tile; }

__device__ __forceinline__ void ring_acquire(uint32_t sb, Ring& r, uint32_t bytes) {
  mbar_wait(bar_addr(sb, B_RG_EMPTY + r.slot), r.phase ^ 1);
  mbar_expect_tx(bar_addr(sb, B_RG_FULL + r.slot), bytes);
}
__device__ __forceinline__ void producer_main(const Params& p, uint32_t sb) {
  const Role ro = get_role();
  const int h = ro.h, j = ro.j;
  for (int it = EARLY_LD; it < 71; it++) {
    const int t = it >> 4, k = it & 15, s = it & 3;
    mbar_wait(bar_addr(sb, B_P1_EMPTY + s), ((it >> 2) & 1) ^ 1);
    const uint32_t full = bar_addr(sb, B_P1_FULL + s), dst = sb + s * P1_STAGE;
    mbar_expect_tx(full, P1_STAGE);
    if (t < 4) {
      tma_ld2(dst, &p.ckv, full, k * 64, kv_block(j, t) * 128);
      tma_ld3(dst + 16384, (t >> 1) ? &p.wuv : &p.wuk, full, 0, k * 64, h * 4);
    } else {
      tma_ld2(dst, &p.x, full, k * 64, q_tile(h, j, 0) * 128);
      tma_ld3(dst + 16384, &p.wq, full, 0, k * 64, h * 4);
    }
    {
      const int nx = it + PF_D, tn = nx >> 4, kn = nx & 15;
      if (tn == 0 || tn == 2) tma_pf2(tn ? &p.wvp : &p.wkp, h * HD, kn * 64 + j * 8);
      if (tn < 4 && tn != 2 && !(kn & 1)) tma_pf2(&p.ckp, kn * 64, kv_block(j, tn) * 128 + h * 8);
    }
    if (it >= PF_QA && it < PF_QA + 14) {
      const int i = it - PF_QA;
      if (!(i & 1)) tma_pf2(&p.xp, i * 32, q_tile(h, j, 0) * 128 + (h & 7) * 16);
      tma_pf2(&p.wqp, h * HD, (i * 8 + j) * 4);
    }
    if (it >= PF_CV && it < PF_CV + 3) {
      mbar_wait(bar_addr(sb, B_XS), 0);
      tma_pf2(&p.xs3, 0, (h * 8 + j) * CV_LINES + (it - PF_CV) * (CV_LINES / 3));
    }
  }
  mbar_wait(bar_addr(sb, B_P1_EMPTY + 3), 0);
  mbar_wait(bar_addr(sb, B_XS), 0);
  mbar_expect_tx(bar_addr(sb, B_RG_FULL + 4), CV_BYTES);
  for (int i = 0; i < 3; i++) tma_ld2(sb + CV_X + i * (CV_BYTES / 3), &p.xs3, bar_addr(sb, B_RG_FULL + 4), 0, (h * 8 + j) * CV_LINES + i * (CV_LINES / 3));
  Ring r{0, 1};
  auto prefetch_q = [&](int kc, int qt) {
    if (PF_X && kc >= 0 && kc < 7) tma_pf2(&p.x, kc * 64, qt * 128);
  };
  auto prefetch_wo = [&](int i) {
    if (PF_WO && i >= 0 && i < 14 && !(i & 1)) tma_pf2(&p.wop, o_chunk(h, i >> 1) * 64, h * HD + j * 32);
  };
  mbar_wait(bar_addr(sb, B_KV), 0);
  for (int which = 0; which < 2; which++) {
    const int qt = q_tile(h, j, which);
    if (which == 1) {
      uint32_t xdst = 0;
      for (int kc = 0; kc < 7; kc++) {
        ring_acquire(sb, r, P1_STAGE);
        const uint32_t full = bar_addr(sb, B_RG_FULL + r.slot);
        tma_ld3(sb + r.slot * SLOT, &p.wq, full, 0, kc * 64, h * 4);
        r.next();
        if (kc == 0 || (kc & 1)) {
          mbar_wait(bar_addr(sb, B_RG_EMPTY + r.slot), r.phase ^ 1);
          mbar_arrive(bar_addr(sb, B_RG_FULL + r.slot));
          xdst = sb + r.slot * SLOT;
          r.next();
        } else xdst += 16384;
        tma_ld2(xdst, &p.x, full, kc * 64, qt * 128);
        prefetch_q(kc + PF_X, qt);
      }
    }
    const int n = 2 * qt + 2;
    for (int f = 0; f < 2 * n; f++) {
      if (which == 0) prefetch_q(f - 2 * n + PF_X, 15 - qt); else prefetch_wo(f - 2 * n + PF_WO);
      const bool isK = (f == 0) || ((f & 1) && f < 2 * n - 1);
      const int i = isK ? (f + 1) >> 1 : (f == 2 * n - 1 ? n - 1 : (f >> 1) - 1);
      const int tile = which ? n - 1 - i : i;
      if (!isK) mbar_wait(bar_addr(sb, B_KV + 1 + ((tile >> 4) ^ ((HI_ORDER >> 2) & 1))), 0);
      if (which == 0 && f < 2) mbar_wait(bar_addr(sb, B_P1_EMPTY + f), 1);
      ring_acquire(sb, r, 32768);
      tma_ld2(sb + r.slot * SLOT, &p.tl, bar_addr(sb, B_RG_FULL + r.slot), 0, kv_tile(!isK, h, tile) * 256);
      r.next();
    }
  }
  for (int i = 0; i < 14; i++) {
    ring_acquire(sb, r, 32768);
    tma_ld2(sb + r.slot * SLOT, &p.wo, bar_addr(sb, B_RG_FULL + r.slot), o_chunk(h, i >> 1) * 64, ((i & 1) ? h ^ 8 : h) * HD);
    prefetch_wo(i + PF_WO);
    r.next();
  }
}

__device__ __forceinline__ void storer_main(const Params& p, uint32_t sb) {
  const Role ro = get_role();
  const int h = ro.h, j = ro.j, w = fresh_warp() - 1;
  const uint32_t full = bar_addr(sb, B_ST_FULL + w), empty = bar_addr(sb, B_ST_EMPTY + w);
  if ((threadIdx.x & 31) != 0) return;
  for (int job = 0; job < 8; job++) {
    const int t = job >> 1;
    const int line = kv_tile(t >> 1, h, 2 * kv_block(j, t) + w) * 256 + (job & 1) * 128;
    mbar_wait_nap(full, job & 1);
    for (int i = 0; i < 8; i++) {
      if (i) __nanosleep(job < 6 ? PACE_A : PACE_B);
      tma_st2(&p.ts, sb + P1_STG + w * 16384 + i * 2048, 0, line + i * 16);
    }
    bulk_commit();
    bulk_wait_read();
    mbar_arrive(empty);
    if (job >= 3 && (job & 1)) { bulk_wait_all(); flag_signal(&g_flags.kv_ready[3 * h + t - 1].v); }
  }
  const int cta = h * 8 + j, qt = q_tile(h, j, 1);
  const uint32_t qreg = q_region(sb, w);
  {
    mbar_wait_nap(bar_addr(sb, B_CTXS + 4 * w), 0);
    for (int b = 0; b < 4; b++) {
      mbar_wait(bar_addr(sb, B_CTXS + 4 * w + b), 0);
      for (int i = 0; i < 4; i++) {
        tma_st2(&p.ts, qreg + b * 8192 + i * 2048, 0, (CTX_TILE0 + cta * 2 + w) * 256 + b * 64 + i * 16);
        __nanosleep(PACE_C);
      }
      bulk_commit();
    }
    bulk_wait_read();
    mbar_arrive(empty);
    bulk_wait_all();
    mbar_arrive(bar_addr(sb, B_CTXD));
  }
  {
    const int wx = w ^ 1;
    mbar_wait_nap(bar_addr(sb, B_CTXD + 1), 0);
    mbar_wait_nap(bar_addr(sb, B_QFREE + w), 0);
    mbar_expect_tx(bar_addr(sb, B_CTXF + w), 32768);
    tma_ld2(qreg, &p.tl, bar_addr(sb, B_CTXF + w), 0, (CTX_TILE0 + (cta ^ 64) * 2 + wx) * 256);
    for (int ch = 0; ch < 7; ch++) {
      const int b = ch & 1;
      mbar_wait(bar_addr(sb, B_S2_FULL + w * 2 + b), (ch >> 1) & 1);
      tma_red2(&p.part, qreg + b * 8192, DA + o_chunk(h, ch) * 64, qt * 128 + wx * 64);
      bulk_commit();
      if (ch == 0 && w == 1) mbar_arrive(bar_addr(sb, B_GFREE));
      bulk_wait_read();
      mbar_arrive(bar_addr(sb, B_S2_EMPTY + w * 2 + b));
    }
  }
}

template <int OFF, int NB, int NREG>
__device__ __forceinline__ void store_blocks(uint32_t base, uint32_t lanebase, const uint32_t (&pk)[NREG]) {
#pragma unroll
  for (int J = 0; J < NB * 8; J += 2) {
    const uint32_t a = base + (J >> 3) * 8192 + (lanebase ^ ((J & 7) << 4));
    stsm4(a, pk[OFF + 2 * J], pk[OFF + 2 * J + 1], pk[OFF + 2 * J + 2], pk[OFF + 2 * J + 3]);
  }
}
__device__ __forceinline__ void warp_arrive(uint32_t bar, int lane) { __syncwarp(); if (lane == 0) mbar_arrive(bar); }
__device__ __forceinline__ void release(uint32_t bar, int lane) { lane0_arrive(bar, 1, lane); }

template <int W> __device__ __forceinline__ constexpr int cv_tile(int u) { return 2 * u + ((u ^ W) & 1); }
__device__ __forceinline__ uint32_t cv_x_lane(uint32_t lane) { return (16 + (lane & 15) - (lane >> 4)) * 16; }
__device__ __forceinline__ uint32_t cv_h_lane(uint32_t lane, uint32_t hE, uint32_t hO) {
  const uint32_t g = lane >> 2, c = lane & 3;
  return (g & 1) ? hO + (15 + 2 * c - g) * 2 : hE + (16 + 2 * c - g) * 2;
}
template <int W>
__device__ __forceinline__ void conv_mma(float (&ca)[8][4], uint32_t xa, uint32_t ha, uint32_t sb, uint32_t lb, const uint32_t (&pk)[64], uint32_t one) {
  constexpr int N = 16 - W;
  uint32_t fx[N][4], fh[N][2];
  auto ld_h = [&](int i, int rr) { fh[i][0] = lds4(ha + i * 256 + rr * 128); fh[i][1] = lds4(ha + i * 256 + rr * 128 + 16); };
  uint32_t c1 = 0, c3 = 0;
  ldsm4(fx[0], xa);
#pragma unroll
  for (int u = 0; u < 8; u++) ld_h(cv_tile<W>(u), 0);
  ldsm4(fx[1], xa + 256);
#pragma unroll
  for (int u = 0; u < 8; u++) if (cv_tile<W ^ 1>(u) < N) ld_h(cv_tile<W ^ 1>(u), 0);
#pragma unroll
  for (int i = 2; i < N; i++) ldsm4(fx[i], xa + i * 256);
#pragma unroll
  for (int sx = 0; sx < N; sx++) {
#pragma unroll
    for (int u = 0; u < 8; u++) {
      const int jj = cv_tile<W>(u) - sx;
      if (jj >= 0) mma16816(ca[u], fx[sx], fh[jj < 0 ? 0 : jj][0], fh[jj < 0 ? 0 : jj][1]);
    }
    {
      const uint32_t t1 = fx[sx][1], t3 = fx[sx][3];
      fx[sx][1] = fx[sx][0] * one; fx[sx][3] = fx[sx][2] ^ (one - 1); fx[sx][0] = c1 * one; fx[sx][2] = c3 ^ (one - 1);
      c1 = t1; c3 = t3;
    }
    ld_h(N - 1 - sx, 1);
  }
  mbar_wait(bar_addr(sb, B_P1_EMPTY + 2), 1);
  if (W == 0) { mbar_wait(bar_addr(sb, B_ST_EMPTY), 1); mbar_wait(bar_addr(sb, B_ST_EMPTY + 1), 1); }
#pragma unroll
  for (int jj = 15; jj >= 0; jj--) {
    if (W == 0) stsm4(q_region(sb, W) + (jj >> 2) * 8192 + (lb ^ ((jj & 3) << 5)), pk[4 * jj], pk[4 * jj + 1], pk[4 * jj + 2], pk[4 * jj + 3]);
#pragma unroll
    for (int u = 0; u < 8; u++) {
      const int sx = cv_tile<W>(u) - jj;
      if (sx >= 0) mma16816(ca[u], fx[sx < 0 ? 0 : sx], fh[jj < N ? jj : 0][0], fh[jj < N ? jj : 0][1]);
    }
  }
}

__device__ __forceinline__ void consumer_main(const Params& p, uint32_t sb, uint8_t* xs_base, uint32_t one) {
  const int lane = fresh_tid() & 31, w = (fresh_warp() >> 2) - 1;
  const uint32_t lb = lane_base16();
  int qt, cc;
  { const Role ro = get_role(); qt = q_tile(ro.h, ro.j, 0); cc = ro.h * 8 + ro.j; }
  const uint32_t st_full = bar_addr(sb, B_ST_FULL + w), st_empty = bar_addr(sb, B_ST_EMPTY + w);
  const uint32_t stg = sb + P1_STG + w * 16384;

  auto turn_begin = [&]() { named_sync(PP_BAR + w, 256); };
  auto turn_end = [&]() { named_arrive(PP_BAR + (w ^ 1), 256); };
  float acc[128];
#pragma unroll
  for (int i = 0; i < 128; i++) acc[i] = 0.f;
  uint32_t pk[64];
#pragma unroll
  for (int i = 0; i < 64; i++) pk[i] = 0;
  if (fresh_warp() != 4) named_sync(0, NTHREADS);
  const uint32_t qreg = q_region(sb, w);
  for (int t = 0; t < 5; t++) {
    const int nk = t < 4 ? 16 : 7;
#pragma unroll 1
    for (int k = 0; k < nk; k++) {
      const int it = t * 16 + k, s = k & 3;
      if (it == 0) { mbar_wait(bar_addr(sb, B_P1_FULL), 0); turn_begin(); }
      const uint64_t da = desc_k(sb + s * P1_STAGE + w * 8192), db = desc_mn(sb + s * P1_STAGE + 16384);
      wg_fence();
#pragma unroll
      for (int kk = 0; kk < 4; kk++) wgmma_ss_n256_tb(acc, desc_add(da, kk * 32), desc_add(db, kk * 2048), (k | kk) != 0);
      wg_commit();
      turn_end();
      wg_wait<1>();
      if (k > 0) release(bar_addr(sb, B_P1_EMPTY + ((k - 1) & 3)), lane);
      const int k1 = t < 4 ? STG_K1 : STG_Q1, k2 = t < 4 ? STG_K2 : STG_Q2;
      if (t > 0 && (k == k1 || k == k2)) {
        const int job = 2 * (t - 1) + (k != k1);
        mbar_wait(job > 0 ? st_empty : bar_addr(sb, B_SIDE + 1), job > 0 ? (job - 1) & 1 : 0);
        if (k == k1) store_blocks<0, 2>(stg, lb, pk); else store_blocks<32, 2>(stg, lb, pk);
      }
      if (t > 0 && (k == k1 + 1 || k == k2 + 1)) { fence_async_smem(); warp_arrive(st_full, lane); }
      if (it < 70) { mbar_wait(bar_addr(sb, B_P1_FULL + ((k + 1) & 3)), ((it + 1) >> 2) & 1); turn_begin(); }
      else mbar_wait(bar_addr(sb, B_RG_FULL + 4), 0);
    }
    wg_wait<0>();
    reg_fence(acc);
    release(bar_addr(sb, B_P1_EMPTY + ((nk - 1) & 3)), lane);
#pragma unroll
    for (int i = 0; i < 64; i++) pk[i] = pack_bf16(acc[2 * i], acc[2 * i + 1]);
  }
  {
    const uint32_t wq = lb >> 11, ln = lane, cx = sb + CV_X;
    float ca[8][4];
#pragma unroll
    for (int i = 0; i < 8; i++) { ca[i][0] = 0.f; ca[i][1] = 0.f; ca[i][2] = 0.f; ca[i][3] = 0.f; }
    const uint32_t xa = cx + CV_XO + cv_x_lane(ln) - wq * 32, ha = cv_h_lane(ln, cx, cx + CV_HCOPY) + wq * 32;
    if (w) conv_mma<1>(ca, xa, ha, sb, lb, pk, one); else conv_mma<0>(ca, xa, ha, sb, lb, pk, one);
    const uint32_t ex = sb + CV_R + w * 16384 + ln * 16;
#pragma unroll
    for (int u = 0; u < 8; u++)
      sts16(ex + (wq * 8 + u) * 512, __float_as_uint(ca[u][0]), __float_as_uint(ca[u][1]), __float_as_uint(ca[u][2]), __float_as_uint(ca[u][3]));
  }
  auto conv_finish = [&]() {
    const uint32_t wq = lb >> 11, cx = sb + CV_X, ex = sb + CV_R + w * 16384 + lane * 16;
    uint8_t* gz = xs_base + (size_t)cc * CV_BYTES;
    const uint32_t Dd = lds4(cx + CV_D);
#pragma unroll
    for (int e = 0; e < 2; e++) {
      const uint32_t u = 2 * wq + e, nt = 2 * u + ((e ^ w) & 1);
      float y[4] = {0.f, 0.f, 0.f, 0.f};
#pragma unroll
      for (int v = 0; v < 4; v++) {
        const uint4 t = lds16(ex + (v * 8 + u) * 512);
        y[0] += __uint_as_float(t.x); y[1] += __uint_as_float(t.y); y[2] += __uint_as_float(t.z); y[3] += __uint_as_float(t.w);
      }
      const uint32_t o = CV_XO + (16 + 16 * nt) * 16 + lane * 4;
      *reinterpret_cast<uint32_t*>(gz + o)       = badd(pack_bf16(y[0], y[1]), bmul(lds4(cx + o), Dd));
      *reinterpret_cast<uint32_t*>(gz + o + 128) = badd(pack_bf16(y[2], y[3]), bmul(lds4(cx + o + 128), Dd));
    }
    __syncwarp();
    release(bar_addr(sb, B_RG_EMPTY + 3), lane);
    release(bar_addr(sb, B_RG_EMPTY + 4), lane);
    if (lane == 0) mbar_arrive(bar_addr(sb, B_CONV));
  };
  Ring r{0, 1};
  auto take = [&]() { const uint32_t sl = r.slot; mbar_wait(bar_addr(sb, B_RG_FULL + sl), r.phase); r.next(); return sl; };
  constexpr float SC = 0.0625f * 1.4426950408889634f;
  uint32_t ws;
#pragma unroll 1
  for (int which = 0;; which++) {
    float s[32];
#pragma unroll
    for (int i = 0; i < 32; i++) s[i] = 0.f;
    uint32_t pa[16];
    float b0, b1, l0, l1;
    const uint64_t dq = desc_k(qreg);
    uint64_t dk = 0, dqq = 0, dv = 0;
    auto prep_qk = [&](uint32_t kaddr) { dk = desc_k(kaddr); dqq = dq + (kaddr >> 31); asm volatile("" : "+l"(dk), "+l"(dqq)); };
    auto prep_pv = [&](uint32_t vaddr) { dv = desc_mn(vaddr); asm volatile("" : "+l"(dv)); };
    auto issue_qk = [&]() {
#pragma unroll
      for (int kk = 0; kk < 16; kk++)
        wgmma_ss_n64(s, desc_add(dqq, (kk >> 2) * 8192 + (kk & 3) * 32), desc_add(dk, (kk >> 2) * 8192 + (kk & 3) * 32), kk != 0);
    };
    auto issue_pv = [&](int accumulate) {
#pragma unroll
      for (int kk = 0; kk < 4; kk++)
        wgmma_rs_n256_tb(acc, pa[4 * kk], pa[4 * kk + 1], pa[4 * kk + 2], pa[4 * kk + 3], desc_add(dv, kk * 2048), accumulate | kk);
    };
    auto mask_diag = [&]() {
      const int d = (int)((lb >> 11) << 4) + (lane >> 2) - 2 * (lane & 3);
#pragma unroll
      for (int jj = 0; jj < 8; jj++) {
        if (8 * jj > d)     s[4 * jj]     = -INFINITY;
        if (8 * jj + 1 > d) s[4 * jj + 1] = -INFINITY;
        if (8 * jj - 8 > d) s[4 * jj + 2] = -INFINITY;
        if (8 * jj - 7 > d) s[4 * jj + 3] = -INFINITY;
      }
    };
    auto row_max = [&](float& x0, float& x1) {
      x0 = fmaxf(s[0], s[1]); x1 = fmaxf(s[2], s[3]);
#pragma unroll
      for (int jj = 1; jj < 8; jj++) {
        x0 = fmaxf(x0, fmaxf(s[4 * jj], s[4 * jj + 1]));
        x1 = fmaxf(x1, fmaxf(s[4 * jj + 2], s[4 * jj + 3]));
      }
      x0 = fmaxf(x0, __shfl_xor_sync(0xffffffffu, x0, 1));
      x1 = fmaxf(x1, __shfl_xor_sync(0xffffffffu, x1, 1));
      x0 = fmaxf(x0, __shfl_xor_sync(0xffffffffu, x0, 2));
      x1 = fmaxf(x1, __shfl_xor_sync(0xffffffffu, x1, 2));
    };
    auto exps = [&](uint32_t (&pp)[16], float& r0, float& r1) {
      float t0, t1, t2, t3;
#pragma unroll
      for (int jj = 0; jj < 8; jj++) {
        const float e0 = ex2(fmaf(s[4 * jj], SC, b0)), e1 = ex2(fmaf(s[4 * jj + 1], SC, b0));
        const float e2 = ex2(fmaf(s[4 * jj + 2], SC, b1)), e3 = ex2(fmaf(s[4 * jj + 3], SC, b1));
        if (jj == 0) { t0 = e0; t1 = e1; t2 = e2; t3 = e3; } else { t0 += e0; t1 += e1; t2 += e2; t3 += e3; }
        pp[2 * jj] = pack_bf16(e0, e1); pp[2 * jj + 1] = pack_bf16(e2, e3);
      }
      r0 = t0 + t1; r1 = t2 + t3;
    };

    const bool up = w == which;
    const int n = 2 * qt + 2, nw = n - up;
    int fd = which ? 0 : 2 * n - 1;
    const int dir = which ? 1 : -1;
    auto skip = [&]() { r.next(); fd += dir; };
    auto give = [&](uint32_t sl, int d) {
      lane0_arrive(bar_addr(sb, B_RG_EMPTY + sl), (d & ~2) == 0 ? 2 : 1, lane);
    };
    if (which && up) skip();
    uint32_t ks = take();
    prep_qk(sb + ks * SLOT);
    turn_begin();
    wg_fence();
#pragma unroll
    for (int kk = 0; kk < 16; kk++)
      wgmma_rs_n64(s, pk[4 * kk], pk[4 * kk + 1], pk[4 * kk + 2], pk[4 * kk + 3], desc_add(dk, (kk >> 2) * 8192 + (kk & 3) * 32), kk != 0);
    wg_commit();
    turn_end();
    if (!which && up) conv_finish();
    if (which) mbar_wait(st_empty, 0);
    if (!up) store_blocks<0, Q_PRE>(qreg, lb, pk);
    wg_wait<0>();
    reg_fence(s);
    reg_fence(pk);
    give(ks, fd);
    fd += dir;
    if (which && up) { skip(); store_blocks<0, 4>(qreg, lb, pk); }
    if (which || nw == 1) mask_diag();
    row_max(b0, b1);
    if (!up) store_blocks<16 * Q_PRE, 4 - Q_PRE>(qreg + Q_PRE * 8192, lb, pk);
    b0 *= -SC; b1 *= -SC;
#pragma unroll
    for (int i = 0; i < 128; i++) acc[i] = 0.f;
    exps(pa, l0, l1);
    if (!which && !up) conv_finish();
    if (which && nw == 1) { fence_async_smem(); warp_arrive(bar_addr(sb, B_QFREE + w), lane); }
#pragma unroll 1
    for (int jj = 1; jj < nw; jj++) {
      ks = take();
      const uint32_t vs = take();
      if (jj == 1) fence_async_smem();
#pragma unroll
      for (int i = 0; i < 32; i++) s[i] = 0.f;
      prep_qk(sb + ks * SLOT);
      prep_pv(sb + vs * SLOT);
      turn_begin();
      wg_fence();
      issue_qk();
      wg_commit();
      issue_pv(1);
      wg_commit();
      turn_end();
      wg_wait<1>();
      reg_fence(s);
      give(ks, fd);
      if (jj == nw - 1) {
        if (!which) mask_diag();
        else if (lane == 0) mbar_arrive(bar_addr(sb, B_QFREE + w));
      }
      uint32_t pn[16];
      float t0, t1, a0 = 1.f, a1 = 1.f;
      exps(pn, t0, t1);
      const bool redo = __any_sync(0xffffffffu, !(t0 + t1 <= 0x1p30f));
      if (redo) {
        row_max(a0, a1);
        const float c0 = fminf(b0, -SC * a0), c1 = fminf(b1, -SC * a1);
        a0 = ex2(c0 - b0); a1 = ex2(c1 - b1);
        b0 = c0; b1 = c1;
        l0 *= a0; l1 *= a1;
        exps(pn, t0, t1);
      }
      l0 += t0; l1 += t1;
      wg_wait<0>();
      reg_fence(acc);
      reg_fence(pa);
      give(vs, fd + dir);
      fd += 2 * dir;
      if (redo) {
#pragma unroll
        for (int i = 0; i < 32; i++) { acc[4 * i] *= a0; acc[4 * i + 1] *= a0; acc[4 * i + 2] *= a1; acc[4 * i + 3] *= a1; }
      }
#pragma unroll
      for (int i = 0; i < 16; i++) pa[i] = (i & 1) ? pn[i] ^ (one - 1) : pn[i] * one;
    }
    if (!which && up) skip();
    const uint32_t vs = take();
    prep_pv(sb + vs * SLOT);
    turn_begin();
    wg_fence();
    issue_pv(1);
    wg_commit();
    turn_end();
    if (!which && up) r.next();
    ws = take();
    l0 += __shfl_xor_sync(0xffffffffu, l0, 1); l1 += __shfl_xor_sync(0xffffffffu, l1, 1);
    l0 += __shfl_xor_sync(0xffffffffu, l0, 2); l1 += __shfl_xor_sync(0xffffffffu, l1, 2);
    float i0, i1;
    asm volatile("rcp.approx.ftz.f32 %0, %1;" : "=f"(i0) : "f"(l0));
    asm volatile("rcp.approx.ftz.f32 %0, %1;" : "=f"(i1) : "f"(l1));
    if (one == 2) mbar_wait(st_empty, 0);
    wg_wait<0>();
    reg_fence(acc);
    reg_fence(pa);
    give(vs, fd);
#pragma unroll
    for (int i = 0; i < 32; i++) {
      pk[2 * i]     = pack_bf16(acc[4 * i] * i0, acc[4 * i + 1] * i0);
      pk[2 * i + 1] = pack_bf16(acc[4 * i + 2] * i1, acc[4 * i + 3] * i1);
    }
    if (which) break;
    uint32_t xs = r.slot, xaddr = sb + xs * SLOT + (w ^ 1) * 8192;
    r.next();
#pragma unroll 1
    for (int kc = 0;; kc++) {
      const uint64_t da = desc_k(xaddr), db = desc_mn(sb + ws * SLOT);
      turn_begin();
      wg_fence();
#pragma unroll
      for (int kk = 0; kk < 4; kk++) wgmma_ss_n256_tb(acc, desc_add(da, kk * 32), desc_add(db, kk * 2048), (kc | kk) != 0);
      wg_commit();
      turn_end();
      const int cb = kc;
      if (cb >= 1 && cb <= 4) { fence_async_smem(); warp_arrive(bar_addr(sb, B_CTXS + 4 * w + cb - 1), lane); }
      if ((unsigned)cb < 4) {
        if (cb & 2) { if (cb & 1) store_blocks<48, 1>(qreg + 24576, lb, pk); else store_blocks<32, 1>(qreg + 16384, lb, pk); }
        else        { if (cb & 1) store_blocks<16, 1>(qreg + 8192, lb, pk);  else store_blocks<0, 1>(qreg, lb, pk); }
      }
      wg_wait<0>();
      release(bar_addr(sb, B_RG_EMPTY + ws), lane);
      if (!(kc & 1)) release(bar_addr(sb, B_RG_EMPTY + xs), lane);
      if (kc == 6) break;
      ws = take();
      if (!(kc & 1)) { xs = r.slot; r.next(); xaddr = sb + xs * SLOT + (w ^ 1) * 8192; } else xaddr += 16384;
    }
    reg_fence(acc);
#pragma unroll
    for (int i = 0; i < 64; i++) pk[i] = pack_bf16(acc[2 * i], acc[2 * i + 1]);
    qt = 15 - qt;
  }

  {
    float oa[32], ob[32];
#pragma unroll
    for (int i = 0; i < 32; i++) { oa[i] = 0.f; ob[i] = 0.f; }
    auto stage_o = [&](float (&o)[32], int ch) {
      reg_fence(o);
      uint32_t q[16];
#pragma unroll
      for (int i = 0; i < 16; i++) q[i] = pack_bf16(o[2 * i], o[2 * i + 1]);
      if (ch >= 2) mbar_wait(bar_addr(sb, B_S2_EMPTY + w * 2 + (ch & 1)), ((ch >> 1) - 1) & 1);
      store_blocks<0, 1>(qreg + (ch & 1) * 8192, lb, q);
    };
    auto hand_over = [&](int ch) {
      fence_async_smem();
      warp_arrive(bar_addr(sb, B_S2_FULL + w * 2 + (ch & 1)), lane);
    };
    uint32_t pk2[64];
    uint32_t p2 = 0;
    auto chunk = [&](int ch, auto first, float (&o)[32], float (&oprev)[32]) {
      constexpr bool FIRST = decltype(first)::value;
      const uint32_t s1 = FIRST ? ws : take();
      const uint64_t d1 = desc_mn(sb + s1 * SLOT);
      turn_begin();
      wg_fence();
#pragma unroll
      for (int kk = 0; kk < 16; kk++) {
        wgmma_rs_n64_tb(o, pk[4 * kk], pk[4 * kk + 1], pk[4 * kk + 2], pk[4 * kk + 3], desc_add(d1, kk * 2048), kk != 0);
        if (kk == ARRIVE_KK) turn_end();
      }
      wg_commit();
      if constexpr (!FIRST) {
        wg_wait<1>();
        release(bar_addr(sb, B_RG_EMPTY + p2), lane);
        stage_o(oprev, ch - 1);
      } else {
        mbar_wait(bar_addr(sb, B_CTXF + w), 0);
#pragma unroll
        for (int kk = 0; kk < O_PRE; kk++) {
          uint32_t f[4];
          ldsm4(f, qreg + (kk >> 2) * 8192 + (lb ^ ((kk & 3) << 5)));
          pk2[4 * kk] = f[0]; pk2[4 * kk + 1] = f[1]; pk2[4 * kk + 2] = f[2]; pk2[4 * kk + 3] = f[3];
        }
      }
      const uint32_t s2 = take();
      const uint64_t d2 = desc_mn(sb + s2 * SLOT);
      turn_begin();
      wg_fence();
#pragma unroll
      for (int kk = 0; kk < 16; kk++) {
        if (FIRST && kk >= O_PRE) wgmma_ss_n64_tb(o, desc_add(desc_k(qreg), (kk >> 2) * 8192 + (kk & 3) * 32), desc_add(d2, kk * 2048), 1);
        else wgmma_rs_n64_tb(o, pk2[4 * kk], pk2[4 * kk + 1], pk2[4 * kk + 2], pk2[4 * kk + 3], desc_add(d2, kk * 2048), 1);
        if (kk == ARRIVE_KK && (ch < 6 || w == 1)) turn_end();
      }
      wg_commit();
      if (!FIRST) hand_over(ch - 1);
      if constexpr (FIRST) {
#pragma unroll
        for (int kk = O_PRE; kk < 16; kk++) {
          uint32_t f[4];
          ldsm4(f, qreg + (kk >> 2) * 8192 + (lb ^ ((kk & 3) << 5)));
          pk2[4 * kk] = f[0]; pk2[4 * kk + 1] = f[1]; pk2[4 * kk + 2] = f[2]; pk2[4 * kk + 3] = f[3];
        }
      }
      wg_wait<1>();
      release(bar_addr(sb, B_RG_EMPTY + s1), lane);
      p2 = s2;
    };
    chunk(0, Int<1>(), oa, ob);
#pragma unroll 1
    for (int ch = 1; ch < 7; ch += 2) { chunk(ch, Int<0>(), ob, oa); chunk(ch + 1, Int<0>(), oa, ob); }
    wg_wait<0>();
    reg_fence(pk);
    reg_fence(pk2);
    stage_o(oa, 6);
    hand_over(6);
  }

}

#define CONV_STAGGER_NS 1200
namespace ssm {
#define CONV_GROUPS (D_SPARE / 8 / NCONV)
constexpr int GROUPS = CONV_GROUPS;
constexpr uint32_t ZROWS = 16;
constexpr uint32_t CHAN = (ZROWS + 256 + 1) * 16;
constexpr uint32_t XBUF = 8 * CHAN;
constexpr uint32_t OFF_X = 0;
constexpr uint32_t HCOPY = 4160;
constexpr uint32_t OFF_H = 2 * XBUF;
constexpr uint32_t HWARP = 3 * HCOPY;
constexpr uint32_t IO_K = 128, IO_V = IO_K + 4096, IO_Q = IO_V + 4096, IOBUF = IO_Q + 4096;
constexpr uint32_t OFF_IO = (OFF_H + 8 * HWARP + 127) / 128 * 128;
constexpr uint32_t END = OFF_IO + 4 * IOBUF;
static_assert(IOBUF % 128 == 0 && OFF_H % 16 == 0, "TMA destination alignment");
static_assert(END <= BARS, "smem");
enum : uint32_t { B_XREADY = 0, B_ZDONE = 2, B_KV = 4, B_Q = 8, B_HRAW = 12, B_QLAST = 20 };
constexpr int CW_BAR = 4;

__device__ __forceinline__ int group_d0(int cidx, int grp) { return (grp * NCONV + cidx) * 8; }
__device__ __forceinline__ uint32_t x_lane(int lane) { return (lane & 7) * CHAN + (ZROWS + (lane >> 3)) * 16; }
__device__ __forceinline__ uint32_t t_lane(int lane) { return (uint32_t)(8 * (lane >> 3) + 7 - (lane & 7)) * 16; }
struct Taps { uint32_t s[4]; };
__device__ __forceinline__ Taps load_taps(const Params& p, int d0, int c) {
  const uint2 s0 = __ldg(reinterpret_cast<const uint2*>(p.a_shift + (d0 + 2 * c) * 4)), s1 = __ldg(reinterpret_cast<const uint2*>(p.a_shift + (d0 + 2 * c + 1) * 4));
  return Taps{{__byte_perm(s0.x, s1.x, 0x5410), __byte_perm(s0.x, s1.x, 0x7632), __byte_perm(s0.y, s1.y, 0x5410), __byte_perm(s0.y, s1.y, 0x7632)}};
}
__device__ __forceinline__ uint32_t short_conv(const Taps& t, uint32_t k0, uint32_t k1, uint32_t k2, uint32_t k3, uint32_t v) {
  return bmul(badd(badd(badd(bmul(k0, t.s[3]), bmul(k1, t.s[2])), bmul(k2, t.s[1])), bmul(k3, t.s[0])), v);
}
template <int U, class F>
__device__ __forceinline__ void x_chunk(const Taps& taps, uint32_t ka, F xa) {
#pragma unroll 1
  for (int u0 = 0; u0 < 8; u0 += U) {
    uint32_t k0[U][4], k1[U][4], k2[U][4], k3[U][4], vv[U][4];
#pragma unroll
    for (int u = 0; u < U; u++) {
      const uint32_t a = ka + (u0 + u) * 512;
      ldsm4(k0[u], a - 48); ldsm4(k1[u], a - 32); ldsm4(k2[u], a - 16); ldsm4(k3[u], a); ldsm4(vv[u], a + 4096);
    }
#pragma unroll
    for (int u = 0; u < U; u++)
      stsm4t(xa(u0 + u), short_conv(taps, k0[u][0], k1[u][0], k2[u][0], k3[u][0], vv[u][0]), short_conv(taps, k0[u][1], k1[u][1], k2[u][1], k3[u][1], vv[u][1]),
             short_conv(taps, k0[u][2], k1[u][2], k2[u][2], k3[u][2], vv[u][2]), short_conv(taps, k0[u][3], k1[u][3], k2[u][3], k3[u][3], vv[u][3]));
  }
}
template <int U>
__device__ __forceinline__ void shift_filter(uint32_t hE, uint32_t hO, int lane) {
#pragma unroll 1
  for (int i0 = 0; i0 < 8; i0 += U) {
    uint4 w[U]; uint32_t nx[U];
    const uint32_t o = 32 + lane * 16 + i0 * 512;
#pragma unroll
    for (int i = 0; i < U; i++) { w[i] = lds16(hE + o + i * 512); nx[i] = lds4(hE + o + i * 512 + 16); }
#pragma unroll
    for (int i = 0; i < U; i++)
      sts16(hO + o + i * 512, __byte_perm(w[i].x, w[i].y, 0x5432), __byte_perm(w[i].y, w[i].z, 0x5432), __byte_perm(w[i].z, w[i].w, 0x5432), __byte_perm(w[i].w, nx[i], 0x5432));
    if (o == 32) asm volatile("st.shared.u32 [%0], %1;" :: "r"(hO + 28), "r"(w[0].x << 16) : "memory");
  }
}
template <int U, class F>
__device__ __forceinline__ void gate_chunk(F xa, uint32_t qa) {
#pragma unroll 1
  for (int i0 = 0; i0 < 8; i0 += U) {
    uint32_t zz[U][4], qq[U][4];
#pragma unroll
    for (int i = 0; i < U; i++) { ldsm4t(zz[i], xa(i0 + i)); ldsm4(qq[i], qa + (i0 + i) * 512); }
#pragma unroll
    for (int i = 0; i < U; i++) stsm4(qa + (i0 + i) * 512, bmul(qq[i][0], zz[i][0]), bmul(qq[i][1], zz[i][1]), bmul(qq[i][2], zz[i][2]), bmul(qq[i][3], zz[i][3]));
  }
}

__device__ __forceinline__ void io_warp(const Params& p, uint32_t sb, int cidx, int wq) {
  const int lane = threadIdx.x & 31;
  const uint32_t io = sb + OFF_IO + wq * IOBUF, bkv = bar_addr(sb, B_KV + wq), bq = bar_addr(sb, B_Q + wq);
  auto load_kv = [&](int e) {
    __syncwarp();
    if (lane != 0) return;
    const int d0 = group_d0(cidx, e >> 1), row = (2 * wq + (e & 1)) * 256;
    if (e < 2 * GROUPS) {
      mbar_expect_tx(bkv, IO_Q);
      tma_ld2(io, &p.ak8, bkv, d0, row - 8);
      tma_ld2(io + IO_K, &p.ak, bkv, d0, row);
      tma_ld2(io + IO_V, &p.av, bkv, d0, row);
    } else {
      const uint32_t bar = bar_addr(sb, B_QLAST + 2 * wq + 1);
      mbar_expect_tx(bar, 4096);
      tma_ld2(io + IO_K, &p.aq, bar, group_d0(cidx, GROUPS - 1), row + 256);
    }
  };
  auto load_q = [&](int e) {
    __syncwarp();
    if (lane != 0) return;
    const uint32_t bar = e < 2 * GROUPS - 2 ? bq : bar_addr(sb, B_QLAST + 2 * wq);
    mbar_expect_tx(bar, 4096);
    tma_ld2(io + IO_Q, &p.aq, bar, group_d0(cidx, e >> 1), (2 * wq + (e & 1)) * 256);
  };
  load_kv(0);
  const uint32_t xl = sb + OFF_X + x_lane(lane) + wq * 1024, tl = io + t_lane(lane);
#pragma unroll 1
  for (int grp = -2; grp + 1 < GROUPS; grp++) {
    const bool more = grp + 2 < GROUPS;
    const Taps taps = load_taps(p, group_d0(cidx, more ? grp + 2 : 0), lane & 3);
    if (grp >= 0) mbar_wait_nap(bar_addr(sb, B_ZDONE + (grp & 1)), (grp >> 1) & 1);

#pragma unroll 1
    for (int i = 0; i < 2; i++) {
      const uint32_t xa = xl + (grp & 1) * XBUF + i * 512;
      if (grp >= 0) {
        mbar_wait_nap(bq, i);
        gate_chunk<4>([&](int u) { return xa + u * 64; }, tl + IO_Q);
      }
      if (more) {
        mbar_wait_nap(bkv, i);
        x_chunk<2>(taps, tl + IO_K, [&](int u) { return xa + u * 64; });
        load_kv(2 * (grp + 2) + i + 1);
        if (i == 1) warp_arrive(bar_addr(sb, B_XREADY + (grp & 1)), lane);
      }
      if (grp >= 0) {
        fence_async_smem();
        __syncwarp();
        if (lane == 0) {
          tma_st2(&p.ao, io + IO_Q, group_d0(cidx, grp), (2 * wq + i) * 256);
          bulk_commit();
          bulk_wait_read();
        }
      }
      if (2 * grp + i + 1 >= 0) load_q(2 * grp + i + 1);
    }
  }
  if (lane == 0) bulk_wait_all();
}

__device__ __forceinline__ void conv_warp(const Params& p, uint32_t sb, int cidx, int ch) {
  const int lane = threadIdx.x & 31;
  const uint32_t hE0 = sb + OFF_H + ch * HWARP, hO = hE0 + HCOPY;
  const uint32_t hbar = bar_addr(sb, B_HRAW + ch);
  auto fetch_h = [&](int grp) {
    if (lane == 0) {
      mbar_expect_tx(hbar, 4096);
      asm volatile("cp.async.bulk.shared::cluster.global.mbarrier::complete_tx::bytes [%0], [%1], %2, [%3];"
                   :: "r"(hE0 + (grp & 1) * 2 * HCOPY + 32), "l"(p.a_ssmk + (size_t)(group_d0(cidx, grp) + ch) * SEQ), "r"(4096), "r"(hbar) : "memory");
    }
  };
  fetch_h(0);
#pragma unroll 1
  for (int grp = 0; grp < GROUPS; grp++) {
    const uint32_t xc = sb + OFF_X + (grp & 1) * XBUF + ch * CHAN;
    const uint32_t D1 = __ldg(reinterpret_cast<const unsigned short*>(p.a_D + group_d0(cidx, grp) + ch));
    mbar_wait(hbar, grp & 1);
    const uint32_t hE = hE0 + (grp & 1) * 2 * HCOPY;
    if (grp + 1 < GROUPS) fetch_h(grp + 1);
    shift_filter<8>(hE, hO, lane);
    __syncwarp();
    const uint32_t ha = cv_h_lane(lane, hE, hO), xa = xc + cv_x_lane(lane);
    mbar_wait(bar_addr(sb, B_XREADY + (grp & 1)), (grp >> 1) & 1);
    if (grp == 0 && ch >= 4) __nanosleep(CONV_STAGGER_NS);

    float acc[16][4];
#pragma unroll
    for (int i = 0; i < 16; i++) { acc[i][0] = 0.f; acc[i][1] = 0.f; acc[i][2] = 0.f; acc[i][3] = 0.f; }
#pragma unroll 1
    for (int r = 0; r < 8; r++) {
      uint32_t fx[16][4], fh[16][2];
#pragma unroll
      for (int i = 0; i < 16; i++) { fh[i][0] = lds4(ha + i * 256 + r * 32); fh[i][1] = lds4(ha + i * 256 + r * 32 + 16); }
#pragma unroll
      for (int i = 0; i < 16; i++) ldsm4(fx[i], xa + i * 256 - r * 32);
#pragma unroll
      for (int sx = 0; sx < 16; sx++)
#pragma unroll
        for (int jj = 0; jj < 16 - sx; jj++) mma16816(acc[jj + sx], fx[sx], fh[jj][0], fh[jj][1]);
    }

    {
      uint32_t x[8][4], Dd;
      asm volatile("prmt.b32 %0, %1, %1, 0x1010;" : "=r"(Dd) : "r"(D1));
      const uint32_t ad = xc + (ZROWS + lane) * 16;
#pragma unroll
      for (int i = 0; i < 8; i++) ldsm4(x[i], ad + i * 512);
#pragma unroll
      for (int i = 0; i < 8; i++)
        stsm4(ad + i * 512, add_skip(pack_bf16(acc[2 * i][0], acc[2 * i][1]), x[i][0], Dd), add_skip(pack_bf16(acc[2 * i][2], acc[2 * i][3]), x[i][1], Dd),
              add_skip(pack_bf16(acc[2 * i + 1][0], acc[2 * i + 1][1]), x[i][2], Dd), add_skip(pack_bf16(acc[2 * i + 1][2], acc[2 * i + 1][3]), x[i][3], Dd));
    }
    if (grp + 1 < GROUPS) warp_arrive(bar_addr(sb, B_ZDONE + (grp & 1)), lane);
  }
  {
    mbar_wait(bar_addr(sb, B_QLAST + ch), 0);
    named_sync(CW_BAR, 256);
    const uint32_t qb = sb + OFF_IO + (ch >> 1) * IOBUF + ((ch & 1) ? IO_K : IO_Q);
    const uint32_t xa = sb + OFF_X + ((GROUPS - 1) & 1) * XBUF + x_lane(lane) + ch * 512;
    gate_chunk<8>([&](int u) { return xa + u * 64; }, qb + t_lane(lane));
    fence_async_smem();
    __syncwarp();
    if (lane == 0) { tma_st2(&p.ao, qb, group_d0(cidx, GROUPS - 1), ch * 256); bulk_commit(); bulk_wait_read(); }
  }
}

__device__ __forceinline__ void init(uint32_t sb) {
  if (threadIdx.x < 16 * ZROWS) sts16(sb + OFF_X + (threadIdx.x >> 4) * CHAN + (threadIdx.x & 15) * 16, 0, 0, 0, 0);
  if (threadIdx.x < 96) sts16(sb + OFF_H + (threadIdx.x >> 2) * HCOPY + (threadIdx.x & 1) * 16 + ((threadIdx.x & 2) ? 4128 : 0), 0, 0, 0, 0);
  if (threadIdx.x == 0) {
    for (int i = 0; i < 2; i++) { mbar_init(bar_addr(sb, B_XREADY + i), 4); mbar_init(bar_addr(sb, B_ZDONE + i), 8); }
    for (int i = 0; i < 4; i++) { mbar_init(bar_addr(sb, B_KV + i), 1); mbar_init(bar_addr(sb, B_Q + i), 1); }
    for (int i = 0; i < 8; i++) { mbar_init(bar_addr(sb, B_HRAW + i), 1); mbar_init(bar_addr(sb, B_QLAST + i), 1); }
    fence_async_smem();
  }
  named_sync(0, NTHREADS);
}
}

__device__ __forceinline__ void ssm_side_work(const Params& p, uint32_t sb, unsigned epoch) {
  const Role ro = get_role();
  const int h = ro.h, j = ro.j;
  const int lane = threadIdx.x & 31;
  const int d0 = D_SPARE + 8 * h, qt = q_tile(h, j, 1), cta = h * 8 + j;
  auto x4 = [&](uint32_t base, int u) { return base + (u >> 1) * 1024 + (lane & 7) * 128 + ((((u & 1) * 4 + (lane >> 3)) ^ (lane & 7)) << 4); };
  {
    const uint32_t xb = sb + P1_STG, kb = xb + 4096, hE = kb + 8320, hO = hE + CV_HCOPY, zero = hE + CV_XO, bar = bar_addr(sb, B_SIDE);
    if (lane == 0) {
      mbar_expect_tx(bar, 128 + 3 * 4096);
      tma_ld2(kb, &p.ak8, bar, d0, 256 * j - 8);
      tma_ld2(kb + 128, &p.ak, bar, d0, 256 * j);
      bulk_ld(hE + 32, p.a_ssmk + (size_t)(d0 + j) * SEQ, 4096, bar);
      __nanosleep(600);
      tma_ld2(kb + 128 + 4096, &p.av, bar, d0, 256 * j);
    }
    const ssm::Taps taps = ssm::load_taps(p, d0, lane & 3);
    const uint32_t Dd = (uint32_t)__ldg(reinterpret_cast<const unsigned short*>(p.a_D + d0 + j)) * 0x10001u;
    for (int i = 0; i < 4; i++) sts16(zero + i * 512 + lane * 16, 0, 0, 0, 0);
    if (lane < 8) sts16(hE + (lane >> 2) * CV_HCOPY + (lane & 1) * 16 + ((lane & 2) ? 4128 : 0), lane == 3 ? Dd : 0, 0, 0, 0);
    __syncwarp();
    mbar_wait_nap(bar, 0);
    ssm::x_chunk<1>(taps, kb + 128 + ssm::t_lane(lane), [&](int u) { return x4(xb, u); });
    ssm::shift_filter<2>(hE, hO, lane);
    fence_async_smem();
    __syncwarp();
    if (lane == 0) {
      tma_st3(&p.xsx, xb, 0, h * 8, CV_OWN + 4 * j);
      __nanosleep(200);
      tma_st2(&p.xso, hE, 0, cta * CV_LINES);
      for (int i = 0; i < 7; i++) { __nanosleep(200); tma_st2(&p.oz, zero, DA + i * 64, qt * 128 + (h & 7) * 16); }
      bulk_commit();
      bulk_wait_read();
      mbar_arrive(bar_addr(sb, B_SIDE + 1));
      bulk_wait_all();
      flag_signal(&g_flags.xs_ready[h].v);
      flag_signal_again(&g_flags.out_ready[qt].v);
      flag_wait(&g_flags.xs_ready[h].v, 8, epoch);
      fence_async_all();
      mbar_arrive(bar_addr(sb, B_XS));
    }
  }
  if (lane == 0) {
    for (int i = 0; i < 3; i++) {
      flag_wait(&g_flags.kv_ready[3 * h + i].v, 16, epoch);
      fence_async_all();
      mbar_arrive(bar_addr(sb, B_KV + i));
    }
    mbar_wait_nap(bar_addr(sb, B_CONV), 0);
    flag_signal(&g_flags.zs_ready[h].v);
    flag_wait(&g_flags.zs_ready[h].v, 8, epoch);
    flag_wait(&g_flags.out_ready[qt].v, 8, epoch);
    for (int i = 0; i < 2; i++) {
      if ((i == 0) == (h >= 8)) {
        mbar_wait_nap(bar_addr(sb, B_CTXD), 0);
        flag_signal(&g_flags.ctx_ready[cta].v);
      } else {
        flag_wait(&g_flags.ctx_ready[cta ^ 64].v, 1, epoch);
        fence_async_all();
        mbar_arrive(bar_addr(sb, B_CTXD + 1));
      }
    }
    asm volatile("red.relaxed.gpu.global.add.u64 [%0], 1;" :: "l"(&g_flags.done) : "memory");
  }
  __syncwarp();
  fence_async_all();
  const uint32_t qb = q_region(sb, 1) + 16384, zb = qb + 4096, bar = bar_addr(sb, B_GATE);
  mbar_wait_slow(bar_addr(sb, B_GFREE), 0);
  if (lane == 0) { mbar_expect_tx(bar, 8192); tma_ld2(qb, &p.aq, bar, d0, 256 * j); tma_ld3(zb, &p.xsx, bar, 0, h * 8, CV_OWN + 4 * j); }
  mbar_wait(bar, 0);
  ssm::gate_chunk<2>([&](int u) { return x4(zb, u); }, qb + ssm::t_lane(lane));
  fence_async_smem();
  __syncwarp();
  if (lane == 0) { tma_st2(&p.ao, qb, d0, 256 * j); bulk_commit(); bulk_wait_all(); }
}

__global__ void __cluster_dims__(2, 1, 1) __launch_bounds__(NTHREADS, 1)
concat_heads__ssm_conv_h3__compressed_kv_cla__prompt_kernel(uint8_t* xs, uint32_t one, const __grid_constant__ Params p) {
  if (threadIdx.x == 0) { prefetch_map(&p.wuk); prefetch_map(&p.ckv); }
  extern __shared__ uint8_t smem_raw[];
  const uint32_t sb = (smem_u32(smem_raw) + 1023) & ~1023u;
  const int warp = __shfl_sync(0xffffffffu, threadIdx.x >> 5, 0);
  const int wg = warp >> 2;
  const int cta = blockIdx.x;
  const bool attn = cta < NMAIN;
  if (attn && (threadIdx.x >> 5) == 4) {
    const Role ro = get_role();
    auto load = [&](int k) {
      const uint32_t full = bar_addr(sb, B_P1_FULL + k), dst = sb + k * P1_STAGE;
      mbar_expect_tx(full, P1_STAGE);
      tma_ld2(dst, &p.ckv, full, k * 64, kv_block(ro.j, 0) * 128);
      tma_ld3(dst + 16384, &p.wuk, full, 0, k * 64, ro.h * 4);
    };
    if (threadIdx.x == 128) {
      for (int i = 0; i < 4; i++) mbar_init(bar_addr(sb, B_P1_FULL + i), 1);
      asm volatile("fence.mbarrier_init.release.cluster;" ::: "memory");
      load(0);
    }
    __syncwarp();
    named_arrive(0, NTHREADS);
    if (threadIdx.x == 128) {
      for (int k = 1; k < EARLY_LD; k++) load(k);
    }
    __syncwarp();
  }
  const int lane = threadIdx.x & 31;
  if (wg == 0) {
    if (!attn) {
      asm volatile("setmaxnreg.dec.sync.aligned.u32 72;");
      if (one) { ssm::init(sb); ssm::io_warp(p, sb, cta - NMAIN, fresh_warp()); }
      return;
    }
    asm volatile("setmaxnreg.dec.sync.aligned.u32 40;");
    named_arrive(PP_BAR + 1, 256);
    if (warp == 2) {
      if (lane == 0) {
        for (int i = 0; i < 4; i++) mbar_init(bar_addr(sb, B_P1_EMPTY + i), 8);
        for (int i = 0; i < NSLOT; i++) {
          mbar_init(bar_addr(sb, B_RG_FULL + i), 1); mbar_init(bar_addr(sb, B_RG_EMPTY + i), 8);
        }
        for (int i = 0; i < 2; i++) { mbar_init(bar_addr(sb, B_ST_FULL + i), 4); mbar_init(bar_addr(sb, B_ST_EMPTY + i), 1); }
        mbar_init(bar_addr(sb, B_XS), 1); mbar_init(bar_addr(sb, B_SIDE), 1); mbar_init(bar_addr(sb, B_SIDE + 1), 1);
        mbar_init(bar_addr(sb, B_CTXD), 2); mbar_init(bar_addr(sb, B_CTXD + 1), 1); mbar_init(bar_addr(sb, B_CONV), 8); mbar_init(bar_addr(sb, B_GATE), 1); mbar_init(bar_addr(sb, B_GFREE), 1);
        for (int i = 0; i < 3; i++) mbar_init(bar_addr(sb, B_KV + i), 1);
        for (int i = 0; i < 8; i++) mbar_init(bar_addr(sb, B_CTXS + i), 4);
        for (int i = 0; i < 4; i++) { mbar_arrive(bar_addr(sb, B_RG_FULL + i)); if (i < 3) mbar_arrive_n(bar_addr(sb, B_RG_EMPTY + i), 8); }
        for (int i = 0; i < 4; i++) { mbar_init(bar_addr(sb, B_S2_FULL + i), 4); mbar_init(bar_addr(sb, B_S2_EMPTY + i), 1); }
        for (int i = 0; i < 2; i++) { mbar_init(bar_addr(sb, B_QFREE + i), 4); mbar_init(bar_addr(sb, B_CTXF + i), 1); }
        asm volatile("fence.mbarrier_init.release.cluster;" ::: "memory");
      }
      __syncwarp();
      named_arrive(0, NTHREADS);
    } else {
      named_sync(0, NTHREADS);
    }
    if (warp == 0) {
      if (lane == 0) producer_main(p, sb);
    } else if (warp < 3) {
      storer_main(p, sb);
    } else {
      const unsigned epoch = load_epoch();
      mbar_wait(bar_addr(sb, B_P1_FULL + 3), 0);
      __nanosleep(SIDE_DELAY_NS);
      ssm_side_work(p, sb, epoch);
    }
  } else {
    if (attn) {
      asm volatile("setmaxnreg.inc.sync.aligned.u32 232;");
      if (one) consumer_main(p, sb, xs, one);
    } else {
      asm volatile("setmaxnreg.inc.sync.aligned.u32 216;");
      if (one) { ssm::init(sb); ssm::conv_warp(p, sb, cta - NMAIN, fresh_warp() - 4); }
    }
  }
}

typedef CUresult (*EncodeTiledFn)(CUtensorMap*, CUtensorMapDataType, cuuint32_t, void*, const cuuint64_t*, const cuuint64_t*,
                                  const cuuint32_t*, const cuuint32_t*, CUtensorMapInterleave, CUtensorMapSwizzle,
                                  CUtensorMapL2promotion, CUtensorMapFloatOOBfill);

void make_map(EncodeTiledFn enc, CUtensorMap* m, const void* ptr, int rank, const uint64_t* dims, const uint64_t* strides, const uint32_t* box) {
  cuuint64_t d[3], s[2]; cuuint32_t b[3], e[3] = {1, 1, 1};
  for (int i = 0; i < rank; i++) { d[i] = dims[i]; b[i] = box[i]; if (i) s[i - 1] = strides[i - 1]; }
  enc(m, CU_TENSOR_MAP_DATA_TYPE_BFLOAT16, rank, const_cast<void*>(ptr), d, s, b, e, CU_TENSOR_MAP_INTERLEAVE_NONE,
      CU_TENSOR_MAP_SWIZZLE_128B, CU_TENSOR_MAP_L2_PROMOTION_L2_256B, CU_TENSOR_MAP_FLOAT_OOB_FILL_NONE);
}
void map2(EncodeTiledFn enc, CUtensorMap* m, const void* ptr, uint64_t cols, uint64_t rows, uint32_t bc, uint32_t br) {
  const uint64_t dims[2] = {cols, rows}, st[1] = {cols * 2}; const uint32_t box[2] = {bc, br};
  make_map(enc, m, ptr, 2, dims, st, box);
}
void map2_plain(EncodeTiledFn enc, CUtensorMap* m, const void* ptr, uint64_t cols, uint64_t rows, uint32_t bc, uint32_t br) {
  cuuint64_t d[2] = {cols, rows}, st[1] = {cols * 2}; cuuint32_t b[2] = {bc, br}, e[2] = {1, 1};
  enc(m, CU_TENSOR_MAP_DATA_TYPE_BFLOAT16, 2, const_cast<void*>(ptr), d, st, b, e, CU_TENSOR_MAP_INTERLEAVE_NONE,
      CU_TENSOR_MAP_SWIZZLE_NONE, CU_TENSOR_MAP_L2_PROMOTION_L2_128B, CU_TENSOR_MAP_FLOAT_OOB_FILL_NONE);
}
void map3(EncodeTiledFn enc, CUtensorMap* m, const void* ptr, uint64_t rows, uint32_t nblk) {
  const uint64_t dims[3] = {64, rows, 64}, st[2] = {8192, 128}; const uint32_t box[3] = {64, 64, nblk};
  make_map(enc, m, ptr, 3, dims, st, box);
}

}

extern "C" void kernel_launch(void* const* d_in, const int* in_sizes, int n_in, void* d_out, int out_size) {
  (void)in_sizes; (void)n_in; (void)out_size;
  static EncodeTiledFn enc = nullptr;
  static void *tiles_ptr = nullptr, *xs_ptr = nullptr;
  if (!enc) {
    void* fn = nullptr; cudaDriverEntryPointQueryResult qr;
    cudaGetDriverEntryPoint("cuTensorMapEncodeTiled", &fn, cudaEnableDefault, &qr);
    enc = (EncodeTiledFn)fn;
    cudaGetSymbolAddress(&tiles_ptr, g_tiles);
    cudaGetSymbolAddress(&xs_ptr, g_xs);
    cudaFuncSetAttribute(concat_heads__ssm_conv_h3__compressed_kv_cla__prompt_kernel, cudaFuncAttributeMaxDynamicSharedMemorySize, SMEM_BYTES);
  }
  Params p;
  map2_plain(enc, &p.aq, d_in[0], DA, SEQ, 8, 256);
  map2_plain(enc, &p.ak, d_in[1], DA, SEQ, 8, 256);
  map2_plain(enc, &p.ak8, d_in[1], DA, SEQ, 8, 8);
  map2_plain(enc, &p.av, d_in[2], DA, SEQ, 8, 256);
  map2_plain(enc, &p.ao, d_out, OUTW, SEQ, 8, 256);
  p.a_shift = (const bf16*)d_in[3]; p.a_ssmk = (const bf16*)d_in[4]; p.a_D = (const bf16*)d_in[5];
  map2(enc, &p.x, d_in[6], DM, SEQ, 64, 128);
  map2(enc, &p.ckv, d_in[7], DC, SEQ, 64, 128);
  map3(enc, &p.wq, d_in[8], DM, 4);
  map2_plain(enc, &p.wqp, d_in[8], NH * HD, DM, 256, 4);
  map2_plain(enc, &p.wkp, d_in[9], NH * HD, DC, 256, 8);
  map2_plain(enc, &p.wvp, d_in[10], NH * HD, DC, 256, 8);
  map2_plain(enc, &p.ckp, d_in[7], DC, SEQ, 128, 8);
  map2_plain(enc, &p.wop, d_in[11], DM, NH * HD, 64, 32);
  map2_plain(enc, &p.xp, d_in[6], DM, SEQ, 64, 16);
  map3(enc, &p.wuk, d_in[9], DC, 4);
  map3(enc, &p.wuv, d_in[10], DC, 4);
  map2(enc, &p.wo, d_in[11], DM, NH * HD, 64, 256);
  map2(enc, &p.part, d_out, OUTW, SEQ, 64, 64);
  map2_plain(enc, &p.tl, tiles_ptr, 64, (uint64_t)NTILES * 256, 64, 256);
  map2_plain(enc, &p.ts, tiles_ptr, 64, (uint64_t)NTILES * 256, 64, 16);
  map2_plain(enc, &p.xs3, xs_ptr, 64, NMAIN * CV_LINES, 64, CV_LINES / 3);
  map2_plain(enc, &p.xso, xs_ptr, 64, NMAIN * CV_LINES, 64, CV_OWN);
  {
    const uint64_t dims[3] = {64, NMAIN, CV_LINES}, st[2] = {CV_BYTES, 128}; const uint32_t box[3] = {64, 8, 4};
    make_map(enc, &p.xsx, xs_ptr, 3, dims, st, box);
  }
  map2_plain(enc, &p.oz, d_out, OUTW, SEQ, 64, 16);
  concat_heads__ssm_conv_h3__compressed_kv_cla__prompt_kernel<<<NCTA, NTHREADS, SMEM_BYTES>>>((uint8_t*)xs_ptr, 1u, p);
}
```
